```python
import torch

def _softmax(x, axis=-1):
    return torch.softmax(x, dim=axis)
def _gelu(x):
    return torch.nn.functional.gelu(x, approximate="tanh")
def _silu(x):
    return torch.nn.functional.silu(x)
def _sigmoid(x):
    return torch.sigmoid(x)
def _layernorm(x, axis=-1, eps=1e-5):
    m = x.mean(dim=axis, keepdim=True)
    v = x.var(dim=axis, keepdim=True, unbiased=False)
    return (x - m) / torch.sqrt(v + eps)
def _scatter_add(tgt, idx, src, axis=0):
    return tgt.clone().index_add_(axis, idx, src)
def _segment_sum(src, seg, n):
    out = torch.zeros((n,) + src.shape[1:], dtype=src.dtype)
    return out.index_add_(0, seg, src)
def _pad(x, pw):
    flat = tuple(v for pair in reversed(pw) for v in pair)
    return torch.nn.functional.pad(x, flat)

kernel_name = 'recurrent_scan__sliding_block_cached__dense_activation_relu__prompt'

def setup_inputs():

    _w = (lambda a: (lambda t: t.to(torch.bfloat16) if t.is_floating_point() else t)(torch.as_tensor(a)))
    def _A_setup():
        B, Sq, D = 1, 2048, 1024
        Hq, Hkv, Sk, Dh = 32, 4, 2048, 128
        assert Hq % Hkv == 0, (Hq, Hkv)
        return {
            "x": _w((lambda *s: torch.randn(*s, dtype=torch.bfloat16) * 0.05)(B, Sq, D)),
            "k_cache": _w((lambda *s: torch.randn(*s, dtype=torch.bfloat16) * 0.8)(B, Hkv, Sk, Dh)),
            "v_cache": _w((lambda *s: torch.randn(*s, dtype=torch.bfloat16) * 0.2)(B, Hkv, Sk, Dh)),
            "wq": _w((lambda *s: torch.randn(*s, dtype=torch.bfloat16) * 0.8)(D, Hq * Dh) * (D ** -0.5)),
            "wo": _w((lambda *s: torch.randn(*s, dtype=torch.bfloat16) * 0.2)(Hq * Dh, D) * ((Hq * Dh) ** -0.5)),
        }
    _A_in = _A_setup()

    def _B_setup():
        B, S, D, Dff = 1, 2048, 1024, 3584
        return {
            "x": _w((lambda *s: torch.randn(*s, dtype=torch.bfloat16) * 0.05)(B, S, D)),
            "w1": _w((lambda *s: torch.randn(*s, dtype=torch.bfloat16) * 0.1)(D, Dff)),
            "w2": _w((lambda *s: torch.randn(*s, dtype=torch.bfloat16) * 0.1)(Dff, D)),
        }
    _B_in = _B_setup()

    return {
        "A_x": _A_in["x"],
        "A_k_cache": _A_in["k_cache"],
        "A_v_cache": _A_in["v_cache"],
        "A_wq": _A_in["wq"],
        "A_wo": _A_in["wo"],
        "B_x": _B_in["x"],
        "B_w1": _B_in["w1"],
        "B_w2": _B_in["w2"],
    }

def reference(A_x, A_k_cache, A_v_cache, A_wq, A_wo, B_x, B_w1, B_w2):
    def _A_ref(x, k_cache, v_cache, wq, wo):
        B, Sq, D = x.shape
        Hq, Dh = 32, 128
        Hkv, Sk = k_cache.shape[1], k_cache.shape[2]
        W = min(4096, max(256, Sk // 4))
        rep = Hq // Hkv
        q = (lambda x, *d: x.permute(*d))((x @ wq).reshape(B, Sq, Hq, Dh), 0, 2, 1, 3)
        k = (lambda x, n, axis: torch.repeat_interleave(x, n, dim=axis))(k_cache[:, :, Sk - W:, :], rep, axis=1)
        v = (lambda x, n, axis: torch.repeat_interleave(x, n, dim=axis))(v_cache[:, :, Sk - W:, :], rep, axis=1)
        scores = torch.einsum("bhqd,bhkd->bhqk", q, k) * (Dh ** -0.5)
        p = _softmax(scores, axis=-1)
        o = torch.einsum("bhqk,bhkd->bhqd", p, v)
        return (lambda x, *d: x.permute(*d))(o, 0, 2, 1, 3).reshape(B, Sq, Hq * Dh) @ wo

    def _B_ref(x, w1, w2):
        h = torch.einsum("bsd,df->bsf", x, w1)
        zero = torch.zeros_like(h)
        h = torch.maximum(h, zero)
        return torch.einsum("bsf,fd->bsd", h, w2)

    x = A_x
    xn = _layernorm(x, axis=-1)
    s = _A_ref(xn, A_k_cache, A_v_cache, A_wq, A_wo)
    g = _silu(_B_ref(xn, B_w1, B_w2))
    return x + s * g
```

```cpp
#include <cuda_runtime.h>
#include <cuda_bf16.h>
#include <cuda.h>
#include <stdint.h>

namespace {

constexpr int SEQ    = 2048;
constexpr int DM     = 1024;
constexpr int NQ     = 4096;
constexpr int DFF    = 3584;
constexpr int SK     = 2048;
constexpr int WIN    = 512;
constexpr int KV0    = SK - WIN;
constexpr int C_XN = 0, C_O = 1024, C_H = 5120, C_G = 8704, ACT_W = 9728;

#define HS0 192
#define HS1 192
#define HF0 256
#define HF1 256
static_assert(4 * (HS0 + HS1 + HF0 + HF1) == DFF, "H split");

constexpr int NSLOT = 12, SLOT = 16384, NBAR = 8;
constexpr int SM_STG = NSLOT * SLOT;
constexpr int SM_BAR = SM_STG + 2 * 16384;
constexpr int SMEM_BYTES = SM_BAR + 256 + 1024;
constexpr int B_FULL = 0, B_EMPTY = 64, B_SFULL = 128, B_SEMPTY = 144, B_DONE = 160;

constexpr int NCLUSTER = 64;

struct Flags {
  unsigned ln[16][32];
  unsigned h[16][32];
  unsigned o[16][32];
  unsigned g[16][32];
  unsigned epoch[160];
};
__device__ __nv_bfloat16 g_act[(size_t)SEQ * ACT_W];
__device__ Flags g_flags;

struct Params {
  CUtensorMap act_ld, act_st, x_ld, out_st, k_ld, v_ld, wq, w1b4, w1b3, wo, w2;
  const __nv_bfloat16* x;
  __nv_bfloat16* act;
  Flags* flags;
};

__device__ __forceinline__ uint32_t smem_u32(const void* p) { return (uint32_t)__cvta_generic_to_shared(p); }
__device__ __forceinline__ void mbar_init(uint32_t bar, uint32_t cnt) {
  asm volatile("mbarrier.init.shared::cta.b64 [%0], %1;" ::"r"(bar), "r"(cnt) : "memory");
}
__device__ __forceinline__ bool mbar_try(uint32_t bar, uint32_t parity) {
  uint32_t ok;
  asm volatile("{\n.reg .pred p;\nmbarrier.try_wait.parity.shared::cta.b64 p, [%1], %2;\nselp.u32 %0, 1, 0, p;\n}\n"
               : "=r"(ok) : "r"(bar), "r"(parity) : "memory");
  return ok;
}
__device__ __forceinline__ void mbar_wait(uint32_t bar, uint32_t parity) {
  asm volatile("{\n.reg .pred p;\nWAIT_%=:\nmbarrier.try_wait.parity.shared::cta.b64 p, [%0], %1;\n@p bra DONE_%=;\nbra WAIT_%=;\nDONE_%=:\n}\n"
               ::"r"(bar), "r"(parity) : "memory");
}
__device__ __forceinline__ void mbar_arrive(uint32_t bar) {
  asm volatile("mbarrier.arrive.shared::cta.b64 _, [%0];" ::"r"(bar) : "memory");
}
__device__ __forceinline__ void mbar_arrive_cluster(uint32_t cluster_addr) {
  asm volatile("mbarrier.arrive.shared::cluster.b64 _, [%0];" ::"r"(cluster_addr) : "memory");
}
__device__ __forceinline__ void mbar_expect_tx(uint32_t bar, uint32_t bytes) {
  asm volatile("mbarrier.arrive.expect_tx.shared::cta.b64 _, [%0], %1;" ::"r"(bar), "r"(bytes) : "memory");
}
__device__ __forceinline__ uint32_t mapa(uint32_t addr, uint32_t rank) {
  uint32_t r;
  asm("mapa.shared::cluster.u32 %0, %1, %2;" : "=r"(r) : "r"(addr), "r"(rank));
  return r;
}
__device__ __forceinline__ void cluster_arrive() { asm volatile("barrier.cluster.arrive.relaxed.aligned;" ::: "memory"); }
__device__ __forceinline__ void cluster_wait() { asm volatile("barrier.cluster.wait.acquire.aligned;" ::: "memory"); }
__device__ __forceinline__ void bar_sync(int id, int n) { asm volatile("bar.sync %0, %1;" ::"r"(id), "r"(n) : "memory"); }
__device__ __forceinline__ void bar_arrive(int id, int n) { asm volatile("bar.arrive %0, %1;" ::"r"(id), "r"(n) : "memory"); }
__device__ __forceinline__ void fence_async_smem() { asm volatile("fence.proxy.async.shared::cta;" ::: "memory"); }
__device__ __forceinline__ void fence_async_all() { asm volatile("fence.proxy.async.global;" ::: "memory"); }

__device__ __forceinline__ void tma_ld2(uint32_t dst, const CUtensorMap* m, uint32_t bar, int c0, int c1) {
  asm volatile("cp.async.bulk.tensor.2d.shared::cluster.global.mbarrier::complete_tx::bytes [%0], [%1, {%3, %4}], [%2];"
               ::"r"(dst), "l"(m), "r"(bar), "r"(c0), "r"(c1) : "memory");
}
__device__ __forceinline__ void tma_ld2_mc(uint32_t dst, const CUtensorMap* m, uint32_t bar, int c0, int c1) {
  asm volatile("cp.async.bulk.tensor.2d.shared::cluster.global.mbarrier::complete_tx::bytes.multicast::cluster [%0], [%1, {%3, %4}], [%2], %5;"
               ::"r"(dst), "l"(m), "r"(bar), "r"(c0), "r"(c1), "h"((uint16_t)3) : "memory");
}
__device__ __forceinline__ void tma_ld3_mc(uint32_t dst, const CUtensorMap* m, uint32_t bar, int c0, int c1, int c2) {
  asm volatile("cp.async.bulk.tensor.3d.shared::cluster.global.mbarrier::complete_tx::bytes.multicast::cluster [%0], [%1, {%3, %4, %5}], [%2], %6;"
               ::"r"(dst), "l"(m), "r"(bar), "r"(c0), "r"(c1), "r"(c2), "h"((uint16_t)3) : "memory");
}
__device__ __forceinline__ void tma_st2(const CUtensorMap* m, uint32_t src, int c0, int c1) {
  asm volatile("cp.async.bulk.tensor.2d.global.shared::cta.bulk_group [%0, {%2, %3}], [%1];"
               ::"l"(m), "r"(src), "r"(c0), "r"(c1) : "memory");
}
__device__ __forceinline__ void tma_pf3(const CUtensorMap* m, int c0, int c1, int c2) {
  asm volatile("cp.async.bulk.prefetch.tensor.3d.L2.global [%0, {%1, %2, %3}];" ::"l"(m), "r"(c0), "r"(c1), "r"(c2) : "memory");
}
__device__ __forceinline__ void bulk_commit() { asm volatile("cp.async.bulk.commit_group;" ::: "memory"); }
__device__ __forceinline__ void bulk_wait_read0() { asm volatile("cp.async.bulk.wait_group.read 0;" ::: "memory"); }
__device__ __forceinline__ void bulk_wait0() { asm volatile("cp.async.bulk.wait_group 0;" ::: "memory"); }
__device__ __forceinline__ void prefetch_map(const CUtensorMap* m) {
  asm volatile("prefetch.tensormap [%0];" ::"l"(m) : "memory");
}
__device__ __forceinline__ unsigned ld_acquire(const unsigned* p) {
  unsigned v;
  asm volatile("ld.acquire.gpu.global.u32 %0, [%1];" : "=r"(v) : "l"(p) : "memory");
  return v;
}
__device__ __forceinline__ void red_release(unsigned* p, unsigned v) {
  asm volatile("red.release.gpu.global.add.u32 [%0], %1;" ::"l"(p), "r"(v) : "memory");
}
__device__ __forceinline__ void wg_fence() { asm volatile("wgmma.fence.sync.aligned;" ::: "memory"); }
__device__ __forceinline__ void wg_commit() { asm volatile("wgmma.commit_group.sync.aligned;" ::: "memory"); }
template <int N> __device__ __forceinline__ void wg_wait() { asm volatile("wgmma.wait_group.sync.aligned %0;" ::"n"(N) : "memory"); }
template <int N> __device__ __forceinline__ void fence_regs(float (&d)[N]) {
#pragma unroll
  for (int i = 0; i < N; i++) asm volatile("" : "+f"(d[i])::"memory");
}
template <int N> __device__ __forceinline__ void fence_regs(uint32_t (&d)[N]) {
#pragma unroll
  for (int i = 0; i < N; i++) asm volatile("" : "+r"(d[i])::"memory");
}
__device__ __forceinline__ uint64_t mkdesc(uint32_t addr, uint32_t lbo, uint32_t sbo) {
  return (uint64_t)((addr & 0x3FFFF) >> 4) | ((uint64_t)(lbo >> 4) << 16) | ((uint64_t)(sbo >> 4) << 32) | (1ull << 62);
}
__device__ __forceinline__ uint32_t pack_bf16(float lo, float hi) {
  uint32_t r;
  asm("cvt.rn.bf16x2.f32 %0, %1, %2;" : "=r"(r) : "f"(hi), "f"(lo));
  return r;
}
__device__ __forceinline__ uint32_t pack_bf16_relu(float lo, float hi) {
  uint32_t r;
  asm("cvt.rn.relu.bf16x2.f32 %0, %1, %2;" : "=r"(r) : "f"(hi), "f"(lo));
  return r;
}
__device__ __forceinline__ float bf_lo(uint32_t v) { return __uint_as_float(v << 16); }
__device__ __forceinline__ float bf_hi(uint32_t v) { return __uint_as_float(v & 0xFFFF0000u); }
__device__ __forceinline__ float bf_round(float v) { return __bfloat162float(__float2bfloat16_rn(v)); }
__device__ __forceinline__ float ex2(float x) {
  float r;
  asm("ex2.approx.ftz.f32 %0, %1;" : "=f"(r) : "f"(x));
  return r;
}
__device__ __forceinline__ void stsm4(uint32_t addr, uint32_t r0, uint32_t r1, uint32_t r2, uint32_t r3) {
  asm volatile("stmatrix.sync.aligned.m8n8.x4.shared.b16 [%0], {%1, %2, %3, %4};" ::"r"(addr), "r"(r0), "r"(r1), "r"(r2), "r"(r3) : "memory");
}
__device__ __forceinline__ void ldsm4(uint32_t addr, uint32_t& r0, uint32_t& r1, uint32_t& r2, uint32_t& r3) {
  asm volatile("ldmatrix.sync.aligned.m8n8.x4.shared.b16 {%0, %1, %2, %3}, [%4];" : "=r"(r0), "=r"(r1), "=r"(r2), "=r"(r3) : "r"(addr) : "memory");
}
__device__ __forceinline__ void sts128(uint32_t addr, uint32_t r0, uint32_t r1, uint32_t r2, uint32_t r3) {
  asm volatile("st.shared.v4.b32 [%0], {%1, %2, %3, %4};" ::"r"(addr), "r"(r0), "r"(r1), "r"(r2), "r"(r3) : "memory");
}
__device__ __forceinline__ void lds128(uint32_t addr, uint32_t& r0, uint32_t& r1, uint32_t& r2, uint32_t& r3) {
  asm volatile("ld.shared.v4.b32 {%0, %1, %2, %3}, [%4];" : "=r"(r0), "=r"(r1), "=r"(r2), "=r"(r3) : "r"(addr) : "memory");
}
__device__ __forceinline__ unsigned long long gtime() {
  unsigned long long t;
  asm volatile("mov.u64 %0, %globaltimer;" : "=l"(t));
  return t;
}

__device__ __forceinline__ void wgmma_ss_n256_tb(float (&d)[128], uint64_t da, uint64_t db, uint32_t sc) {
  asm volatile("{\n.reg .pred p;\nsetp.ne.b32 p, %130, 0;\n"
    "wgmma.mma_async.sync.aligned.m64n256k16.f32.bf16.bf16 "
    "{%0, %1, %2, %3, %4, %5, %6, %7, %8, %9, %10, %11, %12, %13, %14, %15, %16, %17, %18, %19, %20, %21, %22, %23, %24, %25, %26, %27, %28, %29, %30, %31, %32, %33, %34, %35, %36, %37, %38, %39, %40, %41, %42, %43, %44, %45, %46, %47, %48, %49, %50, %51, %52, %53, %54, %55, %56, %57, %58, %59, %60, %61, %62, %63, %64, %65, %66, %67, %68, %69, %70, %71, %72, %73, %74, %75, %76, %77, %78, %79, %80, %81, %82, %83, %84, %85, %86, %87, %88, %89, %90, %91, %92, %93, %94, %95, %96, %97, %98, %99, %100, %101, %102, %103, %104, %105, %106, %107, %108, %109, %110, %111, %112, %113, %114, %115, %116, %117, %118, %119, %120, %121, %122, %123, %124, %125, %126, %127}, %128, %129, p, 1, 1, 0, 1;\n}\n"
    : "+f"(d[0]), "+f"(d[1]), "+f"(d[2]), "+f"(d[3]), "+f"(d[4]), "+f"(d[5]), "+f"(d[6]), "+f"(d[7]), "+f"(d[8]), "+f"(d[9]), "+f"(d[10]), "+f"(d[11]), "+f"(d[12]), "+f"(d[13]), "+f"(d[14]), "+f"(d[15]), "+f"(d[16]), "+f"(d[17]), "+f"(d[18]), "+f"(d[19]), "+f"(d[20]), "+f"(d[21]), "+f"(d[22]), "+f"(d[23]), "+f"(d[24]), "+f"(d[25]), "+f"(d[26]), "+f"(d[27]), "+f"(d[28]), "+f"(d[29]), "+f"(d[30]), "+f"(d[31]), "+f"(d[32]), "+f"(d[33]), "+f"(d[34]), "+f"(d[35]), "+f"(d[36]), "+f"(d[37]), "+f"(d[38]), "+f"(d[39]), "+f"(d[40]), "+f"(d[41]), "+f"(d[42]), "+f"(d[43]), "+f"(d[44]), "+f"(d[45]), "+f"(d[46]), "+f"(d[47]), "+f"(d[48]), "+f"(d[49]), "+f"(d[50]), "+f"(d[51]), "+f"(d[52]), "+f"(d[53]), "+f"(d[54]), "+f"(d[55]), "+f"(d[56]), "+f"(d[57]), "+f"(d[58]), "+f"(d[59]), "+f"(d[60]), "+f"(d[61]), "+f"(d[62]), "+f"(d[63]), "+f"(d[64]), "+f"(d[65]), "+f"(d[66]), "+f"(d[67]), "+f"(d[68]), "+f"(d[69]), "+f"(d[70]), "+f"(d[71]), "+f"(d[72]), "+f"(d[73]), "+f"(d[74]), "+f"(d[75]), "+f"(d[76]), "+f"(d[77]), "+f"(d[78]), "+f"(d[79]), "+f"(d[80]), "+f"(d[81]), "+f"(d[82]), "+f"(d[83]), "+f"(d[84]), "+f"(d[85]), "+f"(d[86]), "+f"(d[87]), "+f"(d[88]), "+f"(d[89]), "+f"(d[90]), "+f"(d[91]), "+f"(d[92]), "+f"(d[93]), "+f"(d[94]), "+f"(d[95]), "+f"(d[96]), "+f"(d[97]), "+f"(d[98]), "+f"(d[99]), "+f"(d[100]), "+f"(d[101]), "+f"(d[102]), "+f"(d[103]), "+f"(d[104]), "+f"(d[105]), "+f"(d[106]), "+f"(d[107]), "+f"(d[108]), "+f"(d[109]), "+f"(d[110]), "+f"(d[111]), "+f"(d[112]), "+f"(d[113]), "+f"(d[114]), "+f"(d[115]), "+f"(d[116]), "+f"(d[117]), "+f"(d[118]), "+f"(d[119]), "+f"(d[120]), "+f"(d[121]), "+f"(d[122]), "+f"(d[123]), "+f"(d[124]), "+f"(d[125]), "+f"(d[126]), "+f"(d[127])
    : "l"(da), "l"(db), "r"(sc));
}
__device__ __forceinline__ void wgmma_ss_n192_tb(float (&d)[128], uint64_t da, uint64_t db, uint32_t sc) {
  asm volatile("{\n.reg .pred p;\nsetp.ne.b32 p, %98, 0;\n"
    "wgmma.mma_async.sync.aligned.m64n192k16.f32.bf16.bf16 "
    "{%0, %1, %2, %3, %4, %5, %6, %7, %8, %9, %10, %11, %12, %13, %14, %15, %16, %17, %18, %19, %20, %21, %22, %23, %24, %25, %26, %27, %28, %29, %30, %31, %32, %33, %34, %35, %36, %37, %38, %39, %40, %41, %42, %43, %44, %45, %46, %47, %48, %49, %50, %51, %52, %53, %54, %55, %56, %57, %58, %59, %60, %61, %62, %63, %64, %65, %66, %67, %68, %69, %70, %71, %72, %73, %74, %75, %76, %77, %78, %79, %80, %81, %82, %83, %84, %85, %86, %87, %88, %89, %90, %91, %92, %93, %94, %95}, %96, %97, p, 1, 1, 0, 1;\n}\n"
    : "+f"(d[0]), "+f"(d[1]), "+f"(d[2]), "+f"(d[3]), "+f"(d[4]), "+f"(d[5]), "+f"(d[6]), "+f"(d[7]), "+f"(d[8]), "+f"(d[9]), "+f"(d[10]), "+f"(d[11]), "+f"(d[12]), "+f"(d[13]), "+f"(d[14]), "+f"(d[15]), "+f"(d[16]), "+f"(d[17]), "+f"(d[18]), "+f"(d[19]), "+f"(d[20]), "+f"(d[21]), "+f"(d[22]), "+f"(d[23]), "+f"(d[24]), "+f"(d[25]), "+f"(d[26]), "+f"(d[27]), "+f"(d[28]), "+f"(d[29]), "+f"(d[30]), "+f"(d[31]), "+f"(d[32]), "+f"(d[33]), "+f"(d[34]), "+f"(d[35]), "+f"(d[36]), "+f"(d[37]), "+f"(d[38]), "+f"(d[39]), "+f"(d[40]), "+f"(d[41]), "+f"(d[42]), "+f"(d[43]), "+f"(d[44]), "+f"(d[45]), "+f"(d[46]), "+f"(d[47]), "+f"(d[48]), "+f"(d[49]), "+f"(d[50]), "+f"(d[51]), "+f"(d[52]), "+f"(d[53]), "+f"(d[54]), "+f"(d[55]), "+f"(d[56]), "+f"(d[57]), "+f"(d[58]), "+f"(d[59]), "+f"(d[60]), "+f"(d[61]), "+f"(d[62]), "+f"(d[63]), "+f"(d[64]), "+f"(d[65]), "+f"(d[66]), "+f"(d[67]), "+f"(d[68]), "+f"(d[69]), "+f"(d[70]), "+f"(d[71]), "+f"(d[72]), "+f"(d[73]), "+f"(d[74]), "+f"(d[75]), "+f"(d[76]), "+f"(d[77]), "+f"(d[78]), "+f"(d[79]), "+f"(d[80]), "+f"(d[81]), "+f"(d[82]), "+f"(d[83]), "+f"(d[84]), "+f"(d[85]), "+f"(d[86]), "+f"(d[87]), "+f"(d[88]), "+f"(d[89]), "+f"(d[90]), "+f"(d[91]), "+f"(d[92]), "+f"(d[93]), "+f"(d[94]), "+f"(d[95])
    : "l"(da), "l"(db), "r"(sc));
}
__device__ __forceinline__ void wgmma_rs_n128(float (&d)[64], uint32_t a0, uint32_t a1, uint32_t a2, uint32_t a3, uint64_t db, uint32_t sc) {
  asm volatile("{\n.reg .pred p;\nsetp.ne.b32 p, %69, 0;\n"
    "wgmma.mma_async.sync.aligned.m64n128k16.f32.bf16.bf16 "
    "{%0, %1, %2, %3, %4, %5, %6, %7, %8, %9, %10, %11, %12, %13, %14, %15, %16, %17, %18, %19, %20, %21, %22, %23, %24, %25, %26, %27, %28, %29, %30, %31, %32, %33, %34, %35, %36, %37, %38, %39, %40, %41, %42, %43, %44, %45, %46, %47, %48, %49, %50, %51, %52, %53, %54, %55, %56, %57, %58, %59, %60, %61, %62, %63}, {%64, %65, %66, %67}, %68, p, 1, 1, 0;\n}\n"
    : "+f"(d[0]), "+f"(d[1]), "+f"(d[2]), "+f"(d[3]), "+f"(d[4]), "+f"(d[5]), "+f"(d[6]), "+f"(d[7]), "+f"(d[8]), "+f"(d[9]), "+f"(d[10]), "+f"(d[11]), "+f"(d[12]), "+f"(d[13]), "+f"(d[14]), "+f"(d[15]), "+f"(d[16]), "+f"(d[17]), "+f"(d[18]), "+f"(d[19]), "+f"(d[20]), "+f"(d[21]), "+f"(d[22]), "+f"(d[23]), "+f"(d[24]), "+f"(d[25]), "+f"(d[26]), "+f"(d[27]), "+f"(d[28]), "+f"(d[29]), "+f"(d[30]), "+f"(d[31]), "+f"(d[32]), "+f"(d[33]), "+f"(d[34]), "+f"(d[35]), "+f"(d[36]), "+f"(d[37]), "+f"(d[38]), "+f"(d[39]), "+f"(d[40]), "+f"(d[41]), "+f"(d[42]), "+f"(d[43]), "+f"(d[44]), "+f"(d[45]), "+f"(d[46]), "+f"(d[47]), "+f"(d[48]), "+f"(d[49]), "+f"(d[50]), "+f"(d[51]), "+f"(d[52]), "+f"(d[53]), "+f"(d[54]), "+f"(d[55]), "+f"(d[56]), "+f"(d[57]), "+f"(d[58]), "+f"(d[59]), "+f"(d[60]), "+f"(d[61]), "+f"(d[62]), "+f"(d[63])
    : "r"(a0), "r"(a1), "r"(a2), "r"(a3), "l"(db), "r"(sc));
}
__device__ __forceinline__ void wgmma_rs_n128_tb(float (&d)[64], uint32_t a0, uint32_t a1, uint32_t a2, uint32_t a3, uint64_t db, uint32_t sc) {
  asm volatile("{\n.reg .pred p;\nsetp.ne.b32 p, %69, 0;\n"
    "wgmma.mma_async.sync.aligned.m64n128k16.f32.bf16.bf16 "
    "{%0, %1, %2, %3, %4, %5, %6, %7, %8, %9, %10, %11, %12, %13, %14, %15, %16, %17, %18, %19, %20, %21, %22, %23, %24, %25, %26, %27, %28, %29, %30, %31, %32, %33, %34, %35, %36, %37, %38, %39, %40, %41, %42, %43, %44, %45, %46, %47, %48, %49, %50, %51, %52, %53, %54, %55, %56, %57, %58, %59, %60, %61, %62, %63}, {%64, %65, %66, %67}, %68, p, 1, 1, 1;\n}\n"
    : "+f"(d[0]), "+f"(d[1]), "+f"(d[2]), "+f"(d[3]), "+f"(d[4]), "+f"(d[5]), "+f"(d[6]), "+f"(d[7]), "+f"(d[8]), "+f"(d[9]), "+f"(d[10]), "+f"(d[11]), "+f"(d[12]), "+f"(d[13]), "+f"(d[14]), "+f"(d[15]), "+f"(d[16]), "+f"(d[17]), "+f"(d[18]), "+f"(d[19]), "+f"(d[20]), "+f"(d[21]), "+f"(d[22]), "+f"(d[23]), "+f"(d[24]), "+f"(d[25]), "+f"(d[26]), "+f"(d[27]), "+f"(d[28]), "+f"(d[29]), "+f"(d[30]), "+f"(d[31]), "+f"(d[32]), "+f"(d[33]), "+f"(d[34]), "+f"(d[35]), "+f"(d[36]), "+f"(d[37]), "+f"(d[38]), "+f"(d[39]), "+f"(d[40]), "+f"(d[41]), "+f"(d[42]), "+f"(d[43]), "+f"(d[44]), "+f"(d[45]), "+f"(d[46]), "+f"(d[47]), "+f"(d[48]), "+f"(d[49]), "+f"(d[50]), "+f"(d[51]), "+f"(d[52]), "+f"(d[53]), "+f"(d[54]), "+f"(d[55]), "+f"(d[56]), "+f"(d[57]), "+f"(d[58]), "+f"(d[59]), "+f"(d[60]), "+f"(d[61]), "+f"(d[62]), "+f"(d[63])
    : "r"(a0), "r"(a1), "r"(a2), "r"(a3), "l"(db), "r"(sc));
}

#define TS(i) do {} while (0)

__device__ __forceinline__ uint32_t wrap12(uint32_t p) { return p >= NSLOT ? p - NSLOT : p; }

struct Cons {
  uint32_t sb;
  uint32_t g, pos;
  uint32_t rel;
  uint32_t nstg;
  uint32_t stg;
  uint32_t xr;
  int wg, lane;
  __device__ __forceinline__ void wait_full(uint32_t gg) const { mbar_wait(sb + SM_BAR + B_FULL + (gg & 7) * 8, (gg >> 3) & 1); }
  __device__ __forceinline__ void release(uint32_t gg) const { if (lane < 2) mbar_arrive_cluster(rel + (gg & 7) * 8); }
  __device__ __forceinline__ void stg_acquire() { mbar_wait(sb + SM_BAR + B_SEMPTY + wg * 8, (nstg & 1) ^ 1); nstg++; }
  __device__ __forceinline__ void stg_publish() const {
    fence_async_smem();
    __syncwarp();
    if (lane == 0) mbar_arrive(sb + SM_BAR + B_SFULL + wg * 8);
  }
};

template <int N, bool FIRST>
__device__ __forceinline__ void gemm_step(float (&acc)[128], Cons& c) {
  const uint32_t p1 = wrap12(c.pos + 1), p2 = wrap12(c.pos + 2);
  const uint64_t da = mkdesc(c.sb + c.wg * 8192 + c.pos * SLOT, 16, 1024);
  const uint64_t b0 = mkdesc(c.sb + p1 * SLOT, 4096, 1024);
  const uint64_t b1 = mkdesc(c.sb + p2 * SLOT, 4096, 1024);
  c.wait_full(c.g);
  wg_fence();
  if (N == 256) {
    wgmma_ss_n256_tb(acc, da, b0, FIRST ? 0 : 1);
    wgmma_ss_n256_tb(acc, da + 2, b0 + 128, 1);
    wgmma_ss_n256_tb(acc, da + 4, b1, 1);
    wgmma_ss_n256_tb(acc, da + 6, b1 + 128, 1);
  } else {
    wgmma_ss_n192_tb(acc, da, b0, FIRST ? 0 : 1);
    wgmma_ss_n192_tb(acc, da + 2, b0 + 128, 1);
    wgmma_ss_n192_tb(acc, da + 4, b1, 1);
    wgmma_ss_n192_tb(acc, da + 6, b1 + 128, 1);
  }
  wg_commit();
  if (!FIRST) {
    wg_wait<1>();
    c.release(c.g - 1);
  }
  c.g++;
  c.pos = wrap12(p2 + 1);
}

template <int N>
__device__ __forceinline__ void gemm_loop(float (&acc)[128], Cons& c, int nk) {
  gemm_step<N, true>(acc, c);
#pragma unroll 1
  for (int k = 1; k < nk; k++) gemm_step<N, false>(acc, c);
  wg_wait<0>();
  c.release(c.g - 1);
  fence_regs(acc);
}

__device__ __forceinline__ float silu_bf(float v) {
  const float f = bf_round(v);
  return __fdividef(f, 1.0f + ex2(-1.4426950408889634f * f));
}

template <int MODE, int B0, int NB>
__device__ __forceinline__ void store_event(const float (&acc)[128], Cons& c) {
  uint32_t r[NB * 16];
#pragma unroll
  for (int i = 0; i < NB * 16; i++) {
    const float lo = acc[B0 * 32 + 2 * i], hi = acc[B0 * 32 + 2 * i + 1];
    r[i] = MODE == 0 ? pack_bf16_relu(lo, hi) : pack_bf16(silu_bf(lo), silu_bf(hi));
  }
  c.stg_acquire();
#pragma unroll
  for (int b = 0; b < NB; b++)
#pragma unroll
    for (int kb = 0; kb < 4; kb++)
      stsm4(c.stg + b * 8192 + (((2 * kb) ^ c.xr) << 4), r[b * 16 + kb * 4], r[b * 16 + kb * 4 + 1], r[b * 16 + kb * 4 + 2], r[b * 16 + kb * 4 + 3]);
  c.stg_publish();
}

template <int N>
__device__ __forceinline__ void h_tile(float (&acc)[128], Cons& c) {
  gemm_loop<N>(acc, c, 16);
  store_event<0, 0, 2>(acc, c);
  store_event<0, 2, N / 64 - 2>(acc, c);
}

constexpr float SM_C = 0.08838834764831845f * 1.4426950408889634f;

__device__ __forceinline__ void softmax_step(float (&S)[64], float& m0, float& m1, float& l0, float& l1, float& a0, float& a1, bool first) {
  float x0[4], x1[4];
#pragma unroll
  for (int i = 0; i < 4; i++) { x0[i] = fmaxf(S[4 * i], S[4 * i + 1]); x1[i] = fmaxf(S[4 * i + 2], S[4 * i + 3]); }
#pragma unroll
  for (int i = 4; i < 16; i++) {
    x0[i & 3] = fmaxf(x0[i & 3], fmaxf(S[4 * i], S[4 * i + 1]));
    x1[i & 3] = fmaxf(x1[i & 3], fmaxf(S[4 * i + 2], S[4 * i + 3]));
  }
  float mx0 = fmaxf(fmaxf(x0[0], x0[1]), fmaxf(x0[2], x0[3]));
  float mx1 = fmaxf(fmaxf(x1[0], x1[1]), fmaxf(x1[2], x1[3]));
  mx0 = fmaxf(mx0, __shfl_xor_sync(~0u, mx0, 1));
  mx1 = fmaxf(mx1, __shfl_xor_sync(~0u, mx1, 1));
  mx0 = fmaxf(mx0, __shfl_xor_sync(~0u, mx0, 2));
  mx1 = fmaxf(mx1, __shfl_xor_sync(~0u, mx1, 2));
  const float n0 = first ? mx0 : fmaxf(m0, mx0);
  const float n1 = first ? mx1 : fmaxf(m1, mx1);
  a0 = first ? 0.f : ex2((m0 - n0) * SM_C);
  a1 = first ? 0.f : ex2((m1 - n1) * SM_C);
  m0 = n0; m1 = n1;
  const float c0 = -n0 * SM_C, c1 = -n1 * SM_C;
  float s0[2] = {0.f, 0.f}, s1[2] = {0.f, 0.f};
#pragma unroll
  for (int i = 0; i < 16; i++) {
    S[4 * i]     = ex2(fmaf(S[4 * i],     SM_C, c0));
    S[4 * i + 1] = ex2(fmaf(S[4 * i + 1], SM_C, c0));
    S[4 * i + 2] = ex2(fmaf(S[4 * i + 2], SM_C, c1));
    S[4 * i + 3] = ex2(fmaf(S[4 * i + 3], SM_C, c1));
    s0[0] += S[4 * i]; s0[1] += S[4 * i + 1];
    s1[0] += S[4 * i + 2]; s1[1] += S[4 * i + 3];
  }
  l0 = fmaf(l0, a0, s0[0] + s0[1]);
  l1 = fmaf(l1, a1, s1[0] + s1[1]);
}

__device__ __forceinline__ void write_o(const float (&O)[64], float l0, float l1, const Cons& c) {
  l0 += __shfl_xor_sync(~0u, l0, 1); l1 += __shfl_xor_sync(~0u, l1, 1);
  l0 += __shfl_xor_sync(~0u, l0, 2); l1 += __shfl_xor_sync(~0u, l1, 2);
  const float i0 = __fdividef(1.0f, l0), i1 = __fdividef(1.0f, l1);
#pragma unroll
  for (int kb = 0; kb < 8; kb++)
    stsm4(c.stg + (kb >> 2) * 8192 + (((2 * (kb & 3)) ^ c.xr) << 4),
          pack_bf16(O[8 * kb] * i0, O[8 * kb + 1] * i0), pack_bf16(O[8 * kb + 2] * i1, O[8 * kb + 3] * i1),
          pack_bf16(O[8 * kb + 4] * i0, O[8 * kb + 5] * i0), pack_bf16(O[8 * kb + 6] * i1, O[8 * kb + 7] * i1));
  c.stg_publish();
}

__device__ __forceinline__ void issue_qk(float (&S)[64], const uint32_t (&q)[32], uint32_t s0, uint32_t s1) {
  const uint64_t d0 = mkdesc(s0, 16, 1024), d1 = mkdesc(s1, 16, 1024);
#pragma unroll
  for (int kk = 0; kk < 8; kk++)
    wgmma_rs_n128(S, q[4 * kk], q[4 * kk + 1], q[4 * kk + 2], q[4 * kk + 3], (kk < 4 ? d0 : d1) + (kk & 3) * 2, kk > 0);
}
__device__ __forceinline__ void issue_pv(float (&O)[64], const uint32_t (&p)[32], uint32_t s0, uint32_t s1) {
  const uint64_t d0 = mkdesc(s0, 8192, 1024), d1 = mkdesc(s1, 8192, 1024);
#pragma unroll
  for (int kk = 0; kk < 8; kk++)
    wgmma_rs_n128_tb(O, p[4 * kk], p[4 * kk + 1], p[4 * kk + 2], p[4 * kk + 3], (kk < 4 ? d0 : d1) + (kk & 3) * 128, 1);
}

#define TURN_SYNC()   bar_sync(1 + c.wg, 256)
#define TURN_PASS()   bar_arrive(2 - c.wg, 256)

__device__ __forceinline__ void attn_tile(float (&acc)[128], Cons& c) {
  gemm_loop<256>(acc, c, 16);
  uint32_t q[32], p[32];
  float S[64], O[64];
  const uint32_t stash = c.sb + SM_STG + c.wg * 16384 + ((threadIdx.x >> 5) & 3) * 2048 + c.lane * 16;
#pragma unroll
  for (int i = 0; i < 32; i++) q[i] = pack_bf16(acc[2 * i], acc[2 * i + 1]);
  c.stg_acquire();
#pragma unroll
  for (int i = 0; i < 8; i++)
    sts128(stash + (i >> 2) * 8192 + (i & 3) * 512, pack_bf16(acc[64 + 8 * i], acc[65 + 8 * i]), pack_bf16(acc[66 + 8 * i], acc[67 + 8 * i]),
           pack_bf16(acc[68 + 8 * i], acc[69 + 8 * i]), pack_bf16(acc[70 + 8 * i], acc[71 + 8 * i]));
  fence_regs(q);
  TURN_SYNC();
  c.wait_full(c.g);
  wg_fence();
  issue_qk(S, q, c.sb + c.pos * SLOT, c.sb + wrap12(c.pos + 1) * SLOT);
  wg_commit();
  TURN_PASS();
  wg_wait<0>();
  fence_regs(S);
  c.release(c.g);
  c.g++;
  c.pos = wrap12(c.pos + 2);
  float m0 = 0.f, m1 = 0.f, l0 = 0.f, l1 = 0.f, a0, a1;
  softmax_step(S, m0, m1, l0, l1, a0, a1, true);
#pragma unroll
  for (int i = 0; i < 32; i++) p[i] = pack_bf16(S[2 * i], S[2 * i + 1]);
#pragma unroll
  for (int i = 0; i < 64; i++) O[i] = 0.f;
#pragma unroll 1
  for (int j = 0; j < 7; j++) {
    const uint32_t k0 = c.pos, k1 = wrap12(k0 + 1), v0 = wrap12(k0 + 2), v1 = wrap12(k0 + 3);
    TURN_SYNC();
    c.wait_full(c.g);
    wg_fence();
    issue_qk(S, q, c.sb + k0 * SLOT, c.sb + k1 * SLOT);
    wg_commit();
    c.wait_full(c.g + 1);
    wg_fence();
    issue_pv(O, p, c.sb + v0 * SLOT, c.sb + v1 * SLOT);
    wg_commit();
    TURN_PASS();
    wg_wait<1>();
    fence_regs(S);
    fence_regs(q);
    c.release(c.g);
    if (j == 2) {
#pragma unroll
      for (int i = 0; i < 8; i++) lds128(stash + (i >> 2) * 8192 + (i & 3) * 512, q[4 * i], q[4 * i + 1], q[4 * i + 2], q[4 * i + 3]);
      __syncwarp();
    }
    const float lo0 = l0, lo1 = l1;
    softmax_step(S, m0, m1, l0, l1, a0, a1, j == 3);
    fence_regs(S);
    wg_wait<0>();
    fence_regs(O);
    fence_regs(p);
    fence_regs(S);
    c.release(c.g + 1);
    if (j == 3) {
      write_o(O, lo0, lo1, c);
#pragma unroll
      for (int i = 0; i < 64; i++) O[i] = 0.f;
    } else {
#pragma unroll
      for (int i = 0; i < 16; i++) { O[4 * i] *= a0; O[4 * i + 1] *= a0; O[4 * i + 2] *= a1; O[4 * i + 3] *= a1; }
    }
#pragma unroll
    for (int i = 0; i < 32; i++) p[i] = pack_bf16(S[2 * i], S[2 * i + 1]);
    c.g += 2;
    c.pos = wrap12(v1 + 1);
  }
  TURN_SYNC();
  c.wait_full(c.g);
  wg_fence();
  issue_pv(O, p, c.sb + c.pos * SLOT, c.sb + wrap12(c.pos + 1) * SLOT);
  wg_commit();
  TURN_PASS();
  c.stg_acquire();
  wg_wait<0>();
  fence_regs(O);
  fence_regs(p);
  c.release(c.g);
  c.g++;
  c.pos = wrap12(c.pos + 2);
  write_o(O, l0, l1, c);
}

struct Prod {
  uint32_t sb, g, pos, head, tail_g, tail_pos, hist;
  __device__ __forceinline__ uint32_t full() const { return sb + SM_BAR + B_FULL + (g & 7) * 8; }
  __device__ __forceinline__ uint32_t slot(uint32_t i) const { return sb + wrap12(pos + i) * SLOT; }
  __device__ __forceinline__ void acquire(uint32_t size) {
    while (head + size - tail_pos > NSLOT) {
      mbar_wait(sb + SM_BAR + B_EMPTY + (tail_g & 7) * 8, (tail_g >> 3) & 1);
      tail_pos += 2 + ((hist >> (tail_g & 31)) & 1);
      tail_g++;
    }
    hist = (hist & ~(1u << (g & 31))) | ((size - 2) << (g & 31));
  }
  __device__ __forceinline__ void advance(uint32_t size) { g++; head += size; pos = wrap12(pos + size); }
};

__device__ __forceinline__ void wait_flag(const unsigned* p, unsigned target) {
  while ((int)(ld_acquire(p) - target) < 0) {}
  fence_async_all();
}

__global__ void __cluster_dims__(2, 1, 1) __launch_bounds__(384, 1) fused_kernel(const __grid_constant__ Params P) {
  extern __shared__ uint8_t smem_raw[];
  const uint32_t sb = (smem_u32(smem_raw) + 1023u) & ~1023u;
  const int warp = __shfl_sync(~0u, (int)(threadIdx.x >> 5), 0);
  const int lane = threadIdx.x & 31;
  const int rank = blockIdx.x & 1;
  const int cl = blockIdx.x >> 1;
  const int j = cl >> 3;
  const int rb = (cl & 7) * 2 + rank;
  const bool is_s = j < 4;
  const int hn0 = is_s ? HS0 : HF0, hn1 = is_s ? HS1 : HF1;
  const int hc0 = is_s ? j * (HS0 + HS1) : 4 * (HS0 + HS1) + (j - 4) * (HF0 + HF1);
  const int hc1 = hc0 + hn0;
  const int row0 = rb * 128;
  Flags* fl = P.flags;

  if (warp >= 8) {
    if (warp == 8 && lane == 0) {
      for (int i = 0; i < NBAR; i++) { mbar_init(sb + SM_BAR + B_FULL + i * 8, 1); mbar_init(sb + SM_BAR + B_EMPTY + i * 8, 16); }
      for (int i = 0; i < 2; i++) { mbar_init(sb + SM_BAR + B_SFULL + i * 8, 4); mbar_init(sb + SM_BAR + B_SEMPTY + i * 8, 1); }
      mbar_init(sb + SM_BAR + B_DONE, 11);
      asm volatile("fence.mbarrier_init.release.cluster;" ::: "memory");
    }
    if (warp == 9 && lane < 11) prefetch_map(&P.act_ld + lane);
    __syncwarp();
    cluster_arrive();
    cluster_wait();
    asm volatile("setmaxnreg.dec.sync.aligned.u32 40;");
    if (warp == 8) {
      const unsigned ep1 = *(volatile unsigned*)&fl->epoch[blockIdx.x] + 1;
      Prod p{sb, 0, 0, 0, 0, 0, 0};
      for (int t = 0; t < 2; t++) {
        const int n = t ? hn1 : hn0, nb0 = (t ? hc1 : hc0) >> 6;
        const CUtensorMap* mb = n == 256 ? &P.w1b4 : &P.w1b3;
        const uint32_t bytes = 16384 + n * 128;
        int k = 0;
        if (t == 0) {
          for (; k < 4; k++) {
            p.acquire(3);
            if (lane == 0) { mbar_expect_tx(p.full(), bytes); tma_ld3_mc(p.slot(1 + rank), mb, p.full(), 0, k * 64 + rank * 32, nb0); }
            p.advance(3);
          }
          wait_flag(&fl->ln[rb][0], ep1 * 8);
          if (lane == 0)
            for (int i = 0; i < 4; i++) tma_ld2(sb + i * 3 * SLOT, &P.act_ld, sb + SM_BAR + B_FULL + i * 8, C_XN + i * 64, row0);
        }
        for (; k < 16; k++) {
          p.acquire(3);
          if (lane == 0) {
            mbar_expect_tx(p.full(), bytes);
            tma_ld3_mc(p.slot(1 + rank), mb, p.full(), 0, k * 64 + rank * 32, nb0);
            tma_ld2(p.slot(0), &P.act_ld, p.full(), C_XN + k * 64, row0);
          }
          p.advance(3);
        }
      }
      const int kvrow = (j >> 1) * SK + KV0;
      for (int t = 0; t < 2; t++) {
        const int nb0 = (4 * j + 2 * t) * 2;
        for (int k = 0; k < 16; k++) {
          p.acquire(3);
          if (lane == 0) {
            mbar_expect_tx(p.full(), 49152);
            tma_ld3_mc(p.slot(1 + rank), &P.wq, p.full(), 0, k * 64 + rank * 32, nb0);
            tma_ld2(p.slot(0), &P.act_ld, p.full(), C_XN + k * 64, row0);
          }
          p.advance(3);
        }
        for (int i = 0; i < 16; i++) {
          const bool is_k = i == 0 || (i < 15 && (i & 1));
          const int ch = (is_k ? ((i + 1) >> 1) : (i == 15 ? 7 : (i >> 1) - 1)) & 3;
          p.acquire(2);
          if (lane == 0) {
            mbar_expect_tx(p.full(), 32768);
            if (is_k) tma_ld2_mc(p.slot(rank), &P.k_ld, p.full(), rank * 64, kvrow + ch * 128);
            else      tma_ld3_mc(p.slot(rank), &P.v_ld, p.full(), 0, kvrow + ch * 128 + rank * 64, 0);
          }
          p.advance(2);
        }
        if (t == 0 && !is_s) wait_flag(&fl->h[rb][0], ep1 * 64);
      }
      const int jn = j & 3;
      if (is_s) {
        unsigned ready = 0;
        for (int i = 0; i < 64; i++) {
          const int hi = i >> 1;
          const int head = 4 * ((hi & 15) >> 1) + (hi & 1) + ((hi >> 4) << 1);
          const int kc = head * 128 + (i & 1) * 64;
          p.acquire(3);
          if (lane == 0) { mbar_expect_tx(p.full(), 49152); tma_ld3_mc(p.slot(1 + rank), &P.wo, p.full(), 0, kc + rank * 32, jn * 4); }
          if (!((ready >> head) & 1)) {
            do { ready = __ballot_sync(~0u, (int)(ld_acquire(&fl->o[rb][lane]) - ep1 * 2) >= 0); } while (!((ready >> head) & 1));
            __syncwarp();
            fence_async_all();
          }
          if (lane == 0) tma_ld2(p.slot(0), &P.act_ld, p.full(), C_O + kc, row0);
          p.advance(3);
        }
        for (int i = 0; i < 4; i++) {
          p.acquire(2);
          if (i == 2) wait_flag(&fl->g[rb][jn], ep1 * 4);
          if (lane == 0) {
            mbar_expect_tx(p.full(), 32768);
            const CUtensorMap* m = i < 2 ? &P.x_ld : &P.act_ld;
            const int c0 = (i < 2 ? 0 : C_G) + jn * 256 + (i & 1) * 128;
            tma_ld2(p.slot(0), m, p.full(), c0, row0);
            tma_ld2(p.slot(1), m, p.full(), c0 + 64, row0);
          }
          p.advance(2);
        }
      } else {
        for (int k = 0; k < 56; k++) {
          p.acquire(3);
          if (lane == 0) {
            mbar_expect_tx(p.full(), 49152);
            tma_ld3_mc(p.slot(1 + rank), &P.w2, p.full(), 0, k * 64 + rank * 32, jn * 4);
            tma_ld2(p.slot(0), &P.act_ld, p.full(), C_H + k * 64, row0);
          }
          p.advance(3);
        }
      }
      if (lane == 0) { *(volatile unsigned*)&fl->epoch[blockIdx.x] = ep1; mbar_arrive(sb + SM_BAR + B_DONE); }
    } else if (warp < 11) {
      const int wg = warp - 9;
      if (lane == 0) {
        const uint32_t stg = sb + SM_STG + wg * 16384;
        const int nev = is_s ? 8 : 10;
        for (int n = 0; n < nev; n++) {
          int col, nbox = 2;
          unsigned* flag;
          if (n < 4) {
            col = C_H + ((n & 2) ? hc1 : hc0) + (n & 1) * 128;
            if ((n & 1) && ((n & 2) ? hn1 : hn0) == 192) nbox = 1;
            flag = &fl->h[rb][0];
          } else if (n < 8) {
            col = C_O + (4 * j + n - 4) * 128;
            flag = &fl->o[rb][4 * j + n - 4];
          } else {
            col = C_G + (j & 3) * 256 + (n - 8) * 128;
            flag = &fl->g[rb][j & 3];
          }
          mbar_wait(sb + SM_BAR + B_SFULL + wg * 8, n & 1);
          tma_st2(&P.act_st, stg, col, row0 + wg * 64);
          if (nbox == 2) tma_st2(&P.act_st, stg + 8192, col + 64, row0 + wg * 64);
          bulk_commit();
          bulk_wait_read0();
          mbar_arrive(sb + SM_BAR + B_SEMPTY + wg * 8);
          bulk_wait0();
          fence_async_all();
          red_release(flag, 1);
        }
        mbar_arrive(sb + SM_BAR + B_DONE);
      }
    } else {
      if (lane == 0) {
        const unsigned long long t0 = gtime();
        while (!mbar_try(sb + SM_BAR + B_DONE, 0))
          if (gtime() - t0 > 2000000000ull) __trap();
      }
    }
    __syncwarp();
    cluster_arrive();
    cluster_wait();
  } else {
    const int wg = warp >> 2;
    TS(0);
    {
      const int r = row0 + j * 16 + warp * 2;
      uint4 v[2][4];
#pragma unroll
      for (int a = 0; a < 2; a++)
#pragma unroll
        for (int i = 0; i < 4; i++) v[a][i] = __ldg((const uint4*)(P.x + (size_t)(r + a) * DM + i * 256 + lane * 8));
      cluster_arrive();
#pragma unroll
      for (int a = 0; a < 2; a++) {
        float f[32];
#pragma unroll
        for (int i = 0; i < 4; i++) {
          f[8 * i] = bf_lo(v[a][i].x); f[8 * i + 1] = bf_hi(v[a][i].x); f[8 * i + 2] = bf_lo(v[a][i].y); f[8 * i + 3] = bf_hi(v[a][i].y);
          f[8 * i + 4] = bf_lo(v[a][i].z); f[8 * i + 5] = bf_hi(v[a][i].z); f[8 * i + 6] = bf_lo(v[a][i].w); f[8 * i + 7] = bf_hi(v[a][i].w);
        }
        float s = 0.f;
#pragma unroll
        for (int i = 0; i < 32; i++) s += f[i];
#pragma unroll
        for (int o = 16; o; o >>= 1) s += __shfl_xor_sync(~0u, s, o);
        const float mean = s * (1.0f / DM);
        float q = 0.f;
#pragma unroll
        for (int i = 0; i < 32; i++) { const float d = f[i] - mean; q = fmaf(d, d, q); }
#pragma unroll
        for (int o = 16; o; o >>= 1) q += __shfl_xor_sync(~0u, q, o);
        const float mb = bf_round(mean);
        const float sd = bf_round(sqrtf(bf_round(bf_round(q * (1.0f / DM)) + 1e-5f)));
        const float inv = 1.0f / sd;
#pragma unroll
        for (int i = 0; i < 4; i++) {
          uint4 o;
          o.x = pack_bf16(bf_round(f[8 * i] - mb) * inv, bf_round(f[8 * i + 1] - mb) * inv);
          o.y = pack_bf16(bf_round(f[8 * i + 2] - mb) * inv, bf_round(f[8 * i + 3] - mb) * inv);
          o.z = pack_bf16(bf_round(f[8 * i + 4] - mb) * inv, bf_round(f[8 * i + 5] - mb) * inv);
          o.w = pack_bf16(bf_round(f[8 * i + 6] - mb) * inv, bf_round(f[8 * i + 7] - mb) * inv);
          *(uint4*)(P.act + (size_t)(r + a) * ACT_W + C_XN + i * 256 + lane * 8) = o;
        }
      }
      fence_async_all();
      bar_sync(5, 256);
      if (threadIdx.x == 0) red_release(&fl->ln[rb][0], 1);
      cluster_wait();
    }
    asm volatile("setmaxnreg.inc.sync.aligned.u32 232;");
    Cons c;
    c.sb = sb; c.g = 0; c.pos = 0; c.nstg = 0; c.wg = wg; c.lane = lane;
    c.rel = mapa(sb + SM_BAR + B_EMPTY, lane & 1);
    const uint32_t rowoff = (warp & 3) * 2048 + ((lane & 7) + ((lane >> 3) & 1) * 8) * 128;
    c.stg = sb + SM_STG + wg * 16384 + rowoff;
    c.xr = (lane >> 4) ^ (lane & 7);
    if (wg == 1) bar_arrive(1, 256);
    float acc[128];
    TS(1);
    if (hn0 == 256) h_tile<256>(acc, c); else h_tile<192>(acc, c);
    TS(2);
    if (hn1 == 256) h_tile<256>(acc, c); else h_tile<192>(acc, c);
    TS(3);
#pragma unroll 1
    for (int t = 0; t < 2; t++) {
      attn_tile(acc, c);
      TS(4 + t);
    }
    gemm_loop<256>(acc, c, is_s ? 64 : 56);
    TS(6);
    if (is_s) {
      const uint32_t x0 = c.pos;
      c.wait_full(c.g);
      c.wait_full(c.g + 1);
#pragma unroll
      for (int b = 0; b < 4; b++) {
        if ((b & 1) == 0) c.wait_full(c.g + 2 + (b >> 1));
        const uint32_t xs = sb + wrap12(x0 + b) * SLOT + wg * 8192;
        const uint32_t sx = xs + rowoff, sg = sb + wrap12(wrap12(x0 + 4) + b) * SLOT + wg * 8192 + rowoff;
#pragma unroll
        for (int kb = 0; kb < 4; kb++) {
          const uint32_t off = ((2 * kb) ^ c.xr) << 4;
          uint32_t xv[4], gv[4];
          ldsm4(sx + off, xv[0], xv[1], xv[2], xv[3]);
          ldsm4(sg + off, gv[0], gv[1], gv[2], gv[3]);
#pragma unroll
          for (int r = 0; r < 4; r++) {
            const uint32_t s2 = pack_bf16(acc[32 * b + 8 * kb + 2 * r], acc[32 * b + 8 * kb + 2 * r + 1]);
            const __nv_bfloat162 pr = __hmul2_rn(*(const __nv_bfloat162*)&s2, *(const __nv_bfloat162*)&gv[r]);
            const __nv_bfloat162 o = __hadd2_rn(*(const __nv_bfloat162*)&xv[r], pr);
            xv[r] = *(const uint32_t*)&o;
          }
          stsm4(sx + off, xv[0], xv[1], xv[2], xv[3]);
        }
        fence_async_smem();
        bar_sync(3 + wg, 128);
        if ((threadIdx.x & 127) == 0) { tma_st2(&P.out_st, xs, (j & 3) * 256 + b * 64, row0 + wg * 64); bulk_commit(); }
      }
      if ((threadIdx.x & 127) == 0) bulk_wait0();
    } else {
      store_event<1, 0, 2>(acc, c);
      store_event<1, 2, 2>(acc, c);
    }
    TS(7);
    __syncwarp();
    if (lane == 0) mbar_arrive(sb + SM_BAR + B_DONE);
    cluster_arrive();
    cluster_wait();
  }
}

typedef CUresult (*EncodeFn)(CUtensorMap*, CUtensorMapDataType, cuuint32_t, void*, const cuuint64_t*, const cuuint64_t*,
                             const cuuint32_t*, const cuuint32_t*, CUtensorMapInterleave, CUtensorMapSwizzle,
                             CUtensorMapL2promotion, CUtensorMapFloatOOBfill);

void map2d(EncodeFn enc, CUtensorMap* m, const void* base, uint64_t cols, uint64_t rows, uint32_t box_rows) {
  cuuint64_t dims[2] = {cols, rows};
  cuuint64_t strides[1] = {cols * 2};
  cuuint32_t box[2] = {64, box_rows};
  cuuint32_t es[2] = {1, 1};
  enc(m, CU_TENSOR_MAP_DATA_TYPE_BFLOAT16, 2, (void*)base, dims, strides, box, es, CU_TENSOR_MAP_INTERLEAVE_NONE,
      CU_TENSOR_MAP_SWIZZLE_128B, CU_TENSOR_MAP_L2_PROMOTION_L2_256B, CU_TENSOR_MAP_FLOAT_OOB_FILL_NONE);
}
void map3d(EncodeFn enc, CUtensorMap* m, const void* base, uint64_t cols, uint64_t rows, uint32_t box_rows, uint32_t box_blks) {
  cuuint64_t dims[3] = {64, rows, cols / 64};
  cuuint64_t strides[2] = {cols * 2, 128};
  cuuint32_t box[3] = {64, box_rows, box_blks};
  cuuint32_t es[3] = {1, 1, 1};
  enc(m, CU_TENSOR_MAP_DATA_TYPE_BFLOAT16, 3, (void*)base, dims, strides, box, es, CU_TENSOR_MAP_INTERLEAVE_NONE,
      CU_TENSOR_MAP_SWIZZLE_128B, CU_TENSOR_MAP_L2_PROMOTION_L2_256B, CU_TENSOR_MAP_FLOAT_OOB_FILL_NONE);
}

}

extern "C" void kernel_launch(void* const* d_in, const int* in_sizes, int n_in, void* d_out, int out_size) {
  (void)in_sizes; (void)n_in; (void)out_size;
  static EncodeFn enc = nullptr;
  static void* act = nullptr;
  static void* flags = nullptr;
  if (!enc) {
    void* fn = nullptr;
    cudaDriverEntryPointQueryResult qr;
    cudaGetDriverEntryPoint("cuTensorMapEncodeTiled", &fn, cudaEnableDefault, &qr);
    enc = (EncodeFn)fn;
    cudaGetSymbolAddress(&act, g_act);
    cudaGetSymbolAddress(&flags, g_flags);
    cudaFuncSetAttribute(fused_kernel, cudaFuncAttributeMaxDynamicSharedMemorySize, SMEM_BYTES);
  }
  Params P;
  map2d(enc, &P.act_ld, act, ACT_W, SEQ, 128);
  map2d(enc, &P.act_st, act, ACT_W, SEQ, 64);
  map2d(enc, &P.x_ld, d_in[0], DM, SEQ, 128);
  map2d(enc, &P.out_st, d_out, DM, SEQ, 64);
  map2d(enc, &P.k_ld, d_in[1], 128, 4 * SK, 128);
  map3d(enc, &P.v_ld, d_in[2], 128, 4 * SK, 64, 2);
  map3d(enc, &P.wq, d_in[3], NQ, DM, 32, 4);
  map3d(enc, &P.w1b4, d_in[6], DFF, DM, 32, 4);
  map3d(enc, &P.w1b3, d_in[6], DFF, DM, 32, 3);
  map3d(enc, &P.wo, d_in[4], DM, NQ, 32, 4);
  map3d(enc, &P.w2, d_in[7], DM, DFF, 32, 4);
  P.x = (const __nv_bfloat16*)d_in[0];
  P.act = (__nv_bfloat16*)act;
  P.flags = (Flags*)flags;
  fused_kernel<<<NCLUSTER * 2, 384, SMEM_BYTES>>>(P);
}
```

```cpp
#include <cuda_runtime.h>
#include <cuda_bf16.h>
#include <cuda.h>
#include <stdint.h>

namespace {

constexpr int SEQ    = 2048;
constexpr int DM     = 1024;
constexpr int NQ     = 4096;
constexpr int DFF    = 3584;
constexpr int SK     = 2048;
constexpr int WIN    = 512;
constexpr int KV0    = SK - WIN;
constexpr int C_XN = 0, C_O = 1024, C_H = 5120, C_G = 8704, ACT_W = 9728;

#define HS0 192
#define HS1 192
#define HF0 256
#define HF1 256
static_assert(4 * (HS0 + HS1 + HF0 + HF1) == DFF, "H split");

constexpr int NSLOT = 12, SLOT = 16384, NBAR = 8;
constexpr int SM_STG = NSLOT * SLOT;
constexpr int SM_BAR = SM_STG + 2 * 16384;
constexpr int SMEM_BYTES = SM_BAR + 256 + 1024 + 1536;
constexpr int B_FULL = 0, B_EMPTY = 64, B_SFULL = 128, B_SEMPTY = 144, B_DONE = 160;

constexpr int NCLUSTER = 64;

struct Flags {
  unsigned ln[16][32];
  unsigned h[16][32];
  unsigned o[16][32];
  unsigned g[16][32];
  unsigned epoch[160];
};
__device__ __nv_bfloat16 g_act[(size_t)SEQ * ACT_W];
__device__ Flags g_flags;

struct Params {
  CUtensorMap act_ld, act_st, x_ld, out_st, k_ld, v_ld, wq, w1b4, w1b3, wo, w2;
  const __nv_bfloat16* x;
  __nv_bfloat16* act;
  Flags* flags;
};

__device__ __forceinline__ uint32_t smem_u32(const void* p) { return (uint32_t)__cvta_generic_to_shared(p); }
__device__ __forceinline__ void mbar_init(uint32_t bar, uint32_t cnt) {
  asm volatile("mbarrier.init.shared::cta.b64 [%0], %1;" ::"r"(bar), "r"(cnt) : "memory");
}
__device__ __forceinline__ bool mbar_try(uint32_t bar, uint32_t parity) {
  uint32_t ok;
  asm volatile("{\n.reg .pred p;\nmbarrier.try_wait.parity.shared::cta.b64 p, [%1], %2;\nselp.u32 %0, 1, 0, p;\n}\n"
               : "=r"(ok) : "r"(bar), "r"(parity) : "memory");
  return ok;
}
__device__ __forceinline__ void mbar_wait(uint32_t bar, uint32_t parity) {
  asm volatile("{\n.reg .pred p;\nWAIT_%=:\nmbarrier.try_wait.parity.shared::cta.b64 p, [%0], %1;\n@p bra DONE_%=;\nbra WAIT_%=;\nDONE_%=:\n}\n"
               ::"r"(bar), "r"(parity) : "memory");
}
__device__ __forceinline__ void mbar_arrive(uint32_t bar) {
  asm volatile("mbarrier.arrive.shared::cta.b64 _, [%0];" ::"r"(bar) : "memory");
}
__device__ __forceinline__ void mbar_arrive_cluster(uint32_t cluster_addr) {
  asm volatile("mbarrier.arrive.shared::cluster.b64 _, [%0];" ::"r"(cluster_addr) : "memory");
}
__device__ __forceinline__ void mbar_expect_tx(uint32_t bar, uint32_t bytes) {
  asm volatile("mbarrier.arrive.expect_tx.shared::cta.b64 _, [%0], %1;" ::"r"(bar), "r"(bytes) : "memory");
}
__device__ __forceinline__ uint32_t mapa(uint32_t addr, uint32_t rank) {
  uint32_t r;
  asm("mapa.shared::cluster.u32 %0, %1, %2;" : "=r"(r) : "r"(addr), "r"(rank));
  return r;
}
__device__ __forceinline__ void cluster_arrive() { asm volatile("barrier.cluster.arrive.relaxed.aligned;" ::: "memory"); }
__device__ __forceinline__ void cluster_wait() { asm volatile("barrier.cluster.wait.acquire.aligned;" ::: "memory"); }
__device__ __forceinline__ void bar_sync(int id, int n) { asm volatile("bar.sync %0, %1;" ::"r"(id), "r"(n) : "memory"); }
__device__ __forceinline__ void bar_arrive(int id, int n) { asm volatile("bar.arrive %0, %1;" ::"r"(id), "r"(n) : "memory"); }
__device__ __forceinline__ void fence_async_smem() { asm volatile("fence.proxy.async.shared::cta;" ::: "memory"); }
__device__ __forceinline__ void fence_async_all() { asm volatile("fence.proxy.async.global;" ::: "memory"); }

__device__ __forceinline__ void tma_ld2(uint32_t dst, const CUtensorMap* m, uint32_t bar, int c0, int c1) {
  asm volatile("cp.async.bulk.tensor.2d.shared::cluster.global.mbarrier::complete_tx::bytes [%0], [%1, {%3, %4}], [%2];"
               ::"r"(dst), "l"(m), "r"(bar), "r"(c0), "r"(c1) : "memory");
}
__device__ __forceinline__ void tma_ld2_mc(uint32_t dst, const CUtensorMap* m, uint32_t bar, int c0, int c1) {
  asm volatile("cp.async.bulk.tensor.2d.shared::cluster.global.mbarrier::complete_tx::bytes.multicast::cluster [%0], [%1, {%3, %4}], [%2], %5;"
               ::"r"(dst), "l"(m), "r"(bar), "r"(c0), "r"(c1), "h"((uint16_t)3) : "memory");
}
__device__ __forceinline__ void tma_ld3_mc(uint32_t dst, const CUtensorMap* m, uint32_t bar, int c0, int c1, int c2) {
  asm volatile("cp.async.bulk.tensor.3d.shared::cluster.global.mbarrier::complete_tx::bytes.multicast::cluster [%0], [%1, {%3, %4, %5}], [%2], %6;"
               ::"r"(dst), "l"(m), "r"(bar), "r"(c0), "r"(c1), "r"(c2), "h"((uint16_t)3) : "memory");
}
__device__ __forceinline__ void tma_st2(const CUtensorMap* m, uint32_t src, int c0, int c1) {
  asm volatile("cp.async.bulk.tensor.2d.global.shared::cta.bulk_group [%0, {%2, %3}], [%1];"
               ::"l"(m), "r"(src), "r"(c0), "r"(c1) : "memory");
}
__device__ __forceinline__ void tma_pf3(const CUtensorMap* m, int c0, int c1, int c2) {
  asm volatile("cp.async.bulk.prefetch.tensor.3d.L2.global [%0, {%1, %2, %3}];" ::"l"(m), "r"(c0), "r"(c1), "r"(c2) : "memory");
}
__device__ __forceinline__ void bulk_commit() { asm volatile("cp.async.bulk.commit_group;" ::: "memory"); }
__device__ __forceinline__ void bulk_wait_read0() { asm volatile("cp.async.bulk.wait_group.read 0;" ::: "memory"); }
__device__ __forceinline__ void bulk_wait0() { asm volatile("cp.async.bulk.wait_group 0;" ::: "memory"); }
__device__ __forceinline__ void prefetch_map(const CUtensorMap* m) {
  asm volatile("prefetch.tensormap [%0];" ::"l"(m) : "memory");
}
__device__ __forceinline__ unsigned ld_acquire(const unsigned* p) {
  unsigned v;
  asm volatile("ld.acquire.gpu.global.u32 %0, [%1];" : "=r"(v) : "l"(p) : "memory");
  return v;
}
__device__ __forceinline__ void red_release(unsigned* p, unsigned v) {
  asm volatile("red.release.gpu.global.add.u32 [%0], %1;" ::"l"(p), "r"(v) : "memory");
}
__device__ __forceinline__ void wg_fence() { asm volatile("wgmma.fence.sync.aligned;" ::: "memory"); }
__device__ __forceinline__ void wg_commit() { asm volatile("wgmma.commit_group.sync.aligned;" ::: "memory"); }
template <int N> __device__ __forceinline__ void wg_wait() { asm volatile("wgmma.wait_group.sync.aligned %0;" ::"n"(N) : "memory"); }
template <int N> __device__ __forceinline__ void fence_regs(float (&d)[N]) {
#pragma unroll
  for (int i = 0; i < N; i++) asm volatile("" : "+f"(d[i])::"memory");
}
template <int N> __device__ __forceinline__ void fence_regs(uint32_t (&d)[N]) {
#pragma unroll
  for (int i = 0; i < N; i++) asm volatile("" : "+r"(d[i])::"memory");
}
__device__ __forceinline__ uint64_t mkdesc(uint32_t addr, uint32_t lbo, uint32_t sbo) {
  return (uint64_t)((addr & 0x3FFFF) >> 4) | ((uint64_t)(lbo >> 4) << 16) | ((uint64_t)(sbo >> 4) << 32) | (1ull << 62);
}
__device__ __forceinline__ uint32_t pack_bf16(float lo, float hi) {
  uint32_t r;
  asm("cvt.rn.bf16x2.f32 %0, %1, %2;" : "=r"(r) : "f"(hi), "f"(lo));
  return r;
}
__device__ __forceinline__ uint32_t pack_bf16_relu(float lo, float hi) {
  uint32_t r;
  asm("cvt.rn.relu.bf16x2.f32 %0, %1, %2;" : "=r"(r) : "f"(hi), "f"(lo));
  return r;
}
__device__ __forceinline__ float bf_lo(uint32_t v) { return __uint_as_float(v << 16); }
__device__ __forceinline__ float bf_hi(uint32_t v) { return __uint_as_float(v & 0xFFFF0000u); }
__device__ __forceinline__ float bf_round(float v) { return __bfloat162float(__float2bfloat16_rn(v)); }
__device__ __forceinline__ float ex2(float x) {
  float r;
  asm("ex2.approx.ftz.f32 %0, %1;" : "=f"(r) : "f"(x));
  return r;
}
__device__ __forceinline__ void stsm4(uint32_t addr, uint32_t r0, uint32_t r1, uint32_t r2, uint32_t r3) {
  asm volatile("stmatrix.sync.aligned.m8n8.x4.shared.b16 [%0], {%1, %2, %3, %4};" ::"r"(addr), "r"(r0), "r"(r1), "r"(r2), "r"(r3) : "memory");
}
__device__ __forceinline__ void ldsm4(uint32_t addr, uint32_t& r0, uint32_t& r1, uint32_t& r2, uint32_t& r3) {
  asm volatile("ldmatrix.sync.aligned.m8n8.x4.shared.b16 {%0, %1, %2, %3}, [%4];" : "=r"(r0), "=r"(r1), "=r"(r2), "=r"(r3) : "r"(addr) : "memory");
}
__device__ __forceinline__ void sts128(uint32_t addr, uint32_t r0, uint32_t r1, uint32_t r2, uint32_t r3) {
  asm volatile("st.shared.v4.b32 [%0], {%1, %2, %3, %4};" ::"r"(addr), "r"(r0), "r"(r1), "r"(r2), "r"(r3) : "memory");
}
__device__ __forceinline__ void lds128(uint32_t addr, uint32_t& r0, uint32_t& r1, uint32_t& r2, uint32_t& r3) {
  asm volatile("ld.shared.v4.b32 {%0, %1, %2, %3}, [%4];" : "=r"(r0), "=r"(r1), "=r"(r2), "=r"(r3) : "r"(addr) : "memory");
}
__device__ __forceinline__ unsigned long long gtime() {
  unsigned long long t;
  asm volatile("mov.u64 %0, %globaltimer;" : "=l"(t));
  return t;
}

__device__ __forceinline__ void wgmma_ss_n256_tb(float (&d)[128], uint64_t da, uint64_t db, uint32_t sc) {
  asm volatile("{\n.reg .pred p;\nsetp.ne.b32 p, %130, 0;\n"
    "wgmma.mma_async.sync.aligned.m64n256k16.f32.bf16.bf16 "
    "{%0, %1, %2, %3, %4, %5, %6, %7, %8, %9, %10, %11, %12, %13, %14, %15, %16, %17, %18, %19, %20, %21, %22, %23, %24, %25, %26, %27, %28, %29, %30, %31, %32, %33, %34, %35, %36, %37, %38, %39, %40, %41, %42, %43, %44, %45, %46, %47, %48, %49, %50, %51, %52, %53, %54, %55, %56, %57, %58, %59, %60, %61, %62, %63, %64, %65, %66, %67, %68, %69, %70, %71, %72, %73, %74, %75, %76, %77, %78, %79, %80, %81, %82, %83, %84, %85, %86, %87, %88, %89, %90, %91, %92, %93, %94, %95, %96, %97, %98, %99, %100, %101, %102, %103, %104, %105, %106, %107, %108, %109, %110, %111, %112, %113, %114, %115, %116, %117, %118, %119, %120, %121, %122, %123, %124, %125, %126, %127}, %128, %129, p, 1, 1, 0, 1;\n}\n"
    : "+f"(d[0]), "+f"(d[1]), "+f"(d[2]), "+f"(d[3]), "+f"(d[4]), "+f"(d[5]), "+f"(d[6]), "+f"(d[7]), "+f"(d[8]), "+f"(d[9]), "+f"(d[10]), "+f"(d[11]), "+f"(d[12]), "+f"(d[13]), "+f"(d[14]), "+f"(d[15]), "+f"(d[16]), "+f"(d[17]), "+f"(d[18]), "+f"(d[19]), "+f"(d[20]), "+f"(d[21]), "+f"(d[22]), "+f"(d[23]), "+f"(d[24]), "+f"(d[25]), "+f"(d[26]), "+f"(d[27]), "+f"(d[28]), "+f"(d[29]), "+f"(d[30]), "+f"(d[31]), "+f"(d[32]), "+f"(d[33]), "+f"(d[34]), "+f"(d[35]), "+f"(d[36]), "+f"(d[37]), "+f"(d[38]), "+f"(d[39]), "+f"(d[40]), "+f"(d[41]), "+f"(d[42]), "+f"(d[43]), "+f"(d[44]), "+f"(d[45]), "+f"(d[46]), "+f"(d[47]), "+f"(d[48]), "+f"(d[49]), "+f"(d[50]), "+f"(d[51]), "+f"(d[52]), "+f"(d[53]), "+f"(d[54]), "+f"(d[55]), "+f"(d[56]), "+f"(d[57]), "+f"(d[58]), "+f"(d[59]), "+f"(d[60]), "+f"(d[61]), "+f"(d[62]), "+f"(d[63]), "+f"(d[64]), "+f"(d[65]), "+f"(d[66]), "+f"(d[67]), "+f"(d[68]), "+f"(d[69]), "+f"(d[70]), "+f"(d[71]), "+f"(d[72]), "+f"(d[73]), "+f"(d[74]), "+f"(d[75]), "+f"(d[76]), "+f"(d[77]), "+f"(d[78]), "+f"(d[79]), "+f"(d[80]), "+f"(d[81]), "+f"(d[82]), "+f"(d[83]), "+f"(d[84]), "+f"(d[85]), "+f"(d[86]), "+f"(d[87]), "+f"(d[88]), "+f"(d[89]), "+f"(d[90]), "+f"(d[91]), "+f"(d[92]), "+f"(d[93]), "+f"(d[94]), "+f"(d[95]), "+f"(d[96]), "+f"(d[97]), "+f"(d[98]), "+f"(d[99]), "+f"(d[100]), "+f"(d[101]), "+f"(d[102]), "+f"(d[103]), "+f"(d[104]), "+f"(d[105]), "+f"(d[106]), "+f"(d[107]), "+f"(d[108]), "+f"(d[109]), "+f"(d[110]), "+f"(d[111]), "+f"(d[112]), "+f"(d[113]), "+f"(d[114]), "+f"(d[115]), "+f"(d[116]), "+f"(d[117]), "+f"(d[118]), "+f"(d[119]), "+f"(d[120]), "+f"(d[121]), "+f"(d[122]), "+f"(d[123]), "+f"(d[124]), "+f"(d[125]), "+f"(d[126]), "+f"(d[127])
    : "l"(da), "l"(db), "r"(sc));
}
__device__ __forceinline__ void wgmma_ss_n192_tb(float (&d)[128], uint64_t da, uint64_t db, uint32_t sc) {
  asm volatile("{\n.reg .pred p;\nsetp.ne.b32 p, %98, 0;\n"
    "wgmma.mma_async.sync.aligned.m64n192k16.f32.bf16.bf16 "
    "{%0, %1, %2, %3, %4, %5, %6, %7, %8, %9, %10, %11, %12, %13, %14, %15, %16, %17, %18, %19, %20, %21, %22, %23, %24, %25, %26, %27, %28, %29, %30, %31, %32, %33, %34, %35, %36, %37, %38, %39, %40, %41, %42, %43, %44, %45, %46, %47, %48, %49, %50, %51, %52, %53, %54, %55, %56, %57, %58, %59, %60, %61, %62, %63, %64, %65, %66, %67, %68, %69, %70, %71, %72, %73, %74, %75, %76, %77, %78, %79, %80, %81, %82, %83, %84, %85, %86, %87, %88, %89, %90, %91, %92, %93, %94, %95}, %96, %97, p, 1, 1, 0, 1;\n}\n"
    : "+f"(d[0]), "+f"(d[1]), "+f"(d[2]), "+f"(d[3]), "+f"(d[4]), "+f"(d[5]), "+f"(d[6]), "+f"(d[7]), "+f"(d[8]), "+f"(d[9]), "+f"(d[10]), "+f"(d[11]), "+f"(d[12]), "+f"(d[13]), "+f"(d[14]), "+f"(d[15]), "+f"(d[16]), "+f"(d[17]), "+f"(d[18]), "+f"(d[19]), "+f"(d[20]), "+f"(d[21]), "+f"(d[22]), "+f"(d[23]), "+f"(d[24]), "+f"(d[25]), "+f"(d[26]), "+f"(d[27]), "+f"(d[28]), "+f"(d[29]), "+f"(d[30]), "+f"(d[31]), "+f"(d[32]), "+f"(d[33]), "+f"(d[34]), "+f"(d[35]), "+f"(d[36]), "+f"(d[37]), "+f"(d[38]), "+f"(d[39]), "+f"(d[40]), "+f"(d[41]), "+f"(d[42]), "+f"(d[43]), "+f"(d[44]), "+f"(d[45]), "+f"(d[46]), "+f"(d[47]), "+f"(d[48]), "+f"(d[49]), "+f"(d[50]), "+f"(d[51]), "+f"(d[52]), "+f"(d[53]), "+f"(d[54]), "+f"(d[55]), "+f"(d[56]), "+f"(d[57]), "+f"(d[58]), "+f"(d[59]), "+f"(d[60]), "+f"(d[61]), "+f"(d[62]), "+f"(d[63]), "+f"(d[64]), "+f"(d[65]), "+f"(d[66]), "+f"(d[67]), "+f"(d[68]), "+f"(d[69]), "+f"(d[70]), "+f"(d[71]), "+f"(d[72]), "+f"(d[73]), "+f"(d[74]), "+f"(d[75]), "+f"(d[76]), "+f"(d[77]), "+f"(d[78]), "+f"(d[79]), "+f"(d[80]), "+f"(d[81]), "+f"(d[82]), "+f"(d[83]), "+f"(d[84]), "+f"(d[85]), "+f"(d[86]), "+f"(d[87]), "+f"(d[88]), "+f"(d[89]), "+f"(d[90]), "+f"(d[91]), "+f"(d[92]), "+f"(d[93]), "+f"(d[94]), "+f"(d[95])
    : "l"(da), "l"(db), "r"(sc));
}
__device__ __forceinline__ void wgmma_rs_n128(float (&d)[64], uint32_t a0, uint32_t a1, uint32_t a2, uint32_t a3, uint64_t db, uint32_t sc) {
  asm volatile("{\n.reg .pred p;\nsetp.ne.b32 p, %69, 0;\n"
    "wgmma.mma_async.sync.aligned.m64n128k16.f32.bf16.bf16 "
    "{%0, %1, %2, %3, %4, %5, %6, %7, %8, %9, %10, %11, %12, %13, %14, %15, %16, %17, %18, %19, %20, %21, %22, %23, %24, %25, %26, %27, %28, %29, %30, %31, %32, %33, %34, %35, %36, %37, %38, %39, %40, %41, %42, %43, %44, %45, %46, %47, %48, %49, %50, %51, %52, %53, %54, %55, %56, %57, %58, %59, %60, %61, %62, %63}, {%64, %65, %66, %67}, %68, p, 1, 1, 0;\n}\n"
    : "+f"(d[0]), "+f"(d[1]), "+f"(d[2]), "+f"(d[3]), "+f"(d[4]), "+f"(d[5]), "+f"(d[6]), "+f"(d[7]), "+f"(d[8]), "+f"(d[9]), "+f"(d[10]), "+f"(d[11]), "+f"(d[12]), "+f"(d[13]), "+f"(d[14]), "+f"(d[15]), "+f"(d[16]), "+f"(d[17]), "+f"(d[18]), "+f"(d[19]), "+f"(d[20]), "+f"(d[21]), "+f"(d[22]), "+f"(d[23]), "+f"(d[24]), "+f"(d[25]), "+f"(d[26]), "+f"(d[27]), "+f"(d[28]), "+f"(d[29]), "+f"(d[30]), "+f"(d[31]), "+f"(d[32]), "+f"(d[33]), "+f"(d[34]), "+f"(d[35]), "+f"(d[36]), "+f"(d[37]), "+f"(d[38]), "+f"(d[39]), "+f"(d[40]), "+f"(d[41]), "+f"(d[42]), "+f"(d[43]), "+f"(d[44]), "+f"(d[45]), "+f"(d[46]), "+f"(d[47]), "+f"(d[48]), "+f"(d[49]), "+f"(d[50]), "+f"(d[51]), "+f"(d[52]), "+f"(d[53]), "+f"(d[54]), "+f"(d[55]), "+f"(d[56]), "+f"(d[57]), "+f"(d[58]), "+f"(d[59]), "+f"(d[60]), "+f"(d[61]), "+f"(d[62]), "+f"(d[63])
    : "r"(a0), "r"(a1), "r"(a2), "r"(a3), "l"(db), "r"(sc));
}
__device__ __forceinline__ void wgmma_rs_n128_tb(float (&d)[64], uint32_t a0, uint32_t a1, uint32_t a2, uint32_t a3, uint64_t db, uint32_t sc) {
  asm volatile("{\n.reg .pred p;\nsetp.ne.b32 p, %69, 0;\n"
    "wgmma.mma_async.sync.aligned.m64n128k16.f32.bf16.bf16 "
    "{%0, %1, %2, %3, %4, %5, %6, %7, %8, %9, %10, %11, %12, %13, %14, %15, %16, %17, %18, %19, %20, %21, %22, %23, %24, %25, %26, %27, %28, %29, %30, %31, %32, %33, %34, %35, %36, %37, %38, %39, %40, %41, %42, %43, %44, %45, %46, %47, %48, %49, %50, %51, %52, %53, %54, %55, %56, %57, %58, %59, %60, %61, %62, %63}, {%64, %65, %66, %67}, %68, p, 1, 1, 1;\n}\n"
    : "+f"(d[0]), "+f"(d[1]), "+f"(d[2]), "+f"(d[3]), "+f"(d[4]), "+f"(d[5]), "+f"(d[6]), "+f"(d[7]), "+f"(d[8]), "+f"(d[9]), "+f"(d[10]), "+f"(d[11]), "+f"(d[12]), "+f"(d[13]), "+f"(d[14]), "+f"(d[15]), "+f"(d[16]), "+f"(d[17]), "+f"(d[18]), "+f"(d[19]), "+f"(d[20]), "+f"(d[21]), "+f"(d[22]), "+f"(d[23]), "+f"(d[24]), "+f"(d[25]), "+f"(d[26]), "+f"(d[27]), "+f"(d[28]), "+f"(d[29]), "+f"(d[30]), "+f"(d[31]), "+f"(d[32]), "+f"(d[33]), "+f"(d[34]), "+f"(d[35]), "+f"(d[36]), "+f"(d[37]), "+f"(d[38]), "+f"(d[39]), "+f"(d[40]), "+f"(d[41]), "+f"(d[42]), "+f"(d[43]), "+f"(d[44]), "+f"(d[45]), "+f"(d[46]), "+f"(d[47]), "+f"(d[48]), "+f"(d[49]), "+f"(d[50]), "+f"(d[51]), "+f"(d[52]), "+f"(d[53]), "+f"(d[54]), "+f"(d[55]), "+f"(d[56]), "+f"(d[57]), "+f"(d[58]), "+f"(d[59]), "+f"(d[60]), "+f"(d[61]), "+f"(d[62]), "+f"(d[63])
    : "r"(a0), "r"(a1), "r"(a2), "r"(a3), "l"(db), "r"(sc));
}

#define TS(i) do {} while (0)
#define TR(j, i) do {} while (0)
#define TSS(i, c) do {} while (0)

__device__ __forceinline__ uint32_t wrap12(uint32_t p) { return p >= NSLOT ? p - NSLOT : p; }

struct Cons {
  uint32_t sb;
  uint32_t g, pos;
  uint32_t rel;
  uint32_t nstg;
  uint32_t stg;
  uint32_t xr;
  uint32_t zero;
  int wg, lane;
  __device__ __forceinline__ void wait_full(uint32_t gg) const { mbar_wait(sb + SM_BAR + B_FULL + (gg & 7) * 8, (gg >> 3) & 1); }
  __device__ __forceinline__ void release(uint32_t gg) const { if (lane < 2) mbar_arrive_cluster(rel + (gg & 7) * 8); }
  __device__ __forceinline__ void stg_acquire() { mbar_wait(sb + SM_BAR + B_SEMPTY + wg * 8, (nstg & 1) ^ 1); nstg++; }
  __device__ __forceinline__ void stg_publish() const {
    fence_async_smem();
    __syncwarp();
    if (lane == 0) mbar_arrive(sb + SM_BAR + B_SFULL + wg * 8);
  }
};

template <int N, bool FIRST>
__device__ __forceinline__ void gemm_step(float (&acc)[128], Cons& c) {
  const uint32_t p1 = wrap12(c.pos + 1), p2 = wrap12(c.pos + 2);
  const uint64_t da = mkdesc(c.sb + c.wg * 8192 + c.pos * SLOT, 16, 1024);
  const uint64_t b0 = mkdesc(c.sb + p1 * SLOT, 4096, 1024);
  const uint64_t b1 = mkdesc(c.sb + p2 * SLOT, 4096, 1024);
  c.wait_full(c.g);
  wg_fence();
  if (N == 256) {
    wgmma_ss_n256_tb(acc, da, b0, FIRST ? 0 : 1);
    wgmma_ss_n256_tb(acc, da + 2, b0 + 128, 1);
    wgmma_ss_n256_tb(acc, da + 4, b1, 1);
    wgmma_ss_n256_tb(acc, da + 6, b1 + 128, 1);
  } else {
    wgmma_ss_n192_tb(acc, da, b0, FIRST ? 0 : 1);
    wgmma_ss_n192_tb(acc, da + 2, b0 + 128, 1);
    wgmma_ss_n192_tb(acc, da + 4, b1, 1);
    wgmma_ss_n192_tb(acc, da + 6, b1 + 128, 1);
  }
  wg_commit();
  if (!FIRST) {
    wg_wait<1>();
    c.release(c.g - 1);
  }
  c.g++;
  c.pos = wrap12(p2 + 1);
}

template <int N>
__device__ __forceinline__ void gemm_loop(float (&acc)[128], Cons& c, int nk) {
  gemm_step<N, true>(acc, c);
#pragma unroll 1
  for (int k = 1; k < nk; k++) gemm_step<N, false>(acc, c);
  wg_wait<0>();
  c.release(c.g - 1);
  fence_regs(acc);
}

__device__ __forceinline__ float silu_bf(float v) {
  const float f = bf_round(v);
  return __fdividef(f, 1.0f + ex2(-1.4426950408889634f * f));
}

template <int MODE, int B0, int NB>
__device__ __forceinline__ void store_event(const float (&acc)[128], Cons& c) {
  uint32_t r[NB * 16];
#pragma unroll
  for (int i = 0; i < NB * 16; i++) {
    const float lo = acc[B0 * 32 + 2 * i], hi = acc[B0 * 32 + 2 * i + 1];
    r[i] = MODE == 0 ? pack_bf16_relu(lo, hi) : pack_bf16(silu_bf(lo), silu_bf(hi));
  }
  c.stg_acquire();
#pragma unroll
  for (int b = 0; b < NB; b++)
#pragma unroll
    for (int kb = 0; kb < 4; kb++)
      stsm4(c.stg + b * 8192 + (((2 * kb) ^ c.xr) << 4), r[b * 16 + kb * 4], r[b * 16 + kb * 4 + 1], r[b * 16 + kb * 4 + 2], r[b * 16 + kb * 4 + 3]);
  c.stg_publish();
}

template <int N>
__device__ __forceinline__ void h_tile(float (&acc)[128], Cons& c) {
  gemm_loop<N>(acc, c, 16);
  store_event<0, 0, 2>(acc, c);
  store_event<0, 2, N / 64 - 2>(acc, c);
}

constexpr float SM_C = 0.08838834764831845f * 1.4426950408889634f;

#define ONCE(c) _Pragma("unroll 1") for (uint32_t once_ = 0; once_ <= (c).zero; once_++)
__device__ __forceinline__ void row_max2(const float (&S)[64], float& n0, float& n1) {
  float x[4], y[4];
#pragma unroll
  for (int i = 0; i < 4; i++) { x[i] = fmaxf(S[4 * i], S[4 * i + 1]); y[i] = fmaxf(S[4 * i + 2], S[4 * i + 3]); }
#pragma unroll
  for (int i = 4; i < 16; i++) {
    x[i & 3] = fmaxf(x[i & 3], fmaxf(S[4 * i], S[4 * i + 1]));
    y[i & 3] = fmaxf(y[i & 3], fmaxf(S[4 * i + 2], S[4 * i + 3]));
  }
  n0 = fmaxf(fmaxf(x[0], x[1]), fmaxf(x[2], x[3]));
  n1 = fmaxf(fmaxf(y[0], y[1]), fmaxf(y[2], y[3]));
  n0 = fmaxf(n0, __shfl_xor_sync(~0u, n0, 1));
  n1 = fmaxf(n1, __shfl_xor_sync(~0u, n1, 1));
  n0 = fmaxf(n0, __shfl_xor_sync(~0u, n0, 2));
  n1 = fmaxf(n1, __shfl_xor_sync(~0u, n1, 2));
}
__device__ __forceinline__ void to_exponent(float (&S)[64], float cc0, float cc1) {
#pragma unroll
  for (int i = 0; i < 16; i++) {
    S[4 * i] = fmaf(S[4 * i], SM_C, cc0); S[4 * i + 1] = fmaf(S[4 * i + 1], SM_C, cc0);
    S[4 * i + 2] = fmaf(S[4 * i + 2], SM_C, cc1); S[4 * i + 3] = fmaf(S[4 * i + 3], SM_C, cc1);
  }
}
__device__ __forceinline__ void scale_o(float (&O)[64], float f0, float f1) {
#pragma unroll
  for (int i = 0; i < 16; i++) { O[4 * i] *= f0; O[4 * i + 1] *= f0; O[4 * i + 2] *= f1; O[4 * i + 3] *= f1; }
}
__device__ __forceinline__ void exp_stream(float (&S)[64], uint32_t (&p)[32], float (&O)[64], float& cc0, float& cc1, float& l0, float& l1) {
  float s0, s1;
#pragma unroll 1
  for (int pass = 0;; pass++) {
    float a[4] = {0.f, 0.f, 0.f, 0.f};
#pragma unroll
    for (int i = 0; i < 16; i++) {
      const float e0 = ex2(S[4 * i]), e1 = ex2(S[4 * i + 1]), e2 = ex2(S[4 * i + 2]), e3 = ex2(S[4 * i + 3]);
      a[0] += e0; a[1] += e1; a[2] += e2; a[3] += e3;
      p[2 * i] = pack_bf16(e0, e1);
      p[2 * i + 1] = pack_bf16(e2, e3);
    }
    s0 = a[0] + a[1]; s1 = a[2] + a[3];
    if (pass || !__any_sync(~0u, !(fmaxf(s0, s1) <= 65536.f))) break;
    float d0, d1;
    row_max2(S, d0, d1);
    d0 = fmaxf(d0, 0.f); d1 = fmaxf(d1, 0.f);
#pragma unroll
    for (int i = 0; i < 16; i++) { S[4 * i] -= d0; S[4 * i + 1] -= d0; S[4 * i + 2] -= d1; S[4 * i + 3] -= d1; }
    cc0 -= d0; cc1 -= d1;
    const float f0 = ex2(-d0), f1 = ex2(-d1);
    scale_o(O, f0, f1);
    l0 *= f0; l1 *= f1;
  }
  l0 += s0; l1 += s1;
}

__device__ __forceinline__ void inv_rowsum(float l0, float l1, float& i0, float& i1) {
  l0 += __shfl_xor_sync(~0u, l0, 1); l1 += __shfl_xor_sync(~0u, l1, 1);
  l0 += __shfl_xor_sync(~0u, l0, 2); l1 += __shfl_xor_sync(~0u, l1, 2);
  i0 = __fdividef(1.0f, l0); i1 = __fdividef(1.0f, l1);
}
__device__ __forceinline__ void write_o(const float (&O)[64], const Cons& c) {
  uint32_t t;
  asm volatile("mov.u32 %0, %%tid.x;" : "=r"(t));
  const uint32_t stg = c.sb + SM_STG + (t >> 7) * 16384 + ((t >> 5) & 3) * 2048 + (t & 15) * 128;
  const uint32_t xr = ((t >> 4) & 1) ^ (t & 7);
#pragma unroll
  for (int kb = 0; kb < 8; kb++)
    stsm4(stg + (kb >> 2) * 8192 + (((2 * (kb & 3)) ^ xr) << 4),
          pack_bf16(O[8 * kb], O[8 * kb + 1]), pack_bf16(O[8 * kb + 2], O[8 * kb + 3]),
          pack_bf16(O[8 * kb + 4], O[8 * kb + 5]), pack_bf16(O[8 * kb + 6], O[8 * kb + 7]));
  c.stg_publish();
}

__device__ __forceinline__ void issue_qk(float (&S)[64], const uint32_t (&q)[32], uint32_t s0, uint32_t s1, uint32_t zero) {
  const uint64_t d0 = mkdesc(s0, 16, 1024), d1 = mkdesc(s1, 16, 1024);
#pragma unroll
  for (int kk = 0; kk < 8; kk++)
    wgmma_rs_n128(S, q[4 * kk], q[4 * kk + 1], q[4 * kk + 2], q[4 * kk + 3], (kk < 4 ? d0 : d1) + (kk & 3) * 2, kk > 0 ? 1u : zero);
}
__device__ __forceinline__ void issue_pv(float (&O)[64], const uint32_t (&p)[32], uint32_t s0, uint32_t s1, uint32_t accum) {
  const uint64_t d0 = mkdesc(s0, 8192, 1024), d1 = mkdesc(s1, 8192, 1024);
#pragma unroll
  for (int kk = 0; kk < 8; kk++)
    wgmma_rs_n128_tb(O, p[4 * kk], p[4 * kk + 1], p[4 * kk + 2], p[4 * kk + 3], (kk < 4 ? d0 : d1) + (kk & 3) * 128, kk > 0 ? 1u : accum);
}

#define TURN_SYNC()   bar_sync(1 + c.wg, 256)
#define TURN_PASS()   bar_arrive(2 - c.wg, 256)

__device__ __forceinline__ void attn_tile(float (&acc)[128], Cons& c, int t) {
  gemm_loop<256>(acc, c, 16);
  TSS(8 + t, c);
  uint32_t q[32], p[32];
  float S[64], O[64];
  const uint32_t stash = c.sb + SM_STG + c.wg * 16384 + ((threadIdx.x >> 5) & 3) * 2048 + c.lane * 16;
#pragma unroll
  for (int i = 0; i < 32; i++) q[i] = pack_bf16(acc[2 * i], acc[2 * i + 1]);
  c.stg_acquire();
#pragma unroll
  for (int i = 0; i < 8; i++)
    sts128(stash + (i >> 2) * 8192 + (i & 3) * 512, pack_bf16(acc[64 + 8 * i], acc[65 + 8 * i]), pack_bf16(acc[66 + 8 * i], acc[67 + 8 * i]),
           pack_bf16(acc[68 + 8 * i], acc[69 + 8 * i]), pack_bf16(acc[70 + 8 * i], acc[71 + 8 * i]));
  fence_regs(q);
  TR(0, 0);
  TURN_SYNC();
  TR(0, 1);
  c.wait_full(c.g);
  wg_fence();
  issue_qk(S, q, c.sb + c.pos * SLOT, c.sb + wrap12(c.pos + 1) * SLOT, 0);
  wg_commit();
  TURN_PASS();
  TR(0, 2);
  wg_wait<0>();
  TR(0, 3);
  fence_regs(S);
  c.release(c.g);
  c.g++;
  c.pos = wrap12(c.pos + 2);
  float cc0, cc1, l0 = 0.f, l1 = 0.f;
  row_max2(S, cc0, cc1);
  cc0 *= -SM_C; cc1 *= -SM_C;
  to_exponent(S, cc0, cc1);
#pragma unroll
  for (int i = 0; i < 64; i++) O[i] = 0.f;
  exp_stream(S, p, O, cc0, cc1, l0, l1);
#pragma unroll 1
  for (int j = 0; j < 7 + (int)c.zero; j++) {
    const uint32_t k0 = c.pos, k1 = wrap12(k0 + 1), v0 = wrap12(k0 + 2), v1 = wrap12(k0 + 3);
    TR(j + 1, 0);
    TURN_SYNC();
    TR(j + 1, 1);
    c.wait_full(c.g);
    wg_fence();
    issue_qk(S, q, c.sb + k0 * SLOT, c.sb + k1 * SLOT, 0);
    wg_commit();
    c.wait_full(c.g + 1);
    wg_fence();
    issue_pv(O, p, c.sb + v0 * SLOT, c.sb + v1 * SLOT, j != 4);
    wg_commit();
    TURN_PASS();
    TR(j + 1, 2);
    wg_wait<1>();
    TR(j + 1, 3);
    fence_regs(S);
    fence_regs(q);
    c.release(c.g);
    if (j == 2) {
#pragma unroll
      for (int i = 0; i < 8; i++) lds128(stash + (i >> 2) * 8192 + (i & 3) * 512, q[4 * i], q[4 * i + 1], q[4 * i + 2], q[4 * i + 3]);
      __syncwarp();
    }
    float f0, f1;
    if (j == 3) {
      row_max2(S, cc0, cc1);
      cc0 *= -SM_C; cc1 *= -SM_C;
      inv_rowsum(l0, l1, f0, f1);
      l0 = 0.f; l1 = 0.f;
    }
    ONCE(c) { to_exponent(S, cc0, cc1); }
    TR(j + 1, 4);
    wg_wait<0>();
    TR(j + 1, 5);
    fence_regs(O);
    fence_regs(p);
    c.release(c.g + 1);
    c.g += 2;
    c.pos = wrap12(v1 + 1);
    if (j == 3) {
      scale_o(O, f0, f1);
      write_o(O, c);
    }
    TR(j + 1, 6);
    exp_stream(S, p, O, cc0, cc1, l0, l1);
  }
  TR(8, 0);
  TURN_SYNC();
  TR(8, 1);
  c.wait_full(c.g);
  wg_fence();
  issue_pv(O, p, c.sb + c.pos * SLOT, c.sb + wrap12(c.pos + 1) * SLOT, 1);
  wg_commit();
  TURN_PASS();
  TR(8, 2);
  c.stg_acquire();
  float a0, a1;
  inv_rowsum(l0, l1, a0, a1);
  wg_wait<0>();
  TR(8, 5);
  fence_regs(O);
  fence_regs(p);
  c.release(c.g);
  c.g++;
  c.pos = wrap12(c.pos + 2);
  scale_o(O, a0, a1);
  write_o(O, c);
  TR(9, 0);
}

struct Prod {
  uint32_t sb, g, pos, head, tail_g, tail_pos, hist;
  __device__ __forceinline__ uint32_t full() const { return sb + SM_BAR + B_FULL + (g & 7) * 8; }
  __device__ __forceinline__ uint32_t slot(uint32_t i) const { return sb + wrap12(pos + i) * SLOT; }
  __device__ __forceinline__ void acquire(uint32_t size) {
    while (head + size - tail_pos > NSLOT) {
      mbar_wait(sb + SM_BAR + B_EMPTY + (tail_g & 7) * 8, (tail_g >> 3) & 1);
      tail_pos += 2 + ((hist >> (tail_g & 31)) & 1);
      tail_g++;
    }
    hist = (hist & ~(1u << (g & 31))) | ((size - 2) << (g & 31));
  }
  __device__ __forceinline__ void advance(uint32_t size) { g++; head += size; pos = wrap12(pos + size); }
};

__device__ __forceinline__ void wait_flag(const unsigned* p, unsigned target) {
  while ((int)(ld_acquire(p) - target) < 0) {}
  fence_async_all();
}

__global__ void __cluster_dims__(2, 1, 1) __launch_bounds__(384, 1) fused_kernel(const __grid_constant__ Params P) {
  extern __shared__ uint8_t smem_raw[];
  const uint32_t sb = (smem_u32(smem_raw) + 1023u) & ~1023u;
  const int warp = __shfl_sync(~0u, (int)(threadIdx.x >> 5), 0);
  const int lane = threadIdx.x & 31;
  const int rank = blockIdx.x & 1;
  const int cl = blockIdx.x >> 1;
  const int j = cl >> 3;
  const int rb = (cl & 7) * 2 + rank;
  const bool is_s = j < 4;
  const int hn0 = is_s ? HS0 : HF0, hn1 = is_s ? HS1 : HF1;
  const int hc0 = is_s ? j * (HS0 + HS1) : 4 * (HS0 + HS1) + (j - 4) * (HF0 + HF1);
  const int hc1 = hc0 + hn0;
  const int row0 = rb * 128;
  Flags* fl = P.flags;

  if (warp >= 8) {
    if (warp == 8 && lane == 0) {
      for (int i = 0; i < NBAR; i++) { mbar_init(sb + SM_BAR + B_FULL + i * 8, 1); mbar_init(sb + SM_BAR + B_EMPTY + i * 8, 16); }
      for (int i = 0; i < 2; i++) { mbar_init(sb + SM_BAR + B_SFULL + i * 8, 4); mbar_init(sb + SM_BAR + B_SEMPTY + i * 8, 1); }
      mbar_init(sb + SM_BAR + B_DONE, 11);
      asm volatile("fence.mbarrier_init.release.cluster;" ::: "memory");
    }
    if (warp == 9 && lane < 11) prefetch_map(&P.act_ld + lane);
    __syncwarp();
    cluster_arrive();
    cluster_wait();
    asm volatile("setmaxnreg.dec.sync.aligned.u32 24;");
    if (warp == 8) {
      const unsigned ep1 = *(volatile unsigned*)&fl->epoch[blockIdx.x] + 1;
      Prod p{sb, 0, 0, 0, 0, 0, 0};
      for (int t = 0; t < 2; t++) {
        const int n = t ? hn1 : hn0, nb0 = (t ? hc1 : hc0) >> 6;
        const CUtensorMap* mb = n == 256 ? &P.w1b4 : &P.w1b3;
        const uint32_t bytes = 16384 + n * 128;
        int k = 0;
        if (t == 0) {
          for (; k < 4; k++) {
            p.acquire(3);
            if (lane == 0) { mbar_expect_tx(p.full(), bytes); tma_ld3_mc(p.slot(1 + rank), mb, p.full(), 0, k * 64 + rank * 32, nb0); }
            p.advance(3);
          }
          wait_flag(&fl->ln[rb][0], ep1 * 8);
          if (lane == 0)
            for (int i = 0; i < 4; i++) tma_ld2(sb + i * 3 * SLOT, &P.act_ld, sb + SM_BAR + B_FULL + i * 8, C_XN + i * 64, row0);
        }
        for (; k < 16; k++) {
          p.acquire(3);
          if (lane == 0) {
            mbar_expect_tx(p.full(), bytes);
            tma_ld3_mc(p.slot(1 + rank), mb, p.full(), 0, k * 64 + rank * 32, nb0);
            tma_ld2(p.slot(0), &P.act_ld, p.full(), C_XN + k * 64, row0);
          }
          p.advance(3);
        }
      }
      const int kvrow = (j >> 1) * SK + KV0;
      for (int t = 0; t < 2; t++) {
        const int nb0 = (4 * j + 2 * t) * 2;
        for (int k = 0; k < 16; k++) {
          p.acquire(3);
          if (lane == 0) {
            mbar_expect_tx(p.full(), 49152);
            tma_ld3_mc(p.slot(1 + rank), &P.wq, p.full(), 0, k * 64 + rank * 32, nb0);
            tma_ld2(p.slot(0), &P.act_ld, p.full(), C_XN + k * 64, row0);
          }
          p.advance(3);
        }
        for (int i = 0; i < 16; i++) {
          const bool is_k = i == 0 || (i < 15 && (i & 1));
          const int ch = (is_k ? ((i + 1) >> 1) : (i == 15 ? 7 : (i >> 1) - 1)) & 3;
          p.acquire(2);
          if (lane == 0) {
            mbar_expect_tx(p.full(), 32768);
            if (is_k) tma_ld2_mc(p.slot(rank), &P.k_ld, p.full(), rank * 64, kvrow + ch * 128);
            else      tma_ld3_mc(p.slot(rank), &P.v_ld, p.full(), 0, kvrow + ch * 128 + rank * 64, 0);
          }
          p.advance(2);
        }
        if (t == 0 && !is_s) wait_flag(&fl->h[rb][0], ep1 * 64);
      }
      const int jn = j & 3;
      if (is_s) {
        unsigned ready = 0;
        for (int i = 0; i < 64; i++) {
          const int hi = i >> 1;
          const int head = 4 * ((hi & 15) >> 1) + (hi & 1) + ((hi >> 4) << 1);
          const int kc = head * 128 + (i & 1) * 64;
          p.acquire(3);
          if (lane == 0) { mbar_expect_tx(p.full(), 49152); tma_ld3_mc(p.slot(1 + rank), &P.wo, p.full(), 0, kc + rank * 32, jn * 4); }
          if (!((ready >> head) & 1)) {
            do { ready = __ballot_sync(~0u, (int)(ld_acquire(&fl->o[rb][lane]) - ep1 * 2) >= 0); } while (!((ready >> head) & 1));
            __syncwarp();
            fence_async_all();
          }
          if (lane == 0) tma_ld2(p.slot(0), &P.act_ld, p.full(), C_O + kc, row0);
          p.advance(3);
        }
        for (int i = 0; i < 4; i++) {
          p.acquire(2);
          if (i == 2) wait_flag(&fl->g[rb][jn], ep1 * 4);
          if (lane == 0) {
            mbar_expect_tx(p.full(), 32768);
            const CUtensorMap* m = i < 2 ? &P.x_ld : &P.act_ld;
            const int c0 = (i < 2 ? 0 : C_G) + jn * 256 + (i & 1) * 128;
            tma_ld2(p.slot(0), m, p.full(), c0, row0);
            tma_ld2(p.slot(1), m, p.full(), c0 + 64, row0);
          }
          p.advance(2);
        }
      } else {
        for (int k = 0; k < 56; k++) {
          p.acquire(3);
          if (lane == 0) {
            mbar_expect_tx(p.full(), 49152);
            tma_ld3_mc(p.slot(1 + rank), &P.w2, p.full(), 0, k * 64 + rank * 32, jn * 4);
            tma_ld2(p.slot(0), &P.act_ld, p.full(), C_H + k * 64, row0);
          }
          p.advance(3);
        }
      }
      if (lane == 0) { *(volatile unsigned*)&fl->epoch[blockIdx.x] = ep1; mbar_arrive(sb + SM_BAR + B_DONE); }
    } else if (warp < 11) {
      const int wg = warp - 9;
      if (lane == 0) {
        const uint32_t stg = sb + SM_STG + wg * 16384;
        const int nev = is_s ? 8 : 10;
        for (int n = 0; n < nev; n++) {
          int col, nbox = 2;
          unsigned* flag;
          if (n < 4) {
            col = C_H + ((n & 2) ? hc1 : hc0) + (n & 1) * 128;
            if ((n & 1) && ((n & 2) ? hn1 : hn0) == 192) nbox = 1;
            flag = &fl->h[rb][0];
          } else if (n < 8) {
            col = C_O + (4 * j + n - 4) * 128;
            flag = &fl->o[rb][4 * j + n - 4];
          } else {
            col = C_G + (j & 3) * 256 + (n - 8) * 128;
            flag = &fl->g[rb][j & 3];
          }
          mbar_wait(sb + SM_BAR + B_SFULL + wg * 8, n & 1);
          tma_st2(&P.act_st, stg, col, row0 + wg * 64);
          if (nbox == 2) tma_st2(&P.act_st, stg + 8192, col + 64, row0 + wg * 64);
          bulk_commit();
          bulk_wait_read0();
          mbar_arrive(sb + SM_BAR + B_SEMPTY + wg * 8);
          bulk_wait0();
          fence_async_all();
          red_release(flag, 1);
        }
        mbar_arrive(sb + SM_BAR + B_DONE);
      }
    } else {
      if (lane == 0) {
        const unsigned long long t0 = gtime();
        while (!mbar_try(sb + SM_BAR + B_DONE, 0))
          if (gtime() - t0 > 2000000000ull) __trap();
      }
    }
    __syncwarp();
    cluster_arrive();
    cluster_wait();
  } else {
    const int wg = warp >> 2;
    TS(0);
    {
      const int r = row0 + j * 16 + warp * 2;
      uint4 v[2][4];
#pragma unroll
      for (int a = 0; a < 2; a++)
#pragma unroll
        for (int i = 0; i < 4; i++) v[a][i] = __ldg((const uint4*)(P.x + (size_t)(r + a) * DM + i * 256 + lane * 8));
      cluster_arrive();
#pragma unroll
      for (int a = 0; a < 2; a++) {
        float f[32];
#pragma unroll
        for (int i = 0; i < 4; i++) {
          f[8 * i] = bf_lo(v[a][i].x); f[8 * i + 1] = bf_hi(v[a][i].x); f[8 * i + 2] = bf_lo(v[a][i].y); f[8 * i + 3] = bf_hi(v[a][i].y);
          f[8 * i + 4] = bf_lo(v[a][i].z); f[8 * i + 5] = bf_hi(v[a][i].z); f[8 * i + 6] = bf_lo(v[a][i].w); f[8 * i + 7] = bf_hi(v[a][i].w);
        }
        float s = 0.f;
#pragma unroll
        for (int i = 0; i < 32; i++) s += f[i];
#pragma unroll
        for (int o = 16; o; o >>= 1) s += __shfl_xor_sync(~0u, s, o);
        const float mean = s * (1.0f / DM);
        float q = 0.f;
#pragma unroll
        for (int i = 0; i < 32; i++) { const float d = f[i] - mean; q = fmaf(d, d, q); }
#pragma unroll
        for (int o = 16; o; o >>= 1) q += __shfl_xor_sync(~0u, q, o);
        const float mb = bf_round(mean);
        const float sd = bf_round(sqrtf(bf_round(bf_round(q * (1.0f / DM)) + 1e-5f)));
        const float inv = 1.0f / sd;
#pragma unroll
        for (int i = 0; i < 4; i++) {
          uint4 o;
          o.x = pack_bf16(bf_round(f[8 * i] - mb) * inv, bf_round(f[8 * i + 1] - mb) * inv);
          o.y = pack_bf16(bf_round(f[8 * i + 2] - mb) * inv, bf_round(f[8 * i + 3] - mb) * inv);
          o.z = pack_bf16(bf_round(f[8 * i + 4] - mb) * inv, bf_round(f[8 * i + 5] - mb) * inv);
          o.w = pack_bf16(bf_round(f[8 * i + 6] - mb) * inv, bf_round(f[8 * i + 7] - mb) * inv);
          *(uint4*)(P.act + (size_t)(r + a) * ACT_W + C_XN + i * 256 + lane * 8) = o;
        }
      }
      fence_async_all();
      bar_sync(5, 256);
      if (threadIdx.x == 0) red_release(&fl->ln[rb][0], 1);
      cluster_wait();
    }
    asm volatile("setmaxnreg.inc.sync.aligned.u32 240;");
    Cons c;
        c.zero = blockIdx.y; c.sb = sb; c.g = 0; c.pos = 0; c.nstg = 0; c.wg = wg; c.lane = lane;
    c.rel = mapa(sb + SM_BAR + B_EMPTY, lane & 1);
    const uint32_t rowoff = (warp & 3) * 2048 + ((lane & 7) + ((lane >> 3) & 1) * 8) * 128;
    c.stg = sb + SM_STG + wg * 16384 + rowoff;
    c.xr = (lane >> 4) ^ (lane & 7);
    if (wg == 1) bar_arrive(1, 256);
    float acc[128];
    TS(1);
    if (hn0 == 256) h_tile<256>(acc, c); else h_tile<192>(acc, c);
    TSS(2, c);
    if (hn1 == 256) h_tile<256>(acc, c); else h_tile<192>(acc, c);
    TSS(3, c);
#pragma unroll 1
    for (int t = 0; t < 2; t++) {
      attn_tile(acc, c, t);
      TSS(4 + t, c);
    }
    gemm_loop<256>(acc, c, is_s ? 64 : 56);
    TSS(6, c);
    if (is_s) {
      const uint32_t x0 = c.pos;
      c.wait_full(c.g);
  #pragma unroll
      for (int b = 0; b < 4; b++) {
        if ((b & 1) == 0) c.wait_full(c.g + 2 + (b >> 1));
        const uint32_t xs = sb + wrap12(x0 + b) * SLOT + wg * 8192;
        const uint32_t sx = xs + rowoff, sg = sb + wrap12(wrap12(x0 + 4) + b) * SLOT + wg * 8192 + rowoff;
#pragma unroll
        for (int kb = 0; kb < 4; kb++) {
          const uint32_t off = ((2 * kb) ^ c.xr) << 4;
          uint32_t xv[4], gv[4];
          ldsm4(sx + off, xv[0], xv[1], xv[2], xv[3]);
          ldsm4(sg + off, gv[0], gv[1], gv[2], gv[3]);
#pragma unroll
          for (int r = 0; r < 4; r++) {
            const uint32_t s2 = pack_bf16(acc[32 * b + 8 * kb + 2 * r], acc[32 * b + 8 * kb + 2 * r + 1]);
            const __nv_bfloat162 pr = __hmul2_rn(*(const __nv_bfloat162*)&s2, *(const __nv_bfloat162*)&gv[r]);
            const __nv_bfloat162 o = __hadd2_rn(*(const __nv_bfloat162*)&xv[r], pr);
            xv[r] = *(const uint32_t*)&o;
          }
          stsm4(sx + off, xv[0], xv[1], xv[2], xv[3]);
        }
        fence_async_smem();
        bar_sync(3 + wg, 128);
        if ((threadIdx.x & 127) == 0) { tma_st2(&P.out_st, xs, (j & 3) * 256 + b * 64, row0 + wg * 64); bulk_commit(); }
      }
      if ((threadIdx.x & 127) == 0) bulk_wait0();
    } else {
      store_event<1, 0, 2>(acc, c);
      store_event<1, 2, 2>(acc, c);
    }
    TSS(7, c);
    __syncwarp();
    if (lane == 0) mbar_arrive(sb + SM_BAR + B_DONE);
    cluster_arrive();
    cluster_wait();
  }
}

typedef CUresult (*EncodeFn)(CUtensorMap*, CUtensorMapDataType, cuuint32_t, void*, const cuuint64_t*, const cuuint64_t*,
                             const cuuint32_t*, const cuuint32_t*, CUtensorMapInterleave, CUtensorMapSwizzle,
                             CUtensorMapL2promotion, CUtensorMapFloatOOBfill);

void map2d(EncodeFn enc, CUtensorMap* m, const void* base, uint64_t cols, uint64_t rows, uint32_t box_rows) {
  cuuint64_t dims[2] = {cols, rows};
  cuuint64_t strides[1] = {cols * 2};
  cuuint32_t box[2] = {64, box_rows};
  cuuint32_t es[2] = {1, 1};
  enc(m, CU_TENSOR_MAP_DATA_TYPE_BFLOAT16, 2, (void*)base, dims, strides, box, es, CU_TENSOR_MAP_INTERLEAVE_NONE,
      CU_TENSOR_MAP_SWIZZLE_128B, CU_TENSOR_MAP_L2_PROMOTION_L2_256B, CU_TENSOR_MAP_FLOAT_OOB_FILL_NONE);
}
void map3d(EncodeFn enc, CUtensorMap* m, const void* base, uint64_t cols, uint64_t rows, uint32_t box_rows, uint32_t box_blks) {
  cuuint64_t dims[3] = {64, rows, cols / 64};
  cuuint64_t strides[2] = {cols * 2, 128};
  cuuint32_t box[3] = {64, box_rows, box_blks};
  cuuint32_t es[3] = {1, 1, 1};
  enc(m, CU_TENSOR_MAP_DATA_TYPE_BFLOAT16, 3, (void*)base, dims, strides, box, es, CU_TENSOR_MAP_INTERLEAVE_NONE,
      CU_TENSOR_MAP_SWIZZLE_128B, CU_TENSOR_MAP_L2_PROMOTION_L2_256B, CU_TENSOR_MAP_FLOAT_OOB_FILL_NONE);
}

}

extern "C" void kernel_launch(void* const* d_in, const int* in_sizes, int n_in, void* d_out, int out_size) {
  (void)in_sizes; (void)n_in; (void)out_size;
  static EncodeFn enc = nullptr;
  static void* act = nullptr;
  static void* flags = nullptr;
  if (!enc) {
    void* fn = nullptr;
    cudaDriverEntryPointQueryResult qr;
    cudaGetDriverEntryPoint("cuTensorMapEncodeTiled", &fn, cudaEnableDefault, &qr);
    enc = (EncodeFn)fn;
    cudaGetSymbolAddress(&act, g_act);
    cudaGetSymbolAddress(&flags, g_flags);
    cudaFuncSetAttribute(fused_kernel, cudaFuncAttributeMaxDynamicSharedMemorySize, SMEM_BYTES);
  }
  Params P;
  map2d(enc, &P.act_ld, act, ACT_W, SEQ, 128);
  map2d(enc, &P.act_st, act, ACT_W, SEQ, 64);
  map2d(enc, &P.x_ld, d_in[0], DM, SEQ, 128);
  map2d(enc, &P.out_st, d_out, DM, SEQ, 64);
  map2d(enc, &P.k_ld, d_in[1], 128, 4 * SK, 128);
  map3d(enc, &P.v_ld, d_in[2], 128, 4 * SK, 64, 2);
  map3d(enc, &P.wq, d_in[3], NQ, DM, 32, 4);
  map3d(enc, &P.w1b4, d_in[6], DFF, DM, 32, 4);
  map3d(enc, &P.w1b3, d_in[6], DFF, DM, 32, 3);
  map3d(enc, &P.wo, d_in[4], DM, NQ, 32, 4);
  map3d(enc, &P.w2, d_in[7], DM, DFF, 32, 4);
  P.x = (const __nv_bfloat16*)d_in[0];
  P.act = (__nv_bfloat16*)act;
  P.flags = (Flags*)flags;
  fused_kernel<<<NCLUSTER * 2, 384, SMEM_BYTES>>>(P);
}
```

```cpp
#include <cuda_runtime.h>
#include <cuda_bf16.h>
#include <cuda.h>
#include <stdint.h>

namespace {

constexpr int SEQ    = 2048;
constexpr int DM     = 1024;
constexpr int NQ     = 4096;
constexpr int DFF    = 3584;
constexpr int SK     = 2048;
constexpr int WIN    = 512;
constexpr int KV0    = SK - WIN;
constexpr int C_XN = 0, C_O = 1024, C_H = 5120, C_G = 8704, ACT_W = 9728;

#define HS0 192
#define HS1 192
#define HF0 256
#define HF1 256
static_assert(4 * (HS0 + HS1 + HF0 + HF1) == DFF, "H split");

constexpr int NSLOT = 12, SLOT = 16384, NBAR = 8;
constexpr int SM_STG = NSLOT * SLOT;
constexpr int SM_BAR = SM_STG + 2 * 16384;
constexpr int SMEM_BYTES = SM_BAR + 256 + 1024 + 1536;
constexpr int B_FULL = 0, B_EMPTY = 64, B_SFULL = 128, B_SEMPTY = 144, B_DONE = 160;

constexpr int NCLUSTER = 64;

struct Flags {
  unsigned ln[16][32];
  unsigned h[16][32];
  unsigned o[16][32];
  unsigned g[16][32];
  unsigned epoch[160];
};
__device__ __nv_bfloat16 g_act[(size_t)SEQ * ACT_W];
__device__ Flags g_flags;

struct Params {
  CUtensorMap act_ld, act_st, x_ld, out_st, k_ld, v_ld, wq, w1b4, w1b3, wo, w2;
  const __nv_bfloat16* x;
  __nv_bfloat16* act;
  Flags* flags;
};

__device__ __forceinline__ uint32_t smem_u32(const void* p) { return (uint32_t)__cvta_generic_to_shared(p); }
__device__ __forceinline__ void mbar_init(uint32_t bar, uint32_t cnt) {
  asm volatile("mbarrier.init.shared::cta.b64 [%0], %1;" ::"r"(bar), "r"(cnt) : "memory");
}
__device__ __forceinline__ bool mbar_try(uint32_t bar, uint32_t parity) {
  uint32_t ok;
  asm volatile("{\n.reg .pred p;\nmbarrier.try_wait.parity.shared::cta.b64 p, [%1], %2;\nselp.u32 %0, 1, 0, p;\n}\n"
               : "=r"(ok) : "r"(bar), "r"(parity) : "memory");
  return ok;
}
__device__ __forceinline__ void mbar_wait(uint32_t bar, uint32_t parity) {
  asm volatile("{\n.reg .pred p;\nWAIT_%=:\nmbarrier.try_wait.parity.shared::cta.b64 p, [%0], %1;\n@p bra DONE_%=;\nbra WAIT_%=;\nDONE_%=:\n}\n"
               ::"r"(bar), "r"(parity) : "memory");
}
__device__ __forceinline__ void mbar_arrive(uint32_t bar) {
  asm volatile("mbarrier.arrive.shared::cta.b64 _, [%0];" ::"r"(bar) : "memory");
}
__device__ __forceinline__ void mbar_arrive_cluster(uint32_t cluster_addr) {
  asm volatile("mbarrier.arrive.shared::cluster.b64 _, [%0];" ::"r"(cluster_addr) : "memory");
}
__device__ __forceinline__ void mbar_expect_tx(uint32_t bar, uint32_t bytes) {
  asm volatile("mbarrier.arrive.expect_tx.shared::cta.b64 _, [%0], %1;" ::"r"(bar), "r"(bytes) : "memory");
}
__device__ __forceinline__ uint32_t mapa(uint32_t addr, uint32_t rank) {
  uint32_t r;
  asm("mapa.shared::cluster.u32 %0, %1, %2;" : "=r"(r) : "r"(addr), "r"(rank));
  return r;
}
__device__ __forceinline__ void cluster_arrive() { asm volatile("barrier.cluster.arrive.relaxed.aligned;" ::: "memory"); }
__device__ __forceinline__ void cluster_wait() { asm volatile("barrier.cluster.wait.acquire.aligned;" ::: "memory"); }
__device__ __forceinline__ void bar_sync(int id, int n) { asm volatile("bar.sync %0, %1;" ::"r"(id), "r"(n) : "memory"); }
__device__ __forceinline__ void bar_arrive(int id, int n) { asm volatile("bar.arrive %0, %1;" ::"r"(id), "r"(n) : "memory"); }
__device__ __forceinline__ void fence_async_smem() { asm volatile("fence.proxy.async.shared::cta;" ::: "memory"); }
__device__ __forceinline__ void fence_async_all() { asm volatile("fence.proxy.async.global;" ::: "memory"); }

__device__ __forceinline__ void tma_ld2(uint32_t dst, const CUtensorMap* m, uint32_t bar, int c0, int c1) {
  asm volatile("cp.async.bulk.tensor.2d.shared::cluster.global.mbarrier::complete_tx::bytes [%0], [%1, {%3, %4}], [%2];"
               ::"r"(dst), "l"(m), "r"(bar), "r"(c0), "r"(c1) : "memory");
}
__device__ __forceinline__ void tma_ld2_mc(uint32_t dst, const CUtensorMap* m, uint32_t bar, int c0, int c1) {
  asm volatile("cp.async.bulk.tensor.2d.shared::cluster.global.mbarrier::complete_tx::bytes.multicast::cluster [%0], [%1, {%3, %4}], [%2], %5;"
               ::"r"(dst), "l"(m), "r"(bar), "r"(c0), "r"(c1), "h"((uint16_t)3) : "memory");
}
__device__ __forceinline__ void tma_ld3_mc(uint32_t dst, const CUtensorMap* m, uint32_t bar, int c0, int c1, int c2) {
  asm volatile("cp.async.bulk.tensor.3d.shared::cluster.global.mbarrier::complete_tx::bytes.multicast::cluster [%0], [%1, {%3, %4, %5}], [%2], %6;"
               ::"r"(dst), "l"(m), "r"(bar), "r"(c0), "r"(c1), "r"(c2), "h"((uint16_t)3) : "memory");
}
__device__ __forceinline__ void tma_ld3_mc_hint(uint32_t dst, const CUtensorMap* m, uint32_t bar, int c0, int c1, int c2, uint64_t pol) {
  asm volatile("cp.async.bulk.tensor.3d.shared::cluster.global.mbarrier::complete_tx::bytes.multicast::cluster.L2::cache_hint [%0], [%1, {%3, %4, %5}], [%2], %6, %7;"
               ::"r"(dst), "l"(m), "r"(bar), "r"(c0), "r"(c1), "r"(c2), "h"((uint16_t)3), "l"(pol) : "memory");
}
__device__ __forceinline__ uint64_t policy_evict_first() {
  uint64_t p;
  asm volatile("createpolicy.fractional.L2::evict_first.b64 %0, 1.0;" : "=l"(p));
  return p;
}
__device__ __forceinline__ void tma_st2(const CUtensorMap* m, uint32_t src, int c0, int c1) {
  asm volatile("cp.async.bulk.tensor.2d.global.shared::cta.bulk_group [%0, {%2, %3}], [%1];"
               ::"l"(m), "r"(src), "r"(c0), "r"(c1) : "memory");
}
__device__ __forceinline__ void tma_pf3(const CUtensorMap* m, int c0, int c1, int c2) {
  asm volatile("cp.async.bulk.prefetch.tensor.3d.L2.global [%0, {%1, %2, %3}];" ::"l"(m), "r"(c0), "r"(c1), "r"(c2) : "memory");
}
__device__ __forceinline__ void bulk_commit() { asm volatile("cp.async.bulk.commit_group;" ::: "memory"); }
__device__ __forceinline__ void bulk_wait_read0() { asm volatile("cp.async.bulk.wait_group.read 0;" ::: "memory"); }
__device__ __forceinline__ void bulk_wait0() { asm volatile("cp.async.bulk.wait_group 0;" ::: "memory"); }
__device__ __forceinline__ void prefetch_map(const CUtensorMap* m) {
  asm volatile("prefetch.tensormap [%0];" ::"l"(m) : "memory");
}
__device__ __forceinline__ unsigned ld_acquire(const unsigned* p) {
  unsigned v;
  asm volatile("ld.acquire.gpu.global.u32 %0, [%1];" : "=r"(v) : "l"(p) : "memory");
  return v;
}
__device__ __forceinline__ void red_release(unsigned* p, unsigned v) {
  asm volatile("red.release.gpu.global.add.u32 [%0], %1;" ::"l"(p), "r"(v) : "memory");
}
__device__ __forceinline__ void wg_fence() { asm volatile("wgmma.fence.sync.aligned;" ::: "memory"); }
__device__ __forceinline__ void wg_commit() { asm volatile("wgmma.commit_group.sync.aligned;" ::: "memory"); }
template <int N> __device__ __forceinline__ void wg_wait() { asm volatile("wgmma.wait_group.sync.aligned %0;" ::"n"(N) : "memory"); }
template <int N> __device__ __forceinline__ void fence_regs(float (&d)[N]) {
#pragma unroll
  for (int i = 0; i < N; i++) asm volatile("" : "+f"(d[i])::"memory");
}
template <int N> __device__ __forceinline__ void fence_regs(uint32_t (&d)[N]) {
#pragma unroll
  for (int i = 0; i < N; i++) asm volatile("" : "+r"(d[i])::"memory");
}
__device__ __forceinline__ uint64_t mkdesc(uint32_t addr, uint32_t lbo, uint32_t sbo) {
  return (uint64_t)((addr & 0x3FFFF) >> 4) | ((uint64_t)(lbo >> 4) << 16) | ((uint64_t)(sbo >> 4) << 32) | (1ull << 62);
}
__device__ __forceinline__ uint32_t pack_bf16(float lo, float hi) {
  uint32_t r;
  asm("cvt.rn.bf16x2.f32 %0, %1, %2;" : "=r"(r) : "f"(hi), "f"(lo));
  return r;
}
__device__ __forceinline__ uint32_t pack_bf16_relu(float lo, float hi) {
  uint32_t r;
  asm("cvt.rn.relu.bf16x2.f32 %0, %1, %2;" : "=r"(r) : "f"(hi), "f"(lo));
  return r;
}
__device__ __forceinline__ float bf_lo(uint32_t v) { return __uint_as_float(v << 16); }
__device__ __forceinline__ float bf_hi(uint32_t v) { return __uint_as_float(v & 0xFFFF0000u); }
__device__ __forceinline__ float bf_round(float v) { return __bfloat162float(__float2bfloat16_rn(v)); }
__device__ __forceinline__ float ex2(float x) {
  float r;
  asm("ex2.approx.ftz.f32 %0, %1;" : "=f"(r) : "f"(x));
  return r;
}
__device__ __forceinline__ void stsm4(uint32_t addr, uint32_t r0, uint32_t r1, uint32_t r2, uint32_t r3) {
  asm volatile("stmatrix.sync.aligned.m8n8.x4.shared.b16 [%0], {%1, %2, %3, %4};" ::"r"(addr), "r"(r0), "r"(r1), "r"(r2), "r"(r3) : "memory");
}
__device__ __forceinline__ void ldsm4(uint32_t addr, uint32_t& r0, uint32_t& r1, uint32_t& r2, uint32_t& r3) {
  asm volatile("ldmatrix.sync.aligned.m8n8.x4.shared.b16 {%0, %1, %2, %3}, [%4];" : "=r"(r0), "=r"(r1), "=r"(r2), "=r"(r3) : "r"(addr) : "memory");
}
__device__ __forceinline__ void sts128(uint32_t addr, uint32_t r0, uint32_t r1, uint32_t r2, uint32_t r3) {
  asm volatile("st.shared.v4.b32 [%0], {%1, %2, %3, %4};" ::"r"(addr), "r"(r0), "r"(r1), "r"(r2), "r"(r3) : "memory");
}
__device__ __forceinline__ void lds128(uint32_t addr, uint32_t& r0, uint32_t& r1, uint32_t& r2, uint32_t& r3) {
  asm volatile("ld.shared.v4.b32 {%0, %1, %2, %3}, [%4];" : "=r"(r0), "=r"(r1), "=r"(r2), "=r"(r3) : "r"(addr) : "memory");
}
__device__ __forceinline__ unsigned long long gtime() {
  unsigned long long t;
  asm volatile("mov.u64 %0, %globaltimer;" : "=l"(t));
  return t;
}

__device__ __forceinline__ void wgmma_ss_n256_tb(float (&d)[128], uint64_t da, uint64_t db, uint32_t sc) {
  asm volatile("{\n.reg .pred p;\nsetp.ne.b32 p, %130, 0;\n"
    "wgmma.mma_async.sync.aligned.m64n256k16.f32.bf16.bf16 "
    "{%0, %1, %2, %3, %4, %5, %6, %7, %8, %9, %10, %11, %12, %13, %14, %15, %16, %17, %18, %19, %20, %21, %22, %23, %24, %25, %26, %27, %28, %29, %30, %31, %32, %33, %34, %35, %36, %37, %38, %39, %40, %41, %42, %43, %44, %45, %46, %47, %48, %49, %50, %51, %52, %53, %54, %55, %56, %57, %58, %59, %60, %61, %62, %63, %64, %65, %66, %67, %68, %69, %70, %71, %72, %73, %74, %75, %76, %77, %78, %79, %80, %81, %82, %83, %84, %85, %86, %87, %88, %89, %90, %91, %92, %93, %94, %95, %96, %97, %98, %99, %100, %101, %102, %103, %104, %105, %106, %107, %108, %109, %110, %111, %112, %113, %114, %115, %116, %117, %118, %119, %120, %121, %122, %123, %124, %125, %126, %127}, %128, %129, p, 1, 1, 0, 1;\n}\n"
    : "+f"(d[0]), "+f"(d[1]), "+f"(d[2]), "+f"(d[3]), "+f"(d[4]), "+f"(d[5]), "+f"(d[6]), "+f"(d[7]), "+f"(d[8]), "+f"(d[9]), "+f"(d[10]), "+f"(d[11]), "+f"(d[12]), "+f"(d[13]), "+f"(d[14]), "+f"(d[15]), "+f"(d[16]), "+f"(d[17]), "+f"(d[18]), "+f"(d[19]), "+f"(d[20]), "+f"(d[21]), "+f"(d[22]), "+f"(d[23]), "+f"(d[24]), "+f"(d[25]), "+f"(d[26]), "+f"(d[27]), "+f"(d[28]), "+f"(d[29]), "+f"(d[30]), "+f"(d[31]), "+f"(d[32]), "+f"(d[33]), "+f"(d[34]), "+f"(d[35]), "+f"(d[36]), "+f"(d[37]), "+f"(d[38]), "+f"(d[39]), "+f"(d[40]), "+f"(d[41]), "+f"(d[42]), "+f"(d[43]), "+f"(d[44]), "+f"(d[45]), "+f"(d[46]), "+f"(d[47]), "+f"(d[48]), "+f"(d[49]), "+f"(d[50]), "+f"(d[51]), "+f"(d[52]), "+f"(d[53]), "+f"(d[54]), "+f"(d[55]), "+f"(d[56]), "+f"(d[57]), "+f"(d[58]), "+f"(d[59]), "+f"(d[60]), "+f"(d[61]), "+f"(d[62]), "+f"(d[63]), "+f"(d[64]), "+f"(d[65]), "+f"(d[66]), "+f"(d[67]), "+f"(d[68]), "+f"(d[69]), "+f"(d[70]), "+f"(d[71]), "+f"(d[72]), "+f"(d[73]), "+f"(d[74]), "+f"(d[75]), "+f"(d[76]), "+f"(d[77]), "+f"(d[78]), "+f"(d[79]), "+f"(d[80]), "+f"(d[81]), "+f"(d[82]), "+f"(d[83]), "+f"(d[84]), "+f"(d[85]), "+f"(d[86]), "+f"(d[87]), "+f"(d[88]), "+f"(d[89]), "+f"(d[90]), "+f"(d[91]), "+f"(d[92]), "+f"(d[93]), "+f"(d[94]), "+f"(d[95]), "+f"(d[96]), "+f"(d[97]), "+f"(d[98]), "+f"(d[99]), "+f"(d[100]), "+f"(d[101]), "+f"(d[102]), "+f"(d[103]), "+f"(d[104]), "+f"(d[105]), "+f"(d[106]), "+f"(d[107]), "+f"(d[108]), "+f"(d[109]), "+f"(d[110]), "+f"(d[111]), "+f"(d[112]), "+f"(d[113]), "+f"(d[114]), "+f"(d[115]), "+f"(d[116]), "+f"(d[117]), "+f"(d[118]), "+f"(d[119]), "+f"(d[120]), "+f"(d[121]), "+f"(d[122]), "+f"(d[123]), "+f"(d[124]), "+f"(d[125]), "+f"(d[126]), "+f"(d[127])
    : "l"(da), "l"(db), "r"(sc));
}
__device__ __forceinline__ void wgmma_ss_n192_tb(float (&d)[128], uint64_t da, uint64_t db, uint32_t sc) {
  asm volatile("{\n.reg .pred p;\nsetp.ne.b32 p, %98, 0;\n"
    "wgmma.mma_async.sync.aligned.m64n192k16.f32.bf16.bf16 "
    "{%0, %1, %2, %3, %4, %5, %6, %7, %8, %9, %10, %11, %12, %13, %14, %15, %16, %17, %18, %19, %20, %21, %22, %23, %24, %25, %26, %27, %28, %29, %30, %31, %32, %33, %34, %35, %36, %37, %38, %39, %40, %41, %42, %43, %44, %45, %46, %47, %48, %49, %50, %51, %52, %53, %54, %55, %56, %57, %58, %59, %60, %61, %62, %63, %64, %65, %66, %67, %68, %69, %70, %71, %72, %73, %74, %75, %76, %77, %78, %79, %80, %81, %82, %83, %84, %85, %86, %87, %88, %89, %90, %91, %92, %93, %94, %95}, %96, %97, p, 1, 1, 0, 1;\n}\n"
    : "+f"(d[0]), "+f"(d[1]), "+f"(d[2]), "+f"(d[3]), "+f"(d[4]), "+f"(d[5]), "+f"(d[6]), "+f"(d[7]), "+f"(d[8]), "+f"(d[9]), "+f"(d[10]), "+f"(d[11]), "+f"(d[12]), "+f"(d[13]), "+f"(d[14]), "+f"(d[15]), "+f"(d[16]), "+f"(d[17]), "+f"(d[18]), "+f"(d[19]), "+f"(d[20]), "+f"(d[21]), "+f"(d[22]), "+f"(d[23]), "+f"(d[24]), "+f"(d[25]), "+f"(d[26]), "+f"(d[27]), "+f"(d[28]), "+f"(d[29]), "+f"(d[30]), "+f"(d[31]), "+f"(d[32]), "+f"(d[33]), "+f"(d[34]), "+f"(d[35]), "+f"(d[36]), "+f"(d[37]), "+f"(d[38]), "+f"(d[39]), "+f"(d[40]), "+f"(d[41]), "+f"(d[42]), "+f"(d[43]), "+f"(d[44]), "+f"(d[45]), "+f"(d[46]), "+f"(d[47]), "+f"(d[48]), "+f"(d[49]), "+f"(d[50]), "+f"(d[51]), "+f"(d[52]), "+f"(d[53]), "+f"(d[54]), "+f"(d[55]), "+f"(d[56]), "+f"(d[57]), "+f"(d[58]), "+f"(d[59]), "+f"(d[60]), "+f"(d[61]), "+f"(d[62]), "+f"(d[63]), "+f"(d[64]), "+f"(d[65]), "+f"(d[66]), "+f"(d[67]), "+f"(d[68]), "+f"(d[69]), "+f"(d[70]), "+f"(d[71]), "+f"(d[72]), "+f"(d[73]), "+f"(d[74]), "+f"(d[75]), "+f"(d[76]), "+f"(d[77]), "+f"(d[78]), "+f"(d[79]), "+f"(d[80]), "+f"(d[81]), "+f"(d[82]), "+f"(d[83]), "+f"(d[84]), "+f"(d[85]), "+f"(d[86]), "+f"(d[87]), "+f"(d[88]), "+f"(d[89]), "+f"(d[90]), "+f"(d[91]), "+f"(d[92]), "+f"(d[93]), "+f"(d[94]), "+f"(d[95])
    : "l"(da), "l"(db), "r"(sc));
}
__device__ __forceinline__ void wgmma_rs_n128(float (&d)[64], uint32_t a0, uint32_t a1, uint32_t a2, uint32_t a3, uint64_t db, uint32_t sc) {
  asm volatile("{\n.reg .pred p;\nsetp.ne.b32 p, %69, 0;\n"
    "wgmma.mma_async.sync.aligned.m64n128k16.f32.bf16.bf16 "
    "{%0, %1, %2, %3, %4, %5, %6, %7, %8, %9, %10, %11, %12, %13, %14, %15, %16, %17, %18, %19, %20, %21, %22, %23, %24, %25, %26, %27, %28, %29, %30, %31, %32, %33, %34, %35, %36, %37, %38, %39, %40, %41, %42, %43, %44, %45, %46, %47, %48, %49, %50, %51, %52, %53, %54, %55, %56, %57, %58, %59, %60, %61, %62, %63}, {%64, %65, %66, %67}, %68, p, 1, 1, 0;\n}\n"
    : "+f"(d[0]), "+f"(d[1]), "+f"(d[2]), "+f"(d[3]), "+f"(d[4]), "+f"(d[5]), "+f"(d[6]), "+f"(d[7]), "+f"(d[8]), "+f"(d[9]), "+f"(d[10]), "+f"(d[11]), "+f"(d[12]), "+f"(d[13]), "+f"(d[14]), "+f"(d[15]), "+f"(d[16]), "+f"(d[17]), "+f"(d[18]), "+f"(d[19]), "+f"(d[20]), "+f"(d[21]), "+f"(d[22]), "+f"(d[23]), "+f"(d[24]), "+f"(d[25]), "+f"(d[26]), "+f"(d[27]), "+f"(d[28]), "+f"(d[29]), "+f"(d[30]), "+f"(d[31]), "+f"(d[32]), "+f"(d[33]), "+f"(d[34]), "+f"(d[35]), "+f"(d[36]), "+f"(d[37]), "+f"(d[38]), "+f"(d[39]), "+f"(d[40]), "+f"(d[41]), "+f"(d[42]), "+f"(d[43]), "+f"(d[44]), "+f"(d[45]), "+f"(d[46]), "+f"(d[47]), "+f"(d[48]), "+f"(d[49]), "+f"(d[50]), "+f"(d[51]), "+f"(d[52]), "+f"(d[53]), "+f"(d[54]), "+f"(d[55]), "+f"(d[56]), "+f"(d[57]), "+f"(d[58]), "+f"(d[59]), "+f"(d[60]), "+f"(d[61]), "+f"(d[62]), "+f"(d[63])
    : "r"(a0), "r"(a1), "r"(a2), "r"(a3), "l"(db), "r"(sc));
}
__device__ __forceinline__ void wgmma_rs_n128_tb(float (&d)[64], uint32_t a0, uint32_t a1, uint32_t a2, uint32_t a3, uint64_t db, uint32_t sc) {
  asm volatile("{\n.reg .pred p;\nsetp.ne.b32 p, %69, 0;\n"
    "wgmma.mma_async.sync.aligned.m64n128k16.f32.bf16.bf16 "
    "{%0, %1, %2, %3, %4, %5, %6, %7, %8, %9, %10, %11, %12, %13, %14, %15, %16, %17, %18, %19, %20, %21, %22, %23, %24, %25, %26, %27, %28, %29, %30, %31, %32, %33, %34, %35, %36, %37, %38, %39, %40, %41, %42, %43, %44, %45, %46, %47, %48, %49, %50, %51, %52, %53, %54, %55, %56, %57, %58, %59, %60, %61, %62, %63}, {%64, %65, %66, %67}, %68, p, 1, 1, 1;\n}\n"
    : "+f"(d[0]), "+f"(d[1]), "+f"(d[2]), "+f"(d[3]), "+f"(d[4]), "+f"(d[5]), "+f"(d[6]), "+f"(d[7]), "+f"(d[8]), "+f"(d[9]), "+f"(d[10]), "+f"(d[11]), "+f"(d[12]), "+f"(d[13]), "+f"(d[14]), "+f"(d[15]), "+f"(d[16]), "+f"(d[17]), "+f"(d[18]), "+f"(d[19]), "+f"(d[20]), "+f"(d[21]), "+f"(d[22]), "+f"(d[23]), "+f"(d[24]), "+f"(d[25]), "+f"(d[26]), "+f"(d[27]), "+f"(d[28]), "+f"(d[29]), "+f"(d[30]), "+f"(d[31]), "+f"(d[32]), "+f"(d[33]), "+f"(d[34]), "+f"(d[35]), "+f"(d[36]), "+f"(d[37]), "+f"(d[38]), "+f"(d[39]), "+f"(d[40]), "+f"(d[41]), "+f"(d[42]), "+f"(d[43]), "+f"(d[44]), "+f"(d[45]), "+f"(d[46]), "+f"(d[47]), "+f"(d[48]), "+f"(d[49]), "+f"(d[50]), "+f"(d[51]), "+f"(d[52]), "+f"(d[53]), "+f"(d[54]), "+f"(d[55]), "+f"(d[56]), "+f"(d[57]), "+f"(d[58]), "+f"(d[59]), "+f"(d[60]), "+f"(d[61]), "+f"(d[62]), "+f"(d[63])
    : "r"(a0), "r"(a1), "r"(a2), "r"(a3), "l"(db), "r"(sc));
}

#define TS(i) do {} while (0)
#define TR(j, i) do {} while (0)
#define TSS(i, c) do {} while (0)

__device__ __forceinline__ uint32_t wrap12(uint32_t p) { return p >= NSLOT ? p - NSLOT : p; }

struct Cons {
  uint32_t sb;
  uint32_t g, pos;
  uint32_t rel;
  uint32_t nstg;
  uint32_t stg;
  uint32_t xr;
  uint32_t zero;
  int wg, lane;
  __device__ __forceinline__ void wait_full(uint32_t gg) const { mbar_wait(sb + SM_BAR + B_FULL + (gg & 7) * 8, (gg >> 3) & 1); }
  __device__ __forceinline__ void release(uint32_t gg) const { if (lane < 2) mbar_arrive_cluster(rel + (gg & 7) * 8); }
  __device__ __forceinline__ void stg_acquire() { mbar_wait(sb + SM_BAR + B_SEMPTY + wg * 8, (nstg & 1) ^ 1); nstg++; }
  __device__ __forceinline__ void stg_publish() const {
    fence_async_smem();
    __syncwarp();
    if (lane == 0) mbar_arrive(sb + SM_BAR + B_SFULL + wg * 8);
  }
};

template <int N, bool FIRST>
__device__ __forceinline__ void gemm_step(float (&acc)[128], Cons& c) {
  const uint32_t p1 = wrap12(c.pos + 1), p2 = wrap12(c.pos + 2);
  const uint64_t da = mkdesc(c.sb + c.wg * 8192 + c.pos * SLOT, 16, 1024);
  const uint64_t b0 = mkdesc(c.sb + p1 * SLOT, 4096, 1024);
  const uint64_t b1 = mkdesc(c.sb + p2 * SLOT, 4096, 1024);
  c.wait_full(c.g);
  wg_fence();
  if (N == 256) {
    wgmma_ss_n256_tb(acc, da, b0, FIRST ? 0 : 1);
    wgmma_ss_n256_tb(acc, da + 2, b0 + 128, 1);
    wgmma_ss_n256_tb(acc, da + 4, b1, 1);
    wgmma_ss_n256_tb(acc, da + 6, b1 + 128, 1);
  } else {
    wgmma_ss_n192_tb(acc, da, b0, FIRST ? 0 : 1);
    wgmma_ss_n192_tb(acc, da + 2, b0 + 128, 1);
    wgmma_ss_n192_tb(acc, da + 4, b1, 1);
    wgmma_ss_n192_tb(acc, da + 6, b1 + 128, 1);
  }
  wg_commit();
  if (!FIRST) {
    wg_wait<1>();
    c.release(c.g - 1);
  }
  c.g++;
  c.pos = wrap12(p2 + 1);
}

template <int N>
__device__ __forceinline__ void gemm_loop(float (&acc)[128], Cons& c, int nk) {
  gemm_step<N, true>(acc, c);
#pragma unroll 1
  for (int k = 1; k < nk; k++) gemm_step<N, false>(acc, c);
  wg_wait<0>();
  c.release(c.g - 1);
  fence_regs(acc);
}

__device__ __forceinline__ float silu_bf(float v) {
  const float f = bf_round(v);
  return __fdividef(f, 1.0f + ex2(-1.4426950408889634f * f));
}

template <int MODE, int B0, int NB>
__device__ __forceinline__ void store_event(const float (&acc)[128], Cons& c) {
  uint32_t r[NB * 16];
#pragma unroll
  for (int i = 0; i < NB * 16; i++) {
    const float lo = acc[B0 * 32 + 2 * i], hi = acc[B0 * 32 + 2 * i + 1];
    r[i] = MODE == 0 ? pack_bf16_relu(lo, hi) : pack_bf16(silu_bf(lo), silu_bf(hi));
  }
  c.stg_acquire();
#pragma unroll
  for (int b = 0; b < NB; b++)
#pragma unroll
    for (int kb = 0; kb < 4; kb++)
      stsm4(c.stg + b * 8192 + (((2 * kb) ^ c.xr) << 4), r[b * 16 + kb * 4], r[b * 16 + kb * 4 + 1], r[b * 16 + kb * 4 + 2], r[b * 16 + kb * 4 + 3]);
  c.stg_publish();
}

template <int N>
__device__ __forceinline__ void h_tile(float (&acc)[128], Cons& c) {
  gemm_loop<N>(acc, c, 16);
  store_event<0, 0, 2>(acc, c);
  store_event<0, 2, N / 64 - 2>(acc, c);
}

constexpr float SM_C = 0.08838834764831845f * 1.4426950408889634f;

#define ONCE(c) _Pragma("unroll 1") for (uint32_t once_ = 0; once_ <= (c).zero; once_++)
__device__ __forceinline__ void row_max2(const float (&S)[64], float& n0, float& n1) {
  float x[4], y[4];
#pragma unroll
  for (int i = 0; i < 4; i++) { x[i] = fmaxf(S[4 * i], S[4 * i + 1]); y[i] = fmaxf(S[4 * i + 2], S[4 * i + 3]); }
#pragma unroll
  for (int i = 4; i < 16; i++) {
    x[i & 3] = fmaxf(x[i & 3], fmaxf(S[4 * i], S[4 * i + 1]));
    y[i & 3] = fmaxf(y[i & 3], fmaxf(S[4 * i + 2], S[4 * i + 3]));
  }
  n0 = fmaxf(fmaxf(x[0], x[1]), fmaxf(x[2], x[3]));
  n1 = fmaxf(fmaxf(y[0], y[1]), fmaxf(y[2], y[3]));
  n0 = fmaxf(n0, __shfl_xor_sync(~0u, n0, 1));
  n1 = fmaxf(n1, __shfl_xor_sync(~0u, n1, 1));
  n0 = fmaxf(n0, __shfl_xor_sync(~0u, n0, 2));
  n1 = fmaxf(n1, __shfl_xor_sync(~0u, n1, 2));
}
__device__ __forceinline__ void to_exponent(float (&S)[64], float cc0, float cc1) {
#pragma unroll
  for (int i = 0; i < 16; i++) {
    S[4 * i] = fmaf(S[4 * i], SM_C, cc0); S[4 * i + 1] = fmaf(S[4 * i + 1], SM_C, cc0);
    S[4 * i + 2] = fmaf(S[4 * i + 2], SM_C, cc1); S[4 * i + 3] = fmaf(S[4 * i + 3], SM_C, cc1);
  }
}
__device__ __forceinline__ void scale_o(float (&O)[64], float f0, float f1) {
#pragma unroll
  for (int i = 0; i < 16; i++) { O[4 * i] *= f0; O[4 * i + 1] *= f0; O[4 * i + 2] *= f1; O[4 * i + 3] *= f1; }
}
__device__ __forceinline__ void exp_stream(float (&S)[64], uint32_t (&p)[32], float (&O)[64], float& cc0, float& cc1, float& l0, float& l1) {
  float s0, s1;
#pragma unroll 1
  for (int pass = 0;; pass++) {
    float a[4] = {0.f, 0.f, 0.f, 0.f};
#pragma unroll
    for (int i = 0; i < 16; i++) {
      const float e0 = ex2(S[4 * i]), e1 = ex2(S[4 * i + 1]), e2 = ex2(S[4 * i + 2]), e3 = ex2(S[4 * i + 3]);
      a[0] += e0; a[1] += e1; a[2] += e2; a[3] += e3;
      p[2 * i] = pack_bf16(e0, e1);
      p[2 * i + 1] = pack_bf16(e2, e3);
    }
    s0 = a[0] + a[1]; s1 = a[2] + a[3];
    if (pass || !__any_sync(~0u, !(fmaxf(s0, s1) <= 65536.f))) break;
    float d0, d1;
    row_max2(S, d0, d1);
    d0 = fmaxf(d0, 0.f); d1 = fmaxf(d1, 0.f);
#pragma unroll
    for (int i = 0; i < 16; i++) { S[4 * i] -= d0; S[4 * i + 1] -= d0; S[4 * i + 2] -= d1; S[4 * i + 3] -= d1; }
    cc0 -= d0; cc1 -= d1;
    const float f0 = ex2(-d0), f1 = ex2(-d1);
    scale_o(O, f0, f1);
    l0 *= f0; l1 *= f1;
  }
  l0 += s0; l1 += s1;
}

__device__ __forceinline__ void inv_rowsum(float l0, float l1, float& i0, float& i1) {
  l0 += __shfl_xor_sync(~0u, l0, 1); l1 += __shfl_xor_sync(~0u, l1, 1);
  l0 += __shfl_xor_sync(~0u, l0, 2); l1 += __shfl_xor_sync(~0u, l1, 2);
  i0 = __fdividef(1.0f, l0); i1 = __fdividef(1.0f, l1);
}
__device__ __forceinline__ void write_o(const float (&O)[64], const Cons& c) {
  uint32_t t;
  asm volatile("mov.u32 %0, %%tid.x;" : "=r"(t));
  const uint32_t stg = c.sb + SM_STG + (t >> 7) * 16384 + ((t >> 5) & 3) * 2048 + (t & 15) * 128;
  const uint32_t xr = ((t >> 4) & 1) ^ (t & 7);
#pragma unroll
  for (int kb = 0; kb < 8; kb++)
    stsm4(stg + (kb >> 2) * 8192 + (((2 * (kb & 3)) ^ xr) << 4),
          pack_bf16(O[8 * kb], O[8 * kb + 1]), pack_bf16(O[8 * kb + 2], O[8 * kb + 3]),
          pack_bf16(O[8 * kb + 4], O[8 * kb + 5]), pack_bf16(O[8 * kb + 6], O[8 * kb + 7]));
  c.stg_publish();
}

__device__ __forceinline__ void issue_qk(float (&S)[64], const uint32_t (&q)[32], uint32_t s0, uint32_t s1, uint32_t zero) {
  const uint64_t d0 = mkdesc(s0, 16, 1024), d1 = mkdesc(s1, 16, 1024);
#pragma unroll
  for (int kk = 0; kk < 8; kk++)
    wgmma_rs_n128(S, q[4 * kk], q[4 * kk + 1], q[4 * kk + 2], q[4 * kk + 3], (kk < 4 ? d0 : d1) + (kk & 3) * 2, kk > 0 ? 1u : zero);
}
__device__ __forceinline__ void issue_pv(float (&O)[64], const uint32_t (&p)[32], uint32_t s0, uint32_t s1, uint32_t accum) {
  const uint64_t d0 = mkdesc(s0, 8192, 1024), d1 = mkdesc(s1, 8192, 1024);
#pragma unroll
  for (int kk = 0; kk < 8; kk++)
    wgmma_rs_n128_tb(O, p[4 * kk], p[4 * kk + 1], p[4 * kk + 2], p[4 * kk + 3], (kk < 4 ? d0 : d1) + (kk & 3) * 128, kk > 0 ? 1u : accum);
}

#define TURN_SYNC()   bar_sync(1 + c.wg, 256)
#define TURN_PASS()   bar_arrive(2 - c.wg, 256)

__device__ __forceinline__ void attn_tile(float (&acc)[128], Cons& c, int t) {
  gemm_loop<256>(acc, c, 16);
  TSS(8 + t, c);
  uint32_t q[32], p[32];
  float S[64], O[64];
  const uint32_t stash = c.sb + SM_STG + c.wg * 16384 + ((threadIdx.x >> 5) & 3) * 2048 + c.lane * 16;
#pragma unroll
  for (int i = 0; i < 32; i++) q[i] = pack_bf16(acc[2 * i], acc[2 * i + 1]);
  c.stg_acquire();
#pragma unroll
  for (int i = 0; i < 8; i++)
    sts128(stash + (i >> 2) * 8192 + (i & 3) * 512, pack_bf16(acc[64 + 8 * i], acc[65 + 8 * i]), pack_bf16(acc[66 + 8 * i], acc[67 + 8 * i]),
           pack_bf16(acc[68 + 8 * i], acc[69 + 8 * i]), pack_bf16(acc[70 + 8 * i], acc[71 + 8 * i]));
  fence_regs(q);
  TR(0, 0);
  TURN_SYNC();
  TR(0, 1);
  c.wait_full(c.g);
  wg_fence();
  issue_qk(S, q, c.sb + c.pos * SLOT, c.sb + wrap12(c.pos + 1) * SLOT, 0);
  wg_commit();
  TURN_PASS();
  TR(0, 2);
  wg_wait<0>();
  TR(0, 3);
  fence_regs(S);
  c.release(c.g);
  c.g++;
  c.pos = wrap12(c.pos + 2);
  float cc0, cc1, l0 = 0.f, l1 = 0.f;
  row_max2(S, cc0, cc1);
  cc0 *= -SM_C; cc1 *= -SM_C;
  to_exponent(S, cc0, cc1);
#pragma unroll
  for (int i = 0; i < 64; i++) O[i] = 0.f;
  exp_stream(S, p, O, cc0, cc1, l0, l1);
#pragma unroll 1
  for (int j = 0; j < 7 + (int)c.zero; j++) {
    const uint32_t k0 = c.pos, k1 = wrap12(k0 + 1), v0 = wrap12(k0 + 2), v1 = wrap12(k0 + 3);
    TR(j + 1, 0);
    TURN_SYNC();
    TR(j + 1, 1);
    c.wait_full(c.g);
    wg_fence();
    issue_qk(S, q, c.sb + k0 * SLOT, c.sb + k1 * SLOT, 0);
    wg_commit();
    c.wait_full(c.g + 1);
    wg_fence();
    issue_pv(O, p, c.sb + v0 * SLOT, c.sb + v1 * SLOT, j != 4);
    wg_commit();
    TURN_PASS();
    TR(j + 1, 2);
    wg_wait<1>();
    TR(j + 1, 3);
    fence_regs(S);
    fence_regs(q);
    c.release(c.g);
    if (j == 2) {
#pragma unroll
      for (int i = 0; i < 8; i++) lds128(stash + (i >> 2) * 8192 + (i & 3) * 512, q[4 * i], q[4 * i + 1], q[4 * i + 2], q[4 * i + 3]);
      __syncwarp();
    }
    float f0, f1;
    if (j == 3) {
      row_max2(S, cc0, cc1);
      cc0 *= -SM_C; cc1 *= -SM_C;
      inv_rowsum(l0, l1, f0, f1);
      l0 = 0.f; l1 = 0.f;
    }
    ONCE(c) { to_exponent(S, cc0, cc1); }
    TR(j + 1, 4);
    wg_wait<0>();
    TR(j + 1, 5);
    fence_regs(O);
    fence_regs(p);
    c.release(c.g + 1);
    c.g += 2;
    c.pos = wrap12(v1 + 1);
    if (j == 3) {
      scale_o(O, f0, f1);
      write_o(O, c);
    }
    TR(j + 1, 6);
    exp_stream(S, p, O, cc0, cc1, l0, l1);
  }
  TR(8, 0);
  TURN_SYNC();
  TR(8, 1);
  c.wait_full(c.g);
  wg_fence();
  issue_pv(O, p, c.sb + c.pos * SLOT, c.sb + wrap12(c.pos + 1) * SLOT, 1);
  wg_commit();
  TURN_PASS();
  TR(8, 2);
  c.stg_acquire();
  float a0, a1;
  inv_rowsum(l0, l1, a0, a1);
  wg_wait<0>();
  TR(8, 5);
  fence_regs(O);
  fence_regs(p);
  c.release(c.g);
  c.g++;
  c.pos = wrap12(c.pos + 2);
  scale_o(O, a0, a1);
  write_o(O, c);
  TR(9, 0);
}

struct Prod {
  uint32_t sb, g, pos, head, tail_g, tail_pos, hist;
  __device__ __forceinline__ uint32_t full() const { return sb + SM_BAR + B_FULL + (g & 7) * 8; }
  __device__ __forceinline__ uint32_t slot(uint32_t i) const { return sb + wrap12(pos + i) * SLOT; }
  __device__ __forceinline__ void acquire(uint32_t size) {
    while (head + size - tail_pos > NSLOT) {
      mbar_wait(sb + SM_BAR + B_EMPTY + (tail_g & 7) * 8, (tail_g >> 3) & 1);
      tail_pos += 2 + ((hist >> (tail_g & 31)) & 1);
      tail_g++;
    }
    hist = (hist & ~(1u << (g & 31))) | ((size - 2) << (g & 31));
  }
  __device__ __forceinline__ void advance(uint32_t size) { g++; head += size; pos = wrap12(pos + size); }
};

__device__ __forceinline__ void wait_flag(const unsigned* p, unsigned target) {
  while ((int)(ld_acquire(p) - target) < 0) {}
  fence_async_all();
}

__global__ void __cluster_dims__(2, 1, 1) __launch_bounds__(384, 1) fused_kernel(const __grid_constant__ Params P) {
  extern __shared__ uint8_t smem_raw[];
  const uint32_t sb = (smem_u32(smem_raw) + 1023u) & ~1023u;
  const int warp = __shfl_sync(~0u, (int)(threadIdx.x >> 5), 0);
  const int lane = threadIdx.x & 31;
  const int rank = blockIdx.x & 1;
  const int cl = blockIdx.x >> 1;
  const int j = cl >> 3;
  const int rb = (cl & 7) * 2 + rank;
  const bool is_s = j < 4;
  const int hn0 = is_s ? HS0 : HF0, hn1 = is_s ? HS1 : HF1;
  const int hc0 = is_s ? j * (HS0 + HS1) : 4 * (HS0 + HS1) + (j - 4) * (HF0 + HF1);
  const int hc1 = hc0 + hn0;
  const int row0 = rb * 128;
  Flags* fl = P.flags;

  if (warp >= 8) {
    if (warp == 8 && lane == 0) {
      for (int i = 0; i < NBAR; i++) { mbar_init(sb + SM_BAR + B_FULL + i * 8, 1); mbar_init(sb + SM_BAR + B_EMPTY + i * 8, 16); }
      for (int i = 0; i < 2; i++) { mbar_init(sb + SM_BAR + B_SFULL + i * 8, 4); mbar_init(sb + SM_BAR + B_SEMPTY + i * 8, 1); }
      mbar_init(sb + SM_BAR + B_DONE, 11);
      asm volatile("fence.mbarrier_init.release.cluster;" ::: "memory");
    }
    if (warp == 9 && lane < 11) prefetch_map(&P.act_ld + lane);
    __syncwarp();
    cluster_arrive();
    cluster_wait();
    asm volatile("setmaxnreg.dec.sync.aligned.u32 24;");
    if (warp == 8) {
      const unsigned ep1 = *(volatile unsigned*)&fl->epoch[blockIdx.x] + 1;
      Prod p{sb, 0, 0, 0, 0, 0, 0};
      const uint64_t pol = policy_evict_first();
#define LDW(dst, m, bar, c0, c1, c2) tma_ld3_mc_hint(dst, m, bar, c0, c1, c2, pol)
      for (int t = 0; t < 2; t++) {
        const int n = t ? hn1 : hn0, nb0 = (t ? hc1 : hc0) >> 6;
        const CUtensorMap* mb = n == 256 ? &P.w1b4 : &P.w1b3;
        const uint32_t bytes = 16384 + n * 128;
        int k = 0;
        if (t == 0) {
          for (; k < 4; k++) {
            p.acquire(3);
            if (lane == 0) { mbar_expect_tx(p.full(), bytes); LDW(p.slot(1 + rank), mb, p.full(), 0, k * 64 + rank * 32, nb0); }
            p.advance(3);
          }
          wait_flag(&fl->ln[rb][0], ep1 * 8);
          if (lane == 0)
            for (int i = 0; i < 4; i++) tma_ld2(sb + i * 3 * SLOT, &P.act_ld, sb + SM_BAR + B_FULL + i * 8, C_XN + i * 64, row0);
        }
        for (; k < 16; k++) {
          p.acquire(3);
          if (lane == 0) {
            mbar_expect_tx(p.full(), bytes);
            LDW(p.slot(1 + rank), mb, p.full(), 0, k * 64 + rank * 32, nb0);
            tma_ld2(p.slot(0), &P.act_ld, p.full(), C_XN + k * 64, row0);
          }
          p.advance(3);
        }
      }
      const int kvrow = (j >> 1) * SK + KV0;
      for (int t = 0; t < 2; t++) {
        const int nb0 = (4 * j + 2 * t) * 2;
        for (int k = 0; k < 16; k++) {
          p.acquire(3);
          if (lane == 0) {
            mbar_expect_tx(p.full(), 49152);
            LDW(p.slot(1 + rank), &P.wq, p.full(), 0, k * 64 + rank * 32, nb0);
            tma_ld2(p.slot(0), &P.act_ld, p.full(), C_XN + k * 64, row0);
          }
          p.advance(3);
        }
        for (int i = 0; i < 16; i++) {
          const bool is_k = i == 0 || (i < 15 && (i & 1));
          const int ch = (is_k ? ((i + 1) >> 1) : (i == 15 ? 7 : (i >> 1) - 1)) & 3;
          p.acquire(2);
          if (lane == 0) {
            mbar_expect_tx(p.full(), 32768);
            if (is_k) tma_ld2_mc(p.slot(rank), &P.k_ld, p.full(), rank * 64, kvrow + ch * 128);
            else      tma_ld3_mc(p.slot(rank), &P.v_ld, p.full(), 0, kvrow + ch * 128 + rank * 64, 0);
          }
          p.advance(2);
        }
        if (t == 0 && !is_s) wait_flag(&fl->h[rb][0], ep1 * 64);
      }
      const int jn = j & 3;
      if (is_s) {
        unsigned ready = 0;
        for (int i = 0; i < 64; i++) {
          const int hi = i >> 1;
          const int head = 4 * ((hi & 15) >> 1) + (hi & 1) + ((hi >> 4) << 1);
          const int kc = head * 128 + (i & 1) * 64;
          p.acquire(3);
          if (lane == 0) { mbar_expect_tx(p.full(), 49152); LDW(p.slot(1 + rank), &P.wo, p.full(), 0, kc + rank * 32, jn * 4); }
          if (!((ready >> head) & 1)) {
            do { ready = __ballot_sync(~0u, (int)(ld_acquire(&fl->o[rb][lane]) - ep1 * 2) >= 0); } while (!((ready >> head) & 1));
            __syncwarp();
            fence_async_all();
          }
          if (lane == 0) tma_ld2(p.slot(0), &P.act_ld, p.full(), C_O + kc, row0);
          p.advance(3);
        }
        for (int i = 0; i < 4; i++) {
          p.acquire(2);
          if (i == 2) wait_flag(&fl->g[rb][jn], ep1 * 4);
          if (lane == 0) {
            mbar_expect_tx(p.full(), 32768);
            const CUtensorMap* m = i < 2 ? &P.x_ld : &P.act_ld;
            const int c0 = (i < 2 ? 0 : C_G) + jn * 256 + (i & 1) * 128;
            tma_ld2(p.slot(0), m, p.full(), c0, row0);
            tma_ld2(p.slot(1), m, p.full(), c0 + 64, row0);
          }
          p.advance(2);
        }
      } else {
        for (int k = 0; k < 56; k++) {
          p.acquire(3);
          if (lane == 0) {
            mbar_expect_tx(p.full(), 49152);
            LDW(p.slot(1 + rank), &P.w2, p.full(), 0, k * 64 + rank * 32, jn * 4);
            tma_ld2(p.slot(0), &P.act_ld, p.full(), C_H + k * 64, row0);
          }
          p.advance(3);
        }
      }
      if (lane == 0) { *(volatile unsigned*)&fl->epoch[blockIdx.x] = ep1; mbar_arrive(sb + SM_BAR + B_DONE); }
    } else if (warp < 11) {
      const int wg = warp - 9;
      if (lane == 0) {
        const uint32_t stg = sb + SM_STG + wg * 16384;
        const int nev = is_s ? 8 : 10;
        for (int n = 0; n < nev; n++) {
          int col, nbox = 2;
          unsigned* flag;
          if (n < 4) {
            col = C_H + ((n & 2) ? hc1 : hc0) + (n & 1) * 128;
            if ((n & 1) && ((n & 2) ? hn1 : hn0) == 192) nbox = 1;
            flag = &fl->h[rb][0];
          } else if (n < 8) {
            col = C_O + (4 * j + n - 4) * 128;
            flag = &fl->o[rb][4 * j + n - 4];
          } else {
            col = C_G + (j & 3) * 256 + (n - 8) * 128;
            flag = &fl->g[rb][j & 3];
          }
          mbar_wait(sb + SM_BAR + B_SFULL + wg * 8, n & 1);
          tma_st2(&P.act_st, stg, col, row0 + wg * 64);
          if (nbox == 2) tma_st2(&P.act_st, stg + 8192, col + 64, row0 + wg * 64);
          bulk_commit();
          bulk_wait_read0();
          mbar_arrive(sb + SM_BAR + B_SEMPTY + wg * 8);
          bulk_wait0();
          fence_async_all();
          red_release(flag, 1);
        }
        mbar_arrive(sb + SM_BAR + B_DONE);
      }
    } else {
      if (lane == 0) {
        const unsigned long long t0 = gtime();
        while (!mbar_try(sb + SM_BAR + B_DONE, 0))
          if (gtime() - t0 > 2000000000ull) __trap();
      }
    }
    __syncwarp();
    cluster_arrive();
    cluster_wait();
  } else {
    const int wg = warp >> 2;
    TS(0);
    {
      const int r = row0 + j * 16 + warp * 2;
      uint4 v[2][4];
#pragma unroll
      for (int a = 0; a < 2; a++)
#pragma unroll
        for (int i = 0; i < 4; i++) v[a][i] = __ldg((const uint4*)(P.x + (size_t)(r + a) * DM + i * 256 + lane * 8));
      cluster_arrive();
#pragma unroll
      for (int a = 0; a < 2; a++) {
        float f[32];
#pragma unroll
        for (int i = 0; i < 4; i++) {
          f[8 * i] = bf_lo(v[a][i].x); f[8 * i + 1] = bf_hi(v[a][i].x); f[8 * i + 2] = bf_lo(v[a][i].y); f[8 * i + 3] = bf_hi(v[a][i].y);
          f[8 * i + 4] = bf_lo(v[a][i].z); f[8 * i + 5] = bf_hi(v[a][i].z); f[8 * i + 6] = bf_lo(v[a][i].w); f[8 * i + 7] = bf_hi(v[a][i].w);
        }
        float s = 0.f;
#pragma unroll
        for (int i = 0; i < 32; i++) s += f[i];
#pragma unroll
        for (int o = 16; o; o >>= 1) s += __shfl_xor_sync(~0u, s, o);
        const float mean = s * (1.0f / DM);
        float q = 0.f;
#pragma unroll
        for (int i = 0; i < 32; i++) { const float d = f[i] - mean; q = fmaf(d, d, q); }
#pragma unroll
        for (int o = 16; o; o >>= 1) q += __shfl_xor_sync(~0u, q, o);
        const float mb = bf_round(mean);
        const float sd = bf_round(sqrtf(bf_round(bf_round(q * (1.0f / DM)) + 1e-5f)));
        const float inv = 1.0f / sd;
#pragma unroll
        for (int i = 0; i < 4; i++) {
          uint4 o;
          o.x = pack_bf16(bf_round(f[8 * i] - mb) * inv, bf_round(f[8 * i + 1] - mb) * inv);
          o.y = pack_bf16(bf_round(f[8 * i + 2] - mb) * inv, bf_round(f[8 * i + 3] - mb) * inv);
          o.z = pack_bf16(bf_round(f[8 * i + 4] - mb) * inv, bf_round(f[8 * i + 5] - mb) * inv);
          o.w = pack_bf16(bf_round(f[8 * i + 6] - mb) * inv, bf_round(f[8 * i + 7] - mb) * inv);
          *(uint4*)(P.act + (size_t)(r + a) * ACT_W + C_XN + i * 256 + lane * 8) = o;
        }
      }
      TS(11);
      fence_async_all();
      bar_sync(5, 256);
      TS(12);
      if (threadIdx.x == 0) red_release(&fl->ln[rb][0], 1);
      TS(13);
      cluster_wait();
    }
    asm volatile("setmaxnreg.inc.sync.aligned.u32 240;");
    Cons c;
        c.zero = blockIdx.y; c.sb = sb; c.g = 0; c.pos = 0; c.nstg = 0; c.wg = wg; c.lane = lane;
    c.rel = mapa(sb + SM_BAR + B_EMPTY, lane & 1);
    const uint32_t rowoff = (warp & 3) * 2048 + ((lane & 7) + ((lane >> 3) & 1) * 8) * 128;
    c.stg = sb + SM_STG + wg * 16384 + rowoff;
    c.xr = (lane >> 4) ^ (lane & 7);
    if (wg == 1) bar_arrive(1, 256);
    float acc[128];
    TS(1);
    if (hn0 == 256) h_tile<256>(acc, c); else h_tile<192>(acc, c);
    TSS(2, c);
    if (hn1 == 256) h_tile<256>(acc, c); else h_tile<192>(acc, c);
    TSS(3, c);
#pragma unroll 1
    for (int t = 0; t < 2; t++) {
      attn_tile(acc, c, t);
      TSS(4 + t, c);
    }
    gemm_loop<256>(acc, c, is_s ? 64 : 56);
    TSS(6, c);
    if (is_s) {
      const uint32_t x0 = c.pos;
      c.wait_full(c.g);
  #pragma unroll
      for (int b = 0; b < 4; b++) {
        if ((b & 1) == 0) c.wait_full(c.g + 2 + (b >> 1));
        const uint32_t xs = sb + wrap12(x0 + b) * SLOT + wg * 8192;
        const uint32_t sx = xs + rowoff, sg = sb + wrap12(wrap12(x0 + 4) + b) * SLOT + wg * 8192 + rowoff;
#pragma unroll
        for (int kb = 0; kb < 4; kb++) {
          const uint32_t off = ((2 * kb) ^ c.xr) << 4;
          uint32_t xv[4], gv[4];
          ldsm4(sx + off, xv[0], xv[1], xv[2], xv[3]);
          ldsm4(sg + off, gv[0], gv[1], gv[2], gv[3]);
#pragma unroll
          for (int r = 0; r < 4; r++) {
            const uint32_t s2 = pack_bf16(acc[32 * b + 8 * kb + 2 * r], acc[32 * b + 8 * kb + 2 * r + 1]);
            const __nv_bfloat162 pr = __hmul2_rn(*(const __nv_bfloat162*)&s2, *(const __nv_bfloat162*)&gv[r]);
            const __nv_bfloat162 o = __hadd2_rn(*(const __nv_bfloat162*)&xv[r], pr);
            xv[r] = *(const uint32_t*)&o;
          }
          stsm4(sx + off, xv[0], xv[1], xv[2], xv[3]);
        }
        fence_async_smem();
        bar_sync(3 + wg, 128);
        if ((threadIdx.x & 127) == 0) { tma_st2(&P.out_st, xs, (j & 3) * 256 + b * 64, row0 + wg * 64); bulk_commit(); }
      }
      if ((threadIdx.x & 127) == 0) bulk_wait0();
    } else {
      store_event<1, 0, 2>(acc, c);
      store_event<1, 2, 2>(acc, c);
    }
    TSS(7, c);
    __syncwarp();
    if (lane == 0) mbar_arrive(sb + SM_BAR + B_DONE);
    cluster_arrive();
    cluster_wait();
  }
}

typedef CUresult (*EncodeFn)(CUtensorMap*, CUtensorMapDataType, cuuint32_t, void*, const cuuint64_t*, const cuuint64_t*,
                             const cuuint32_t*, const cuuint32_t*, CUtensorMapInterleave, CUtensorMapSwizzle,
                             CUtensorMapL2promotion, CUtensorMapFloatOOBfill);

void map2d(EncodeFn enc, CUtensorMap* m, const void* base, uint64_t cols, uint64_t rows, uint32_t box_rows) {
  cuuint64_t dims[2] = {cols, rows};
  cuuint64_t strides[1] = {cols * 2};
  cuuint32_t box[2] = {64, box_rows};
  cuuint32_t es[2] = {1, 1};
  enc(m, CU_TENSOR_MAP_DATA_TYPE_BFLOAT16, 2, (void*)base, dims, strides, box, es, CU_TENSOR_MAP_INTERLEAVE_NONE,
      CU_TENSOR_MAP_SWIZZLE_128B, CU_TENSOR_MAP_L2_PROMOTION_L2_256B, CU_TENSOR_MAP_FLOAT_OOB_FILL_NONE);
}
void map3d(EncodeFn enc, CUtensorMap* m, const void* base, uint64_t cols, uint64_t rows, uint32_t box_rows, uint32_t box_blks) {
  cuuint64_t dims[3] = {64, rows, cols / 64};
  cuuint64_t strides[2] = {cols * 2, 128};
  cuuint32_t box[3] = {64, box_rows, box_blks};
  cuuint32_t es[3] = {1, 1, 1};
  enc(m, CU_TENSOR_MAP_DATA_TYPE_BFLOAT16, 3, (void*)base, dims, strides, box, es, CU_TENSOR_MAP_INTERLEAVE_NONE,
      CU_TENSOR_MAP_SWIZZLE_128B, CU_TENSOR_MAP_L2_PROMOTION_L2_256B, CU_TENSOR_MAP_FLOAT_OOB_FILL_NONE);
}

}

extern "C" void kernel_launch(void* const* d_in, const int* in_sizes, int n_in, void* d_out, int out_size) {
  (void)in_sizes; (void)n_in; (void)out_size;
  static EncodeFn enc = nullptr;
  static void* act = nullptr;
  static void* flags = nullptr;
  if (!enc) {
    void* fn = nullptr;
    cudaDriverEntryPointQueryResult qr;
    cudaGetDriverEntryPoint("cuTensorMapEncodeTiled", &fn, cudaEnableDefault, &qr);
    enc = (EncodeFn)fn;
    cudaGetSymbolAddress(&act, g_act);
    cudaGetSymbolAddress(&flags, g_flags);
    cudaFuncSetAttribute(fused_kernel, cudaFuncAttributeMaxDynamicSharedMemorySize, SMEM_BYTES);
  }
  Params P;
  map2d(enc, &P.act_ld, act, ACT_W, SEQ, 128);
  map2d(enc, &P.act_st, act, ACT_W, SEQ, 64);
  map2d(enc, &P.x_ld, d_in[0], DM, SEQ, 128);
  map2d(enc, &P.out_st, d_out, DM, SEQ, 64);
  map2d(enc, &P.k_ld, d_in[1], 128, 4 * SK, 128);
  map3d(enc, &P.v_ld, d_in[2], 128, 4 * SK, 64, 2);
  map3d(enc, &P.wq, d_in[3], NQ, DM, 32, 4);
  map3d(enc, &P.w1b4, d_in[6], DFF, DM, 32, 4);
  map3d(enc, &P.w1b3, d_in[6], DFF, DM, 32, 3);
  map3d(enc, &P.wo, d_in[4], DM, NQ, 32, 4);
  map3d(enc, &P.w2, d_in[7], DM, DFF, 32, 4);
  P.x = (const __nv_bfloat16*)d_in[0];
  P.act = (__nv_bfloat16*)act;
  P.flags = (Flags*)flags;
  fused_kernel<<<NCLUSTER * 2, 384, SMEM_BYTES>>>(P);
}
```

```cpp
#include <cuda_runtime.h>
#include <cuda_bf16.h>
#include <cuda.h>
#include <stdint.h>

namespace {

constexpr int SEQ    = 2048;
constexpr int DM     = 1024;
constexpr int NQ     = 4096;
constexpr int DFF    = 3584;
constexpr int SK     = 2048;
constexpr int WIN    = 512;
constexpr int KV0    = SK - WIN;
constexpr int C_XN = 0, C_O = 1024, C_H = 5120, C_G = 8704, ACT_W = 9728;

constexpr int H_REG = 384, H_SPARE0 = 8 * H_REG;
static_assert(H_SPARE0 + 512 == DFF, "H split");

constexpr int NSLOT = 12, SLOT = 16384, NBAR = 8;
constexpr int SM_STG = NSLOT * SLOT;
constexpr int SM_BAR = SM_STG + 2 * 16384;
constexpr int SMEM_BYTES = SM_BAR + 256 + 1024 + 1536;
constexpr int B_FULL = 0, B_EMPTY = 64, B_SFULL = 128, B_SEMPTY = 144, B_DONE = 160;

constexpr int NCLUSTER = 66;

struct Flags {
  unsigned ln[16][32];
  unsigned h[16][32];
  unsigned o[16][32];
  unsigned g[16][32];
  unsigned epoch[160];
};
__device__ __nv_bfloat16 g_act[(size_t)SEQ * ACT_W];
__device__ Flags g_flags;

struct Params {
  CUtensorMap act_ld, act_st, x_ld, out_st, k_ld, v_ld, wq, w1b4, w1b3, wo, w2;
  const __nv_bfloat16* x;
  __nv_bfloat16* act;
  Flags* flags;
};

__device__ __forceinline__ uint32_t smem_u32(const void* p) { return (uint32_t)__cvta_generic_to_shared(p); }
__device__ __forceinline__ void mbar_init(uint32_t bar, uint32_t cnt) {
  asm volatile("mbarrier.init.shared::cta.b64 [%0], %1;" ::"r"(bar), "r"(cnt) : "memory");
}
__device__ __forceinline__ bool mbar_try(uint32_t bar, uint32_t parity) {
  uint32_t ok;
  asm volatile("{\n.reg .pred p;\nmbarrier.try_wait.parity.shared::cta.b64 p, [%1], %2;\nselp.u32 %0, 1, 0, p;\n}\n"
               : "=r"(ok) : "r"(bar), "r"(parity) : "memory");
  return ok;
}
__device__ __forceinline__ void mbar_wait(uint32_t bar, uint32_t parity) {
  asm volatile("{\n.reg .pred p;\nWAIT_%=:\nmbarrier.try_wait.parity.shared::cta.b64 p, [%0], %1;\n@p bra DONE_%=;\nbra WAIT_%=;\nDONE_%=:\n}\n"
               ::"r"(bar), "r"(parity) : "memory");
}
__device__ __forceinline__ void mbar_arrive(uint32_t bar) {
  asm volatile("mbarrier.arrive.shared::cta.b64 _, [%0];" ::"r"(bar) : "memory");
}
__device__ __forceinline__ void mbar_arrive_cluster(uint32_t cluster_addr) {
  asm volatile("mbarrier.arrive.shared::cluster.b64 _, [%0];" ::"r"(cluster_addr) : "memory");
}
__device__ __forceinline__ void mbar_expect_tx(uint32_t bar, uint32_t bytes) {
  asm volatile("mbarrier.arrive.expect_tx.shared::cta.b64 _, [%0], %1;" ::"r"(bar), "r"(bytes) : "memory");
}
__device__ __forceinline__ uint32_t mapa(uint32_t addr, uint32_t rank) {
  uint32_t r;
  asm("mapa.shared::cluster.u32 %0, %1, %2;" : "=r"(r) : "r"(addr), "r"(rank));
  return r;
}
__device__ __forceinline__ void cluster_arrive() { asm volatile("barrier.cluster.arrive.relaxed.aligned;" ::: "memory"); }
__device__ __forceinline__ void cluster_wait() { asm volatile("barrier.cluster.wait.acquire.aligned;" ::: "memory"); }
__device__ __forceinline__ void bar_sync(int id, int n) { asm volatile("bar.sync %0, %1;" ::"r"(id), "r"(n) : "memory"); }
__device__ __forceinline__ void bar_arrive(int id, int n) { asm volatile("bar.arrive %0, %1;" ::"r"(id), "r"(n) : "memory"); }
__device__ __forceinline__ void fence_async_smem() { asm volatile("fence.proxy.async.shared::cta;" ::: "memory"); }
__device__ __forceinline__ void fence_async_all() { asm volatile("fence.proxy.async.global;" ::: "memory"); }

__device__ __forceinline__ void tma_ld2(uint32_t dst, const CUtensorMap* m, uint32_t bar, int c0, int c1) {
  asm volatile("cp.async.bulk.tensor.2d.shared::cluster.global.mbarrier::complete_tx::bytes [%0], [%1, {%3, %4}], [%2];"
               ::"r"(dst), "l"(m), "r"(bar), "r"(c0), "r"(c1) : "memory");
}
__device__ __forceinline__ void tma_ld2_mc(uint32_t dst, const CUtensorMap* m, uint32_t bar, int c0, int c1) {
  asm volatile("cp.async.bulk.tensor.2d.shared::cluster.global.mbarrier::complete_tx::bytes.multicast::cluster [%0], [%1, {%3, %4}], [%2], %5;"
               ::"r"(dst), "l"(m), "r"(bar), "r"(c0), "r"(c1), "h"((uint16_t)3) : "memory");
}
__device__ __forceinline__ void tma_ld3_mc(uint32_t dst, const CUtensorMap* m, uint32_t bar, int c0, int c1, int c2) {
  asm volatile("cp.async.bulk.tensor.3d.shared::cluster.global.mbarrier::complete_tx::bytes.multicast::cluster [%0], [%1, {%3, %4, %5}], [%2], %6;"
               ::"r"(dst), "l"(m), "r"(bar), "r"(c0), "r"(c1), "r"(c2), "h"((uint16_t)3) : "memory");
}
__device__ __forceinline__ void tma_ld3_mc_hint(uint32_t dst, const CUtensorMap* m, uint32_t bar, int c0, int c1, int c2, uint64_t pol) {
  asm volatile("cp.async.bulk.tensor.3d.shared::cluster.global.mbarrier::complete_tx::bytes.multicast::cluster.L2::cache_hint [%0], [%1, {%3, %4, %5}], [%2], %6, %7;"
               ::"r"(dst), "l"(m), "r"(bar), "r"(c0), "r"(c1), "r"(c2), "h"((uint16_t)3), "l"(pol) : "memory");
}
__device__ __forceinline__ uint64_t policy_evict_first() {
  uint64_t p;
  asm volatile("createpolicy.fractional.L2::evict_first.b64 %0, 1.0;" : "=l"(p));
  return p;
}
__device__ __forceinline__ void tma_st2(const CUtensorMap* m, uint32_t src, int c0, int c1) {
  asm volatile("cp.async.bulk.tensor.2d.global.shared::cta.bulk_group [%0, {%2, %3}], [%1];"
               ::"l"(m), "r"(src), "r"(c0), "r"(c1) : "memory");
}
__device__ __forceinline__ void tma_pf3(const CUtensorMap* m, int c0, int c1, int c2) {
  asm volatile("cp.async.bulk.prefetch.tensor.3d.L2.global [%0, {%1, %2, %3}];" ::"l"(m), "r"(c0), "r"(c1), "r"(c2) : "memory");
}
__device__ __forceinline__ void bulk_commit() { asm volatile("cp.async.bulk.commit_group;" ::: "memory"); }
__device__ __forceinline__ void bulk_wait_read0() { asm volatile("cp.async.bulk.wait_group.read 0;" ::: "memory"); }
__device__ __forceinline__ void bulk_wait0() { asm volatile("cp.async.bulk.wait_group 0;" ::: "memory"); }
__device__ __forceinline__ void prefetch_map(const CUtensorMap* m) {
  asm volatile("prefetch.tensormap [%0];" ::"l"(m) : "memory");
}
__device__ __forceinline__ unsigned ld_acquire(const unsigned* p) {
  unsigned v;
  asm volatile("ld.acquire.gpu.global.u32 %0, [%1];" : "=r"(v) : "l"(p) : "memory");
  return v;
}
__device__ __forceinline__ void red_release(unsigned* p, unsigned v) {
  asm volatile("red.release.gpu.global.add.u32 [%0], %1;" ::"l"(p), "r"(v) : "memory");
}
__device__ __forceinline__ void wg_fence() { asm volatile("wgmma.fence.sync.aligned;" ::: "memory"); }
__device__ __forceinline__ void wg_commit() { asm volatile("wgmma.commit_group.sync.aligned;" ::: "memory"); }
template <int N> __device__ __forceinline__ void wg_wait() { asm volatile("wgmma.wait_group.sync.aligned %0;" ::"n"(N) : "memory"); }
template <int N> __device__ __forceinline__ void fence_regs(float (&d)[N]) {
#pragma unroll
  for (int i = 0; i < N; i++) asm volatile("" : "+f"(d[i])::"memory");
}
template <int N> __device__ __forceinline__ void fence_regs(uint32_t (&d)[N]) {
#pragma unroll
  for (int i = 0; i < N; i++) asm volatile("" : "+r"(d[i])::"memory");
}
__device__ __forceinline__ uint64_t mkdesc(uint32_t addr, uint32_t lbo, uint32_t sbo) {
  return (uint64_t)((addr & 0x3FFFF) >> 4) | ((uint64_t)(lbo >> 4) << 16) | ((uint64_t)(sbo >> 4) << 32) | (1ull << 62);
}
__device__ __forceinline__ uint32_t pack_bf16(float lo, float hi) {
  uint32_t r;
  asm("cvt.rn.bf16x2.f32 %0, %1, %2;" : "=r"(r) : "f"(hi), "f"(lo));
  return r;
}
__device__ __forceinline__ uint32_t pack_bf16_relu(float lo, float hi) {
  uint32_t r;
  asm("cvt.rn.relu.bf16x2.f32 %0, %1, %2;" : "=r"(r) : "f"(hi), "f"(lo));
  return r;
}
__device__ __forceinline__ float bf_lo(uint32_t v) { return __uint_as_float(v << 16); }
__device__ __forceinline__ float bf_hi(uint32_t v) { return __uint_as_float(v & 0xFFFF0000u); }
__device__ __forceinline__ float bf_round(float v) { return __bfloat162float(__float2bfloat16_rn(v)); }
__device__ __forceinline__ float ex2(float x) {
  float r;
  asm("ex2.approx.ftz.f32 %0, %1;" : "=f"(r) : "f"(x));
  return r;
}
__device__ __forceinline__ float rcp(float x) {
  float r;
  asm("rcp.approx.ftz.f32 %0, %1;" : "=f"(r) : "f"(x));
  return r;
}
__device__ __forceinline__ uint32_t tid_x() {
  uint32_t t;
  asm volatile("mov.u32 %0, %%tid.x;" : "=r"(t));
  return t;
}
__device__ __forceinline__ void stsm4(uint32_t addr, uint32_t r0, uint32_t r1, uint32_t r2, uint32_t r3) {
  asm volatile("stmatrix.sync.aligned.m8n8.x4.shared.b16 [%0], {%1, %2, %3, %4};" ::"r"(addr), "r"(r0), "r"(r1), "r"(r2), "r"(r3) : "memory");
}
__device__ __forceinline__ void ldsm4(uint32_t addr, uint32_t& r0, uint32_t& r1, uint32_t& r2, uint32_t& r3) {
  asm volatile("ldmatrix.sync.aligned.m8n8.x4.shared.b16 {%0, %1, %2, %3}, [%4];" : "=r"(r0), "=r"(r1), "=r"(r2), "=r"(r3) : "r"(addr) : "memory");
}
__device__ __forceinline__ void sts128(uint32_t addr, uint32_t r0, uint32_t r1, uint32_t r2, uint32_t r3) {
  asm volatile("st.shared.v4.b32 [%0], {%1, %2, %3, %4};" ::"r"(addr), "r"(r0), "r"(r1), "r"(r2), "r"(r3) : "memory");
}
__device__ __forceinline__ void lds128(uint32_t addr, uint32_t& r0, uint32_t& r1, uint32_t& r2, uint32_t& r3) {
  asm volatile("ld.shared.v4.b32 {%0, %1, %2, %3}, [%4];" : "=r"(r0), "=r"(r1), "=r"(r2), "=r"(r3) : "r"(addr) : "memory");
}
__device__ __forceinline__ unsigned long long gtime() {
  unsigned long long t;
  asm volatile("mov.u64 %0, %globaltimer;" : "=l"(t));
  return t;
}

__device__ __forceinline__ void wgmma_ss_n256_tb(float (&d)[128], uint64_t da, uint64_t db, uint32_t sc) {
  asm volatile("{\n.reg .pred p;\nsetp.ne.b32 p, %130, 0;\n"
    "wgmma.mma_async.sync.aligned.m64n256k16.f32.bf16.bf16 "
    "{%0, %1, %2, %3, %4, %5, %6, %7, %8, %9, %10, %11, %12, %13, %14, %15, %16, %17, %18, %19, %20, %21, %22, %23, %24, %25, %26, %27, %28, %29, %30, %31, %32, %33, %34, %35, %36, %37, %38, %39, %40, %41, %42, %43, %44, %45, %46, %47, %48, %49, %50, %51, %52, %53, %54, %55, %56, %57, %58, %59, %60, %61, %62, %63, %64, %65, %66, %67, %68, %69, %70, %71, %72, %73, %74, %75, %76, %77, %78, %79, %80, %81, %82, %83, %84, %85, %86, %87, %88, %89, %90, %91, %92, %93, %94, %95, %96, %97, %98, %99, %100, %101, %102, %103, %104, %105, %106, %107, %108, %109, %110, %111, %112, %113, %114, %115, %116, %117, %118, %119, %120, %121, %122, %123, %124, %125, %126, %127}, %128, %129, p, 1, 1, 0, 1;\n}\n"
    : "+f"(d[0]), "+f"(d[1]), "+f"(d[2]), "+f"(d[3]), "+f"(d[4]), "+f"(d[5]), "+f"(d[6]), "+f"(d[7]), "+f"(d[8]), "+f"(d[9]), "+f"(d[10]), "+f"(d[11]), "+f"(d[12]), "+f"(d[13]), "+f"(d[14]), "+f"(d[15]), "+f"(d[16]), "+f"(d[17]), "+f"(d[18]), "+f"(d[19]), "+f"(d[20]), "+f"(d[21]), "+f"(d[22]), "+f"(d[23]), "+f"(d[24]), "+f"(d[25]), "+f"(d[26]), "+f"(d[27]), "+f"(d[28]), "+f"(d[29]), "+f"(d[30]), "+f"(d[31]), "+f"(d[32]), "+f"(d[33]), "+f"(d[34]), "+f"(d[35]), "+f"(d[36]), "+f"(d[37]), "+f"(d[38]), "+f"(d[39]), "+f"(d[40]), "+f"(d[41]), "+f"(d[42]), "+f"(d[43]), "+f"(d[44]), "+f"(d[45]), "+f"(d[46]), "+f"(d[47]), "+f"(d[48]), "+f"(d[49]), "+f"(d[50]), "+f"(d[51]), "+f"(d[52]), "+f"(d[53]), "+f"(d[54]), "+f"(d[55]), "+f"(d[56]), "+f"(d[57]), "+f"(d[58]), "+f"(d[59]), "+f"(d[60]), "+f"(d[61]), "+f"(d[62]), "+f"(d[63]), "+f"(d[64]), "+f"(d[65]), "+f"(d[66]), "+f"(d[67]), "+f"(d[68]), "+f"(d[69]), "+f"(d[70]), "+f"(d[71]), "+f"(d[72]), "+f"(d[73]), "+f"(d[74]), "+f"(d[75]), "+f"(d[76]), "+f"(d[77]), "+f"(d[78]), "+f"(d[79]), "+f"(d[80]), "+f"(d[81]), "+f"(d[82]), "+f"(d[83]), "+f"(d[84]), "+f"(d[85]), "+f"(d[86]), "+f"(d[87]), "+f"(d[88]), "+f"(d[89]), "+f"(d[90]), "+f"(d[91]), "+f"(d[92]), "+f"(d[93]), "+f"(d[94]), "+f"(d[95]), "+f"(d[96]), "+f"(d[97]), "+f"(d[98]), "+f"(d[99]), "+f"(d[100]), "+f"(d[101]), "+f"(d[102]), "+f"(d[103]), "+f"(d[104]), "+f"(d[105]), "+f"(d[106]), "+f"(d[107]), "+f"(d[108]), "+f"(d[109]), "+f"(d[110]), "+f"(d[111]), "+f"(d[112]), "+f"(d[113]), "+f"(d[114]), "+f"(d[115]), "+f"(d[116]), "+f"(d[117]), "+f"(d[118]), "+f"(d[119]), "+f"(d[120]), "+f"(d[121]), "+f"(d[122]), "+f"(d[123]), "+f"(d[124]), "+f"(d[125]), "+f"(d[126]), "+f"(d[127])
    : "l"(da), "l"(db), "r"(sc));
}
__device__ __forceinline__ void wgmma_ss_n192_tb(float (&d)[128], uint64_t da, uint64_t db, uint32_t sc) {
  asm volatile("{\n.reg .pred p;\nsetp.ne.b32 p, %98, 0;\n"
    "wgmma.mma_async.sync.aligned.m64n192k16.f32.bf16.bf16 "
    "{%0, %1, %2, %3, %4, %5, %6, %7, %8, %9, %10, %11, %12, %13, %14, %15, %16, %17, %18, %19, %20, %21, %22, %23, %24, %25, %26, %27, %28, %29, %30, %31, %32, %33, %34, %35, %36, %37, %38, %39, %40, %41, %42, %43, %44, %45, %46, %47, %48, %49, %50, %51, %52, %53, %54, %55, %56, %57, %58, %59, %60, %61, %62, %63, %64, %65, %66, %67, %68, %69, %70, %71, %72, %73, %74, %75, %76, %77, %78, %79, %80, %81, %82, %83, %84, %85, %86, %87, %88, %89, %90, %91, %92, %93, %94, %95}, %96, %97, p, 1, 1, 0, 1;\n}\n"
    : "+f"(d[0]), "+f"(d[1]), "+f"(d[2]), "+f"(d[3]), "+f"(d[4]), "+f"(d[5]), "+f"(d[6]), "+f"(d[7]), "+f"(d[8]), "+f"(d[9]), "+f"(d[10]), "+f"(d[11]), "+f"(d[12]), "+f"(d[13]), "+f"(d[14]), "+f"(d[15]), "+f"(d[16]), "+f"(d[17]), "+f"(d[18]), "+f"(d[19]), "+f"(d[20]), "+f"(d[21]), "+f"(d[22]), "+f"(d[23]), "+f"(d[24]), "+f"(d[25]), "+f"(d[26]), "+f"(d[27]), "+f"(d[28]), "+f"(d[29]), "+f"(d[30]), "+f"(d[31]), "+f"(d[32]), "+f"(d[33]), "+f"(d[34]), "+f"(d[35]), "+f"(d[36]), "+f"(d[37]), "+f"(d[38]), "+f"(d[39]), "+f"(d[40]), "+f"(d[41]), "+f"(d[42]), "+f"(d[43]), "+f"(d[44]), "+f"(d[45]), "+f"(d[46]), "+f"(d[47]), "+f"(d[48]), "+f"(d[49]), "+f"(d[50]), "+f"(d[51]), "+f"(d[52]), "+f"(d[53]), "+f"(d[54]), "+f"(d[55]), "+f"(d[56]), "+f"(d[57]), "+f"(d[58]), "+f"(d[59]), "+f"(d[60]), "+f"(d[61]), "+f"(d[62]), "+f"(d[63]), "+f"(d[64]), "+f"(d[65]), "+f"(d[66]), "+f"(d[67]), "+f"(d[68]), "+f"(d[69]), "+f"(d[70]), "+f"(d[71]), "+f"(d[72]), "+f"(d[73]), "+f"(d[74]), "+f"(d[75]), "+f"(d[76]), "+f"(d[77]), "+f"(d[78]), "+f"(d[79]), "+f"(d[80]), "+f"(d[81]), "+f"(d[82]), "+f"(d[83]), "+f"(d[84]), "+f"(d[85]), "+f"(d[86]), "+f"(d[87]), "+f"(d[88]), "+f"(d[89]), "+f"(d[90]), "+f"(d[91]), "+f"(d[92]), "+f"(d[93]), "+f"(d[94]), "+f"(d[95])
    : "l"(da), "l"(db), "r"(sc));
}
__device__ __forceinline__ void wgmma_rs_n128(float (&d)[64], uint32_t a0, uint32_t a1, uint32_t a2, uint32_t a3, uint64_t db, uint32_t sc) {
  asm volatile("{\n.reg .pred p;\nsetp.ne.b32 p, %69, 0;\n"
    "wgmma.mma_async.sync.aligned.m64n128k16.f32.bf16.bf16 "
    "{%0, %1, %2, %3, %4, %5, %6, %7, %8, %9, %10, %11, %12, %13, %14, %15, %16, %17, %18, %19, %20, %21, %22, %23, %24, %25, %26, %27, %28, %29, %30, %31, %32, %33, %34, %35, %36, %37, %38, %39, %40, %41, %42, %43, %44, %45, %46, %47, %48, %49, %50, %51, %52, %53, %54, %55, %56, %57, %58, %59, %60, %61, %62, %63}, {%64, %65, %66, %67}, %68, p, 1, 1, 0;\n}\n"
    : "+f"(d[0]), "+f"(d[1]), "+f"(d[2]), "+f"(d[3]), "+f"(d[4]), "+f"(d[5]), "+f"(d[6]), "+f"(d[7]), "+f"(d[8]), "+f"(d[9]), "+f"(d[10]), "+f"(d[11]), "+f"(d[12]), "+f"(d[13]), "+f"(d[14]), "+f"(d[15]), "+f"(d[16]), "+f"(d[17]), "+f"(d[18]), "+f"(d[19]), "+f"(d[20]), "+f"(d[21]), "+f"(d[22]), "+f"(d[23]), "+f"(d[24]), "+f"(d[25]), "+f"(d[26]), "+f"(d[27]), "+f"(d[28]), "+f"(d[29]), "+f"(d[30]), "+f"(d[31]), "+f"(d[32]), "+f"(d[33]), "+f"(d[34]), "+f"(d[35]), "+f"(d[36]), "+f"(d[37]), "+f"(d[38]), "+f"(d[39]), "+f"(d[40]), "+f"(d[41]), "+f"(d[42]), "+f"(d[43]), "+f"(d[44]), "+f"(d[45]), "+f"(d[46]), "+f"(d[47]), "+f"(d[48]), "+f"(d[49]), "+f"(d[50]), "+f"(d[51]), "+f"(d[52]), "+f"(d[53]), "+f"(d[54]), "+f"(d[55]), "+f"(d[56]), "+f"(d[57]), "+f"(d[58]), "+f"(d[59]), "+f"(d[60]), "+f"(d[61]), "+f"(d[62]), "+f"(d[63])
    : "r"(a0), "r"(a1), "r"(a2), "r"(a3), "l"(db), "r"(sc));
}
__device__ __forceinline__ void wgmma_rs_n128_tb(float (&d)[64], uint32_t a0, uint32_t a1, uint32_t a2, uint32_t a3, uint64_t db, uint32_t sc) {
  asm volatile("{\n.reg .pred p;\nsetp.ne.b32 p, %69, 0;\n"
    "wgmma.mma_async.sync.aligned.m64n128k16.f32.bf16.bf16 "
    "{%0, %1, %2, %3, %4, %5, %6, %7, %8, %9, %10, %11, %12, %13, %14, %15, %16, %17, %18, %19, %20, %21, %22, %23, %24, %25, %26, %27, %28, %29, %30, %31, %32, %33, %34, %35, %36, %37, %38, %39, %40, %41, %42, %43, %44, %45, %46, %47, %48, %49, %50, %51, %52, %53, %54, %55, %56, %57, %58, %59, %60, %61, %62, %63}, {%64, %65, %66, %67}, %68, p, 1, 1, 1;\n}\n"
    : "+f"(d[0]), "+f"(d[1]), "+f"(d[2]), "+f"(d[3]), "+f"(d[4]), "+f"(d[5]), "+f"(d[6]), "+f"(d[7]), "+f"(d[8]), "+f"(d[9]), "+f"(d[10]), "+f"(d[11]), "+f"(d[12]), "+f"(d[13]), "+f"(d[14]), "+f"(d[15]), "+f"(d[16]), "+f"(d[17]), "+f"(d[18]), "+f"(d[19]), "+f"(d[20]), "+f"(d[21]), "+f"(d[22]), "+f"(d[23]), "+f"(d[24]), "+f"(d[25]), "+f"(d[26]), "+f"(d[27]), "+f"(d[28]), "+f"(d[29]), "+f"(d[30]), "+f"(d[31]), "+f"(d[32]), "+f"(d[33]), "+f"(d[34]), "+f"(d[35]), "+f"(d[36]), "+f"(d[37]), "+f"(d[38]), "+f"(d[39]), "+f"(d[40]), "+f"(d[41]), "+f"(d[42]), "+f"(d[43]), "+f"(d[44]), "+f"(d[45]), "+f"(d[46]), "+f"(d[47]), "+f"(d[48]), "+f"(d[49]), "+f"(d[50]), "+f"(d[51]), "+f"(d[52]), "+f"(d[53]), "+f"(d[54]), "+f"(d[55]), "+f"(d[56]), "+f"(d[57]), "+f"(d[58]), "+f"(d[59]), "+f"(d[60]), "+f"(d[61]), "+f"(d[62]), "+f"(d[63])
    : "r"(a0), "r"(a1), "r"(a2), "r"(a3), "l"(db), "r"(sc));
}

#define TS(i) do {} while (0)
#define TR(j, i) do {} while (0)
#define TSS(i, c) do {} while (0)

__device__ __forceinline__ uint32_t wrap12(uint32_t p) { return p >= NSLOT ? p - NSLOT : p; }

struct Cons {
  uint32_t sb;
  uint32_t g, pos;
  uint32_t rel;
  uint32_t nstg;
  uint32_t zero;
  int wg, lane;
  __device__ __forceinline__ void wait_full(uint32_t gg) const { mbar_wait(sb + SM_BAR + B_FULL + (gg & 7) * 8, (gg >> 3) & 1); }
  __device__ __forceinline__ void release(uint32_t gg) const { if (lane < 2) mbar_arrive_cluster(rel + (gg & 7) * 8); }
  __device__ __forceinline__ void stg_acquire() { mbar_wait(sb + SM_BAR + B_SEMPTY + wg * 8, (nstg & 1) ^ 1); nstg++; }
  __device__ __forceinline__ void stg_publish() const {
    fence_async_smem();
    __syncwarp();
    if (lane == 0) mbar_arrive(sb + SM_BAR + B_SFULL + wg * 8);
  }
};

__device__ __forceinline__ void frag_addr(uint32_t& rowoff, uint32_t& xr) {
  const uint32_t t = tid_x();
  rowoff = ((t >> 5) & 3) * 2048 + (t & 15) * 128;
  xr = (((t >> 4) & 1) ^ (t & 7)) << 4;
}
template <int NB, int NR>
__device__ __forceinline__ void stage_boxes(const uint32_t (&r)[NR], int r0, const Cons& c) {
  uint32_t rowoff, xr;
  frag_addr(rowoff, xr);
  const uint32_t stg = c.sb + SM_STG + c.wg * 16384 + rowoff;
#pragma unroll
  for (int b = 0; b < NB; b++)
#pragma unroll
    for (int kb = 0; kb < 4; kb++)
      stsm4(stg + b * 8192 + ((32 * kb) ^ xr), r[r0 + b * 16 + kb * 4], r[r0 + b * 16 + kb * 4 + 1], r[r0 + b * 16 + kb * 4 + 2], r[r0 + b * 16 + kb * 4 + 3]);
  c.stg_publish();
}

template <int N, bool FIRST>
__device__ __forceinline__ void gemm_step(float (&acc)[128], Cons& c) {
  const uint32_t p1 = wrap12(c.pos + 1), p2 = wrap12(c.pos + 2);
  const uint64_t da = mkdesc(c.sb + c.wg * 8192 + c.pos * SLOT, 16, 1024);
  const uint64_t b0 = mkdesc(c.sb + p1 * SLOT, 4096, 1024);
  const uint64_t b1 = mkdesc(c.sb + p2 * SLOT, 4096, 1024);
  c.wait_full(c.g);
  wg_fence();
  if (N == 256) {
    wgmma_ss_n256_tb(acc, da, b0, FIRST ? 0 : 1);
    wgmma_ss_n256_tb(acc, da + 2, b0 + 128, 1);
    wgmma_ss_n256_tb(acc, da + 4, b1, 1);
    wgmma_ss_n256_tb(acc, da + 6, b1 + 128, 1);
  } else {
    wgmma_ss_n192_tb(acc, da, b0, FIRST ? 0 : 1);
    wgmma_ss_n192_tb(acc, da + 2, b0 + 128, 1);
    wgmma_ss_n192_tb(acc, da + 4, b1, 1);
    wgmma_ss_n192_tb(acc, da + 6, b1 + 128, 1);
  }
  wg_commit();
  if (!FIRST) {
    wg_wait<1>();
    c.release(c.g - 1);
  }
  c.g++;
  c.pos = wrap12(p2 + 1);
}

template <int N>
__device__ __forceinline__ void gemm_loop(float (&acc)[128], Cons& c, int nk) {
  gemm_step<N, true>(acc, c);
#pragma unroll 1
  for (int k = 1; k < nk; k++) gemm_step<N, false>(acc, c);
  wg_wait<0>();
  c.release(c.g - 1);
  fence_regs(acc);
}
template <int N, int NB>
__device__ __forceinline__ void gemm_loop_flush(float (&acc)[128], Cons& c, const uint32_t (&pend)[NB * 16], bool flush) {
  gemm_step<N, true>(acc, c);
#pragma unroll 1
  for (int k = 1; k < 16; k++) {
    gemm_step<N, false>(acc, c);
    if (k == 3 && flush) {
      c.stg_acquire();
      stage_boxes<NB>(pend, 0, c);
    }
  }
  wg_wait<0>();
  c.release(c.g - 1);
  fence_regs(acc);
}
template <int NB>
__device__ __forceinline__ void h_epilogue(const float (&acc)[128], Cons& c, uint32_t (&pend)[NB * 16]) {
  uint32_t r[32];
#pragma unroll
  for (int i = 0; i < 32; i++) r[i] = pack_bf16_relu(acc[2 * i], acc[2 * i + 1]);
  c.stg_acquire();
  stage_boxes<2>(r, 0, c);
#pragma unroll
  for (int i = 0; i < NB * 16; i++) pend[i] = pack_bf16_relu(acc[64 + 2 * i], acc[65 + 2 * i]);
}

__device__ __forceinline__ uint32_t silu2(float lo, float hi) {
  const uint32_t f2 = pack_bf16(lo, hi);
  const float a = bf_lo(f2), b = bf_hi(f2);
  return pack_bf16(a * rcp(1.0f + ex2(-1.4426950408889634f * a)), b * rcp(1.0f + ex2(-1.4426950408889634f * b)));
}

constexpr float SM_C = 0.08838834764831845f * 1.4426950408889634f;

#define ONCE(c) _Pragma("unroll 1") for (uint32_t once_ = 0; once_ <= (c).zero; once_++)
__device__ __forceinline__ void row_max2(const float (&S)[64], float& n0, float& n1) {
  float x[4], y[4];
#pragma unroll
  for (int i = 0; i < 4; i++) { x[i] = fmaxf(S[4 * i], S[4 * i + 1]); y[i] = fmaxf(S[4 * i + 2], S[4 * i + 3]); }
#pragma unroll
  for (int i = 4; i < 16; i++) {
    x[i & 3] = fmaxf(x[i & 3], fmaxf(S[4 * i], S[4 * i + 1]));
    y[i & 3] = fmaxf(y[i & 3], fmaxf(S[4 * i + 2], S[4 * i + 3]));
  }
  n0 = fmaxf(fmaxf(x[0], x[1]), fmaxf(x[2], x[3]));
  n1 = fmaxf(fmaxf(y[0], y[1]), fmaxf(y[2], y[3]));
  n0 = fmaxf(n0, __shfl_xor_sync(~0u, n0, 1));
  n1 = fmaxf(n1, __shfl_xor_sync(~0u, n1, 1));
  n0 = fmaxf(n0, __shfl_xor_sync(~0u, n0, 2));
  n1 = fmaxf(n1, __shfl_xor_sync(~0u, n1, 2));
}
__device__ __forceinline__ void to_exponent(float (&S)[64], float cc0, float cc1) {
#pragma unroll
  for (int i = 0; i < 16; i++) {
    S[4 * i] = fmaf(S[4 * i], SM_C, cc0); S[4 * i + 1] = fmaf(S[4 * i + 1], SM_C, cc0);
    S[4 * i + 2] = fmaf(S[4 * i + 2], SM_C, cc1); S[4 * i + 3] = fmaf(S[4 * i + 3], SM_C, cc1);
  }
}
__device__ __forceinline__ void scale_o(float (&O)[64], float f0, float f1) {
#pragma unroll
  for (int i = 0; i < 16; i++) { O[4 * i] *= f0; O[4 * i + 1] *= f0; O[4 * i + 2] *= f1; O[4 * i + 3] *= f1; }
}
__device__ __forceinline__ void exp_stream(float (&S)[64], uint32_t (&p)[32], float (&O)[64], float& cc0, float& cc1, float& l0, float& l1) {
  float s0, s1;
#pragma unroll 1
  for (int pass = 0;; pass++) {
    float a[4] = {0.f, 0.f, 0.f, 0.f};
#pragma unroll
    for (int i = 0; i < 16; i++) {
      const float e0 = ex2(S[4 * i]), e1 = ex2(S[4 * i + 1]), e2 = ex2(S[4 * i + 2]), e3 = ex2(S[4 * i + 3]);
      a[0] += e0; a[1] += e1; a[2] += e2; a[3] += e3;
      p[2 * i] = pack_bf16(e0, e1);
      p[2 * i + 1] = pack_bf16(e2, e3);
    }
    s0 = a[0] + a[1]; s1 = a[2] + a[3];
    if (pass || !__any_sync(~0u, !(fmaxf(s0, s1) <= 65536.f))) break;
    float d0, d1;
    row_max2(S, d0, d1);
    d0 = fmaxf(d0, 0.f); d1 = fmaxf(d1, 0.f);
#pragma unroll
    for (int i = 0; i < 16; i++) { S[4 * i] -= d0; S[4 * i + 1] -= d0; S[4 * i + 2] -= d1; S[4 * i + 3] -= d1; }
    cc0 -= d0; cc1 -= d1;
    const float f0 = ex2(-d0), f1 = ex2(-d1);
    scale_o(O, f0, f1);
    l0 *= f0; l1 *= f1;
  }
  l0 += s0; l1 += s1;
}

__device__ __forceinline__ void inv_rowsum(float l0, float l1, float& i0, float& i1) {
  l0 += __shfl_xor_sync(~0u, l0, 1); l1 += __shfl_xor_sync(~0u, l1, 1);
  l0 += __shfl_xor_sync(~0u, l0, 2); l1 += __shfl_xor_sync(~0u, l1, 2);
  i0 = rcp(l0); i1 = rcp(l1);
}
__device__ __forceinline__ void write_o(const float (&O)[64], const Cons& c) {
  uint32_t rowoff, xr;
  frag_addr(rowoff, xr);
  const uint32_t stg = c.sb + SM_STG + c.wg * 16384 + rowoff;
#pragma unroll
  for (int kb = 0; kb < 8; kb++)
    stsm4(stg + (kb >> 2) * 8192 + ((32 * (kb & 3)) ^ xr),
          pack_bf16(O[8 * kb], O[8 * kb + 1]), pack_bf16(O[8 * kb + 2], O[8 * kb + 3]),
          pack_bf16(O[8 * kb + 4], O[8 * kb + 5]), pack_bf16(O[8 * kb + 6], O[8 * kb + 7]));
  c.stg_publish();
}

__device__ __forceinline__ void issue_qk(float (&S)[64], const uint32_t (&q)[32], uint32_t s0, uint32_t s1, uint32_t zero) {
  const uint64_t d0 = mkdesc(s0, 16, 1024), d1 = mkdesc(s1, 16, 1024);
#pragma unroll
  for (int kk = 0; kk < 8; kk++)
    wgmma_rs_n128(S, q[4 * kk], q[4 * kk + 1], q[4 * kk + 2], q[4 * kk + 3], (kk < 4 ? d0 : d1) + (kk & 3) * 2, kk > 0 ? 1u : zero);
}
__device__ __forceinline__ void issue_pv(float (&O)[64], const uint32_t (&p)[32], uint32_t s0, uint32_t s1, uint32_t accum) {
  const uint64_t d0 = mkdesc(s0, 8192, 1024), d1 = mkdesc(s1, 8192, 1024);
#pragma unroll
  for (int kk = 0; kk < 8; kk++)
    wgmma_rs_n128_tb(O, p[4 * kk], p[4 * kk + 1], p[4 * kk + 2], p[4 * kk + 3], (kk < 4 ? d0 : d1) + (kk & 3) * 128, kk > 0 ? 1u : accum);
}

#define TURN_SYNC()   bar_sync(1 + c.wg, 256)
#define TURN_PASS()   bar_arrive(2 - c.wg, 256)

__device__ __forceinline__ void attn_tile(const float (&acc)[128], Cons& c, int t) {
  uint32_t q[32], p[32];
  float S[64], O[64];
  const uint32_t stash = c.sb + SM_STG + c.wg * 16384 + ((threadIdx.x >> 5) & 3) * 2048 + c.lane * 16;
#pragma unroll
  for (int i = 0; i < 32; i++) q[i] = pack_bf16(acc[2 * i], acc[2 * i + 1]);
  c.stg_acquire();
#pragma unroll
  for (int i = 0; i < 8; i++)
    sts128(stash + (i >> 2) * 8192 + (i & 3) * 512, pack_bf16(acc[64 + 8 * i], acc[65 + 8 * i]), pack_bf16(acc[66 + 8 * i], acc[67 + 8 * i]),
           pack_bf16(acc[68 + 8 * i], acc[69 + 8 * i]), pack_bf16(acc[70 + 8 * i], acc[71 + 8 * i]));
  fence_regs(q);
  TR(0, 0);
  TURN_SYNC();
  TR(0, 1);
  c.wait_full(c.g);
  wg_fence();
  issue_qk(S, q, c.sb + c.pos * SLOT, c.sb + wrap12(c.pos + 1) * SLOT, 0);
  wg_commit();
  TURN_PASS();
  TR(0, 2);
  wg_wait<0>();
  TR(0, 3);
  fence_regs(S);
  c.release(c.g);
  c.g++;
  c.pos = wrap12(c.pos + 2);
  float cc0, cc1, l0 = 0.f, l1 = 0.f;
  row_max2(S, cc0, cc1);
  cc0 *= -SM_C; cc1 *= -SM_C;
  to_exponent(S, cc0, cc1);
#pragma unroll
  for (int i = 0; i < 64; i++) O[i] = 0.f;
  exp_stream(S, p, O, cc0, cc1, l0, l1);
#pragma unroll 1
  for (int j = 0; j < 7 + (int)c.zero; j++) {
    const uint32_t k0 = c.pos, k1 = wrap12(k0 + 1), v0 = wrap12(k0 + 2), v1 = wrap12(k0 + 3);
    TR(j + 1, 0);
    TURN_SYNC();
    TR(j + 1, 1);
    c.wait_full(c.g);
    wg_fence();
    issue_qk(S, q, c.sb + k0 * SLOT, c.sb + k1 * SLOT, 0);
    wg_commit();
    c.wait_full(c.g + 1);
    wg_fence();
    issue_pv(O, p, c.sb + v0 * SLOT, c.sb + v1 * SLOT, j != 4);
    wg_commit();
    TURN_PASS();
    TR(j + 1, 2);
    wg_wait<1>();
    TR(j + 1, 3);
    fence_regs(S);
    fence_regs(q);
    c.release(c.g);
    if (j == 2) {
#pragma unroll
      for (int i = 0; i < 8; i++) lds128(stash + (i >> 2) * 8192 + (i & 3) * 512, q[4 * i], q[4 * i + 1], q[4 * i + 2], q[4 * i + 3]);
      __syncwarp();
    }
    float f0, f1;
    if (j == 3) {
      row_max2(S, cc0, cc1);
      cc0 *= -SM_C; cc1 *= -SM_C;
      inv_rowsum(l0, l1, f0, f1);
      l0 = 0.f; l1 = 0.f;
    }
    ONCE(c) { to_exponent(S, cc0, cc1); }
    TR(j + 1, 4);
    wg_wait<0>();
    TR(j + 1, 5);
    fence_regs(O);
    fence_regs(p);
    c.release(c.g + 1);
    c.g += 2;
    c.pos = wrap12(v1 + 1);
    if (j == 3) {
      scale_o(O, f0, f1);
      write_o(O, c);
    }
    TR(j + 1, 6);
    exp_stream(S, p, O, cc0, cc1, l0, l1);
  }
  TR(8, 0);
  TURN_SYNC();
  TR(8, 1);
  c.wait_full(c.g);
  wg_fence();
  issue_pv(O, p, c.sb + c.pos * SLOT, c.sb + wrap12(c.pos + 1) * SLOT, 1);
  wg_commit();
  TURN_PASS();
  TR(8, 2);
  c.stg_acquire();
  float a0, a1;
  inv_rowsum(l0, l1, a0, a1);
  wg_wait<0>();
  TR(8, 5);
  fence_regs(O);
  fence_regs(p);
  c.release(c.g);
  c.g++;
  c.pos = wrap12(c.pos + 2);
  scale_o(O, a0, a1);
  write_o(O, c);
  TR(9, 0);
}

struct Prod {
  uint32_t sb, g, pos, head, tail_g, tail_pos, hist;
  __device__ __forceinline__ uint32_t full() const { return sb + SM_BAR + B_FULL + (g & 7) * 8; }
  __device__ __forceinline__ uint32_t slot(uint32_t i) const { return sb + wrap12(pos + i) * SLOT; }
  __device__ __forceinline__ void acquire(uint32_t size) {
#pragma unroll 1
    while (head + size - tail_pos > NSLOT) {
      mbar_wait(sb + SM_BAR + B_EMPTY + (tail_g & 7) * 8, (tail_g >> 3) & 1);
      tail_pos += 2 + ((hist >> (tail_g & 31)) & 1);
      tail_g++;
    }
    hist = (hist & ~(1u << (g & 31))) | ((size - 2) << (g & 31));
  }
  __device__ __forceinline__ void advance(uint32_t size) { g++; head += size; pos = wrap12(pos + size); }
};

__device__ __forceinline__ void wait_flag(const unsigned* p, unsigned target) {
  while ((int)(ld_acquire(p) - target) < 0) {}
  fence_async_all();
}

#define TSP(i) do {} while (0)

__global__ void __cluster_dims__(2, 1, 1) __launch_bounds__(384, 1) fused_kernel(const __grid_constant__ Params P) {
  extern __shared__ uint8_t smem_raw[];
  const uint32_t sb = (smem_u32(smem_raw) + 1023u) & ~1023u;
  const int warp = __shfl_sync(~0u, (int)(threadIdx.x >> 5), 0);
  const int lane = threadIdx.x & 31;
  const int rank = blockIdx.x & 1;
  const int cl = blockIdx.x >> 1;
  const int j = cl >> 3;
  const int rb = (cl & 7) * 2 + rank;
  const bool is_s = j < 4, spare = j == 8;
  const int row0 = rb * 128;
  Flags* fl = P.flags;

  if (warp >= 8) {
    if (warp == 8) {
      if (lane < 21) mbar_init(sb + SM_BAR + lane * 8, lane < 8 ? 1 : lane < 16 ? 16 : lane < 18 ? 4 : lane < 20 ? 1 : 11);
      asm volatile("fence.mbarrier_init.release.cluster;" ::: "memory");
    }
    __syncwarp();
    cluster_arrive();
    if (warp == 9 && lane < 11) prefetch_map(&P.act_ld + lane);
    __syncwarp();
    cluster_wait();
    asm volatile("setmaxnreg.dec.sync.aligned.u32 24;");
    if (warp == 8) {
      TSP(17);
      const unsigned ep1 = *(volatile unsigned*)&fl->epoch[blockIdx.x] + 1;
      Prod p{sb, 0, 0, 0, 0, 0, 0};
#define LDW(dst, m, bar, c0, c1, c2) tma_ld3_mc(dst, m, bar, c0, c1, c2)
      {
        const CUtensorMap* mb = spare ? &P.w1b4 : &P.w1b3;
        const uint32_t bytes = spare ? 49152 : 40960;
        const int nt = spare ? 8 : 2;
#pragma unroll 1
        for (int t = 0; t < nt; t++) {
          const int r = spare ? ((cl & 1) * 4 + (t >> 1)) * 2 + rank : rb;
          const int nb0 = spare ? (H_SPARE0 >> 6) + (t & 1) * 4 : j * 6 + t * 3;
          int k = 0;
          if (t == 0) {
#pragma unroll 1
            for (; k < 4; k++) {
              p.acquire(3);
              if (lane == 0) { mbar_expect_tx(p.full(), bytes); LDW(p.slot(1 + rank), mb, p.full(), 0, k * 64 + rank * 32, nb0); }
              p.advance(3);
            }
            TSP(14);
            wait_flag(&fl->ln[r][0], ep1 * 64);
            TSP(15);
            if (lane == 0)
              for (int i = 0; i < 4; i++) tma_ld2(sb + i * 3 * SLOT, &P.act_ld, sb + SM_BAR + B_FULL + i * 8, C_XN + i * 64, r * 128);
          } else if (spare && !(t & 1)) {
            wait_flag(&fl->ln[r][0], ep1 * 64);
          }
#pragma unroll 1
          for (; k < 16; k++) {
            p.acquire(3);
            if (lane == 0) {
              mbar_expect_tx(p.full(), bytes);
              LDW(p.slot(1 + rank), mb, p.full(), 0, k * 64 + rank * 32, nb0);
              tma_ld2(p.slot(0), &P.act_ld, p.full(), C_XN + k * 64, r * 128);
            }
            p.advance(3);
          }
        }
      }
      if (!spare) {
        const int kvrow = (j >> 1) * SK + KV0;
#pragma unroll 1
        for (int t = 0; t < 2; t++) {
          const int nb0 = (4 * j + 2 * t) * 2;
#pragma unroll 1
          for (int k = 0; k < 16; k++) {
            p.acquire(3);
            if (lane == 0) {
              mbar_expect_tx(p.full(), 49152);
              LDW(p.slot(1 + rank), &P.wq, p.full(), 0, k * 64 + rank * 32, nb0);
              tma_ld2(p.slot(0), &P.act_ld, p.full(), C_XN + k * 64, row0);
            }
            p.advance(3);
          }
#pragma unroll 1
          for (int i = 0; i < 16; i++) {
            const bool is_k = i == 0 || (i < 15 && (i & 1));
            const int ch = (is_k ? ((i + 1) >> 1) : (i == 15 ? 7 : (i >> 1) - 1)) & 3;
            p.acquire(2);
            if (lane == 0) {
              mbar_expect_tx(p.full(), 32768);
              if (is_k) tma_ld2_mc(p.slot(rank), &P.k_ld, p.full(), rank * 64, kvrow + ch * 128);
              else      tma_ld3_mc(p.slot(rank), &P.v_ld, p.full(), 0, kvrow + ch * 128 + rank * 64, 0);
            }
            p.advance(2);
            if (t == 1 && i == 8 && !is_s) wait_flag(&fl->h[rb][0], ep1 * 64);
          }
        }
        const int jn = j & 3;
        if (is_s) {
          unsigned ready = 0;
#pragma unroll 1
          for (int i = 0; i < 64; i++) {
            const int hi = i >> 1;
            const int head = 4 * ((hi & 15) >> 1) + (hi & 1) + ((hi >> 4) << 1);
            const int kc = head * 128 + (i & 1) * 64;
            p.acquire(3);
            if (lane == 0) { mbar_expect_tx(p.full(), 49152); LDW(p.slot(1 + rank), &P.wo, p.full(), 0, kc + rank * 32, jn * 4); }
            if (!((ready >> head) & 1)) {
              do { ready = __ballot_sync(~0u, (int)(ld_acquire(&fl->o[rb][lane]) - ep1 * 2) >= 0); } while (!((ready >> head) & 1));
              __syncwarp();
              fence_async_all();
            }
            if (lane == 0) tma_ld2(p.slot(0), &P.act_ld, p.full(), C_O + kc, row0);
            p.advance(3);
          }
#pragma unroll 1
          for (int i = 0; i < 4; i++) {
            p.acquire(2);
            if (i == 2) wait_flag(&fl->g[rb][jn], ep1 * 4);
            if (lane == 0) {
              mbar_expect_tx(p.full(), 32768);
              const CUtensorMap* m = i < 2 ? &P.x_ld : &P.act_ld;
              const int c0 = (i < 2 ? 0 : C_G) + jn * 256 + (i & 1) * 128;
              tma_ld2(p.slot(0), m, p.full(), c0, row0);
              tma_ld2(p.slot(1), m, p.full(), c0 + 64, row0);
            }
            p.advance(2);
          }
        } else {
#pragma unroll 1
          for (int k = 0; k < 56; k++) {
            p.acquire(3);
            if (lane == 0) { mbar_expect_tx(p.full(), 49152); LDW(p.slot(1 + rank), &P.w2, p.full(), 0, k * 64 + rank * 32, jn * 4); }
            if (k == H_SPARE0 / 64) wait_flag(&fl->h[rb][16], ep1 * 8);
            if (lane == 0) tma_ld2(p.slot(0), &P.act_ld, p.full(), C_H + k * 64, row0);
            p.advance(3);
          }
        }
      }
      if (lane == 0) { *(volatile unsigned*)&fl->epoch[blockIdx.x] = ep1; mbar_arrive(sb + SM_BAR + B_DONE); }
    } else if (warp < 11) {
      const int wg = warp - 9;
      if (lane == 0) {
        const uint32_t stg = sb + SM_STG + wg * 16384;
        const int nev = spare ? 16 : is_s ? 8 : 10;
#pragma unroll 1
        for (int n = 0; n < nev; n++) {
          int col, row = row0, nbox = 2;
          unsigned* flag;
          if (spare) {
            const int r = ((cl & 1) * 4 + (n >> 2)) * 2 + rank;
            row = r * 128;
            col = C_H + H_SPARE0 + (n & 3) * 128;
            flag = &fl->h[r][16];
          } else if (n < 4) {
            col = C_H + j * H_REG + (n >> 1) * 192 + (n & 1) * 128;
            nbox = 2 - (n & 1);
            flag = &fl->h[rb][0];
          } else if (n < 8) {
            col = C_O + (4 * j + n - 4) * 128;
            flag = &fl->o[rb][4 * j + n - 4];
          } else {
            col = C_G + (j & 3) * 256 + (n - 8) * 128;
            flag = &fl->g[rb][j & 3];
          }
          mbar_wait(sb + SM_BAR + B_SFULL + wg * 8, n & 1);
          tma_st2(&P.act_st, stg, col, row + wg * 64);
          if (nbox == 2) tma_st2(&P.act_st, stg + 8192, col + 64, row + wg * 64);
          bulk_commit();
          bulk_wait_read0();
          mbar_arrive(sb + SM_BAR + B_SEMPTY + wg * 8);
          bulk_wait0();
          fence_async_all();
          red_release(flag, 1);
        }
        mbar_arrive(sb + SM_BAR + B_DONE);
      }
    } else {
      if (lane == 0) {
        const unsigned long long t0 = gtime();
        while (!mbar_try(sb + SM_BAR + B_DONE, 0))
          if (gtime() - t0 > 2000000000ull) __trap();
      }
    }
    __syncwarp();
    cluster_arrive();
    cluster_wait();
  } else {
    const int wg = warp >> 2;
    TS(0);
    if (!spare) {
      const int r = row0 + j * 16 + warp * 2;
      uint32_t v[2][16];
#pragma unroll
      for (int a = 0; a < 2; a++)
#pragma unroll
        for (int i = 0; i < 4; i++)
          *(uint4*)&v[a][4 * i] = __ldg((const uint4*)(P.x + (size_t)(r + a) * DM + i * 256 + lane * 8));
      cluster_arrive();
      float s[2], q[2];
#pragma unroll
      for (int a = 0; a < 2; a++) {
        float t0 = 0.f, t1 = 0.f;
#pragma unroll
        for (int i = 0; i < 16; i++) { t0 += bf_lo(v[a][i]); t1 += bf_hi(v[a][i]); }
        s[a] = t0 + t1;
      }
#pragma unroll
      for (int o = 16; o; o >>= 1) { s[0] += __shfl_xor_sync(~0u, s[0], o); s[1] += __shfl_xor_sync(~0u, s[1], o); }
#pragma unroll
      for (int a = 0; a < 2; a++) {
        s[a] *= 1.0f / DM;
        float t0 = 0.f, t1 = 0.f;
#pragma unroll
        for (int i = 0; i < 16; i++) {
          const float d0 = bf_lo(v[a][i]) - s[a], d1 = bf_hi(v[a][i]) - s[a];
          t0 = fmaf(d0, d0, t0); t1 = fmaf(d1, d1, t1);
        }
        q[a] = t0 + t1;
      }
#pragma unroll
      for (int o = 16; o; o >>= 1) { q[0] += __shfl_xor_sync(~0u, q[0], o); q[1] += __shfl_xor_sync(~0u, q[1], o); }
#pragma unroll
      for (int a = 0; a < 2; a++) {
        const uint32_t mb2 = pack_bf16(s[a], s[a]);
        const float inv = 1.0f / bf_round(sqrtf(bf_round(bf_round(q[a] * (1.0f / DM)) + 1e-5f)));
#pragma unroll
        for (int i = 0; i < 16; i++) {
          const __nv_bfloat162 d = __hsub2_rn(*(const __nv_bfloat162*)&v[a][i], *(const __nv_bfloat162*)&mb2);
          const uint32_t du = *(const uint32_t*)&d;
          v[a][i] = pack_bf16(bf_lo(du) * inv, bf_hi(du) * inv);
        }
#pragma unroll
        for (int i = 0; i < 4; i++)
          *(uint4*)(P.act + (size_t)(r + a) * ACT_W + C_XN + i * 256 + lane * 8) = *(const uint4*)&v[a][4 * i];
      }
      TS(11);
      fence_async_all();
      __syncwarp();
      if (lane == 0) red_release(&fl->ln[rb][0], 1);
      TS(13);
    } else {
      cluster_arrive();
    }
    cluster_wait();
    asm volatile("setmaxnreg.inc.sync.aligned.u32 240;");
    Cons c;
    c.zero = blockIdx.y; c.sb = sb; c.g = 0; c.pos = 0; c.nstg = 0; c.wg = wg; c.lane = lane;
    c.rel = mapa(sb + SM_BAR + B_EMPTY, lane & 1);
    float acc[128];
    TS(1);
    if (spare) {
      uint32_t pend[32];
#pragma unroll
      for (int i = 0; i < 32; i++) pend[i] = 0;
#pragma unroll 1
      for (int t = 0; t < 8; t++) {
        gemm_loop_flush<256, 2>(acc, c, pend, t > 0);
        h_epilogue<2>(acc, c, pend);
      }
      c.stg_acquire();
      stage_boxes<2>(pend, 0, c);
      TS(6);
    } else {
      if (wg == 1) bar_arrive(1, 256);
      {
        uint32_t pend[16];
#pragma unroll
        for (int i = 0; i < 16; i++) pend[i] = 0;
#pragma unroll 1
        for (int t = 0; t < 2; t++) {
          gemm_loop_flush<192, 1>(acc, c, pend, t > 0);
          h_epilogue<1>(acc, c, pend);
          TS(2 + t);
        }
        gemm_loop_flush<256, 1>(acc, c, pend, true);
      }
#pragma unroll 1
      for (int t = 0; t < 2; t++) {
        TS(8 + t);
        attn_tile(acc, c, t);
        TS(4 + t);
        gemm_loop<256>(acc, c, t == 0 ? 16 : is_s ? 64 : 56);
      }
      TS(6);
      if (is_s) {
        uint32_t rowoff, xr;
        frag_addr(rowoff, xr);
        const uint32_t x0 = c.pos;
#pragma unroll
        for (int b = 0; b < 4; b++) {
          if ((b & 1) == 0) { c.wait_full(c.g + (b >> 1)); c.wait_full(c.g + 2 + (b >> 1)); }
          const uint32_t xs = sb + wrap12(x0 + b) * SLOT + wg * 8192;
          const uint32_t sx = xs + rowoff, sg = sb + wrap12(wrap12(x0 + 4) + b) * SLOT + wg * 8192 + rowoff;
#pragma unroll
          for (int kb = 0; kb < 4; kb++) {
            const uint32_t off = (32 * kb) ^ xr;
            uint32_t xv[4], gv[4];
            ldsm4(sx + off, xv[0], xv[1], xv[2], xv[3]);
            ldsm4(sg + off, gv[0], gv[1], gv[2], gv[3]);
#pragma unroll
            for (int r = 0; r < 4; r++) {
              const uint32_t s2 = pack_bf16(acc[32 * b + 8 * kb + 2 * r], acc[32 * b + 8 * kb + 2 * r + 1]);
              const __nv_bfloat162 pr = __hmul2_rn(*(const __nv_bfloat162*)&s2, *(const __nv_bfloat162*)&gv[r]);
              const __nv_bfloat162 o = __hadd2_rn(*(const __nv_bfloat162*)&xv[r], pr);
              xv[r] = *(const uint32_t*)&o;
            }
            stsm4(sx + off, xv[0], xv[1], xv[2], xv[3]);
          }
          fence_async_smem();
          bar_sync(3 + wg, 128);
          if ((threadIdx.x & 127) == 0) { tma_st2(&P.out_st, xs, (j & 3) * 256 + b * 64, row0 + wg * 64); bulk_commit(); }
        }
        if ((threadIdx.x & 127) == 0) bulk_wait_read0();
      } else {
#pragma unroll
        for (int hh = 0; hh < 2; hh++) {
          uint32_t r[32];
#pragma unroll
          for (int i = 0; i < 32; i++) r[i] = silu2(acc[64 * hh + 2 * i], acc[64 * hh + 2 * i + 1]);
          c.stg_acquire();
          stage_boxes<2>(r, 0, c);
        }
      }
    }
    TS(7);
    __syncwarp();
    if (lane == 0) mbar_arrive(sb + SM_BAR + B_DONE);
    cluster_arrive();
    cluster_wait();
  }
}

typedef CUresult (*EncodeFn)(CUtensorMap*, CUtensorMapDataType, cuuint32_t, void*, const cuuint64_t*, const cuuint64_t*,
                             const cuuint32_t*, const cuuint32_t*, CUtensorMapInterleave, CUtensorMapSwizzle,
                             CUtensorMapL2promotion, CUtensorMapFloatOOBfill);

void map2d(EncodeFn enc, CUtensorMap* m, const void* base, uint64_t cols, uint64_t rows, uint32_t box_rows) {
  cuuint64_t dims[2] = {cols, rows};
  cuuint64_t strides[1] = {cols * 2};
  cuuint32_t box[2] = {64, box_rows};
  cuuint32_t es[2] = {1, 1};
  enc(m, CU_TENSOR_MAP_DATA_TYPE_BFLOAT16, 2, (void*)base, dims, strides, box, es, CU_TENSOR_MAP_INTERLEAVE_NONE,
      CU_TENSOR_MAP_SWIZZLE_128B, CU_TENSOR_MAP_L2_PROMOTION_L2_256B, CU_TENSOR_MAP_FLOAT_OOB_FILL_NONE);
}
void map3d(EncodeFn enc, CUtensorMap* m, const void* base, uint64_t cols, uint64_t rows, uint32_t box_rows, uint32_t box_blks) {
  cuuint64_t dims[3] = {64, rows, cols / 64};
  cuuint64_t strides[2] = {cols * 2, 128};
  cuuint32_t box[3] = {64, box_rows, box_blks};
  cuuint32_t es[3] = {1, 1, 1};
  enc(m, CU_TENSOR_MAP_DATA_TYPE_BFLOAT16, 3, (void*)base, dims, strides, box, es, CU_TENSOR_MAP_INTERLEAVE_NONE,
      CU_TENSOR_MAP_SWIZZLE_128B, CU_TENSOR_MAP_L2_PROMOTION_L2_256B, CU_TENSOR_MAP_FLOAT_OOB_FILL_NONE);
}

}

extern "C" void kernel_launch(void* const* d_in, const int* in_sizes, int n_in, void* d_out, int out_size) {
  (void)in_sizes; (void)n_in; (void)out_size;
  static EncodeFn enc = nullptr;
  static void* act = nullptr;
  static void* flags = nullptr;
  if (!enc) {
    void* fn = nullptr;
    cudaDriverEntryPointQueryResult qr;
    cudaGetDriverEntryPoint("cuTensorMapEncodeTiled", &fn, cudaEnableDefault, &qr);
    enc = (EncodeFn)fn;
    cudaGetSymbolAddress(&act, g_act);
    cudaGetSymbolAddress(&flags, g_flags);
    cudaFuncSetAttribute(fused_kernel, cudaFuncAttributeMaxDynamicSharedMemorySize, SMEM_BYTES);
  }
  Params P;
  map2d(enc, &P.act_ld, act, ACT_W, SEQ, 128);
  map2d(enc, &P.act_st, act, ACT_W, SEQ, 64);
  map2d(enc, &P.x_ld, d_in[0], DM, SEQ, 128);
  map2d(enc, &P.out_st, d_out, DM, SEQ, 64);
  map2d(enc, &P.k_ld, d_in[1], 128, 4 * SK, 128);
  map3d(enc, &P.v_ld, d_in[2], 128, 4 * SK, 64, 2);
  map3d(enc, &P.wq, d_in[3], NQ, DM, 32, 4);
  map3d(enc, &P.w1b4, d_in[6], DFF, DM, 32, 4);
  map3d(enc, &P.w1b3, d_in[6], DFF, DM, 32, 3);
  map3d(enc, &P.wo, d_in[4], DM, NQ, 32, 4);
  map3d(enc, &P.w2, d_in[7], DM, DFF, 32, 4);
  P.x = (const __nv_bfloat16*)d_in[0];
  P.act = (__nv_bfloat16*)act;
  P.flags = (Flags*)flags;
  fused_kernel<<<NCLUSTER * 2, 384, SMEM_BYTES>>>(P);
}
```

```cpp
#include <cuda_runtime.h>
#include <cuda_bf16.h>
#include <cuda.h>
#include <stdint.h>

namespace {

constexpr int SEQ    = 2048;
constexpr int DM     = 1024;
constexpr int NQ     = 4096;
constexpr int DFF    = 3584;
constexpr int SK     = 2048;
constexpr int WIN    = 512;
constexpr int KV0    = SK - WIN;
constexpr int C_XN = 0, C_O = 1024, C_H = 5120, C_G = 8704, ACT_W = 9728;

constexpr int H_REG = 384, H_SPARE0 = 8 * H_REG;
static_assert(H_SPARE0 + 512 == DFF, "H split");

constexpr int NSLOT = 12, SLOT = 16384, NBAR = 8;
constexpr int SM_STG = NSLOT * SLOT;
constexpr int SM_BAR = SM_STG + 2 * 16384;
constexpr int SMEM_BYTES = SM_BAR + 256 + 1024;
constexpr int B_FULL = 0, B_EMPTY = 64, B_SFULL = 128, B_SEMPTY = 144, B_DONE = 160;

constexpr int NCLUSTER = 66;

struct Flags {
  unsigned ln[16][32];
  unsigned h[16][32];
  unsigned o[16][32];
  unsigned g[16][32];
  unsigned epoch[160];
};
__device__ __nv_bfloat16 g_act[(size_t)SEQ * ACT_W];
__device__ Flags g_flags;

struct Params {
  CUtensorMap act_ld, act_st, x_ld, out_st, k_ld, v_ld, wq, w1b4, w1b3, wo, w2;
  const __nv_bfloat16* x;
  __nv_bfloat16* act;
  Flags* flags;
};

__device__ __forceinline__ uint32_t smem_u32(const void* p) { return (uint32_t)__cvta_generic_to_shared(p); }
__device__ __forceinline__ void mbar_init(uint32_t bar, uint32_t cnt) {
  asm volatile("mbarrier.init.shared::cta.b64 [%0], %1;" ::"r"(bar), "r"(cnt) : "memory");
}
__device__ __forceinline__ bool mbar_try(uint32_t bar, uint32_t parity) {
  uint32_t ok;
  asm volatile("{\n.reg .pred p;\nmbarrier.try_wait.parity.shared::cta.b64 p, [%1], %2;\nselp.u32 %0, 1, 0, p;\n}\n"
               : "=r"(ok) : "r"(bar), "r"(parity) : "memory");
  return ok;
}
__device__ __forceinline__ void mbar_wait(uint32_t bar, uint32_t parity) {
  asm volatile("{\n.reg .pred p;\nWAIT_%=:\nmbarrier.try_wait.parity.shared::cta.b64 p, [%0], %1;\n@p bra DONE_%=;\nbra WAIT_%=;\nDONE_%=:\n}\n"
               ::"r"(bar), "r"(parity) : "memory");
}
__device__ __forceinline__ void mbar_arrive(uint32_t bar) {
  asm volatile("mbarrier.arrive.shared::cta.b64 _, [%0];" ::"r"(bar) : "memory");
}
__device__ __forceinline__ void mbar_arrive_cluster(uint32_t cluster_addr) {
  asm volatile("mbarrier.arrive.shared::cluster.b64 _, [%0];" ::"r"(cluster_addr) : "memory");
}
__device__ __forceinline__ void mbar_expect_tx(uint32_t bar, uint32_t bytes) {
  asm volatile("mbarrier.arrive.expect_tx.shared::cta.b64 _, [%0], %1;" ::"r"(bar), "r"(bytes) : "memory");
}
__device__ __forceinline__ uint32_t mapa(uint32_t addr, uint32_t rank) {
  uint32_t r;
  asm("mapa.shared::cluster.u32 %0, %1, %2;" : "=r"(r) : "r"(addr), "r"(rank));
  return r;
}
__device__ __forceinline__ void cluster_arrive() { asm volatile("barrier.cluster.arrive.relaxed.aligned;" ::: "memory"); }
__device__ __forceinline__ void cluster_wait() { asm volatile("barrier.cluster.wait.acquire.aligned;" ::: "memory"); }
__device__ __forceinline__ void bar_sync(int id, int n) { asm volatile("bar.sync %0, %1;" ::"r"(id), "r"(n) : "memory"); }
__device__ __forceinline__ void bar_arrive(int id, int n) { asm volatile("bar.arrive %0, %1;" ::"r"(id), "r"(n) : "memory"); }
__device__ __forceinline__ void fence_async_smem() { asm volatile("fence.proxy.async.shared::cta;" ::: "memory"); }
__device__ __forceinline__ void fence_async_all() { asm volatile("fence.proxy.async.global;" ::: "memory"); }

__device__ __forceinline__ void tma_ld2(uint32_t dst, const CUtensorMap* m, uint32_t bar, int c0, int c1) {
  asm volatile("cp.async.bulk.tensor.2d.shared::cluster.global.mbarrier::complete_tx::bytes [%0], [%1, {%3, %4}], [%2];"
               ::"r"(dst), "l"(m), "r"(bar), "r"(c0), "r"(c1) : "memory");
}
__device__ __forceinline__ void tma_ld2_mc(uint32_t dst, const CUtensorMap* m, uint32_t bar, int c0, int c1) {
  asm volatile("cp.async.bulk.tensor.2d.shared::cluster.global.mbarrier::complete_tx::bytes.multicast::cluster [%0], [%1, {%3, %4}], [%2], %5;"
               ::"r"(dst), "l"(m), "r"(bar), "r"(c0), "r"(c1), "h"((uint16_t)3) : "memory");
}
__device__ __forceinline__ void tma_ld3_mc(uint32_t dst, const CUtensorMap* m, uint32_t bar, int c0, int c1, int c2) {
  asm volatile("cp.async.bulk.tensor.3d.shared::cluster.global.mbarrier::complete_tx::bytes.multicast::cluster [%0], [%1, {%3, %4, %5}], [%2], %6;"
               ::"r"(dst), "l"(m), "r"(bar), "r"(c0), "r"(c1), "r"(c2), "h"((uint16_t)3) : "memory");
}
__device__ __forceinline__ void tma_ld3_mc_hint(uint32_t dst, const CUtensorMap* m, uint32_t bar, int c0, int c1, int c2, uint64_t pol) {
  asm volatile("cp.async.bulk.tensor.3d.shared::cluster.global.mbarrier::complete_tx::bytes.multicast::cluster.L2::cache_hint [%0], [%1, {%3, %4, %5}], [%2], %6, %7;"
               ::"r"(dst), "l"(m), "r"(bar), "r"(c0), "r"(c1), "r"(c2), "h"((uint16_t)3), "l"(pol) : "memory");
}
__device__ __forceinline__ uint64_t policy_evict_first() {
  uint64_t p;
  asm volatile("createpolicy.fractional.L2::evict_first.b64 %0, 1.0;" : "=l"(p));
  return p;
}
__device__ __forceinline__ void tma_st2(const CUtensorMap* m, uint32_t src, int c0, int c1) {
  asm volatile("cp.async.bulk.tensor.2d.global.shared::cta.bulk_group [%0, {%2, %3}], [%1];"
               ::"l"(m), "r"(src), "r"(c0), "r"(c1) : "memory");
}
__device__ __forceinline__ void tma_pf3(const CUtensorMap* m, int c0, int c1, int c2) {
  asm volatile("cp.async.bulk.prefetch.tensor.3d.L2.global [%0, {%1, %2, %3}];" ::"l"(m), "r"(c0), "r"(c1), "r"(c2) : "memory");
}
__device__ __forceinline__ void bulk_commit() { asm volatile("cp.async.bulk.commit_group;" ::: "memory"); }
__device__ __forceinline__ void bulk_wait_read0() { asm volatile("cp.async.bulk.wait_group.read 0;" ::: "memory"); }
__device__ __forceinline__ void bulk_wait0() { asm volatile("cp.async.bulk.wait_group 0;" ::: "memory"); }
__device__ __forceinline__ void prefetch_map(const CUtensorMap* m) {
  asm volatile("prefetch.tensormap [%0];" ::"l"(m) : "memory");
}
__device__ __forceinline__ unsigned ld_acquire(const unsigned* p) {
  unsigned v;
  asm volatile("ld.acquire.gpu.global.u32 %0, [%1];" : "=r"(v) : "l"(p) : "memory");
  return v;
}
__device__ __forceinline__ void red_release(unsigned* p, unsigned v) {
  asm volatile("red.release.gpu.global.add.u32 [%0], %1;" ::"l"(p), "r"(v) : "memory");
}
__device__ __forceinline__ void wg_fence() { asm volatile("wgmma.fence.sync.aligned;" ::: "memory"); }
__device__ __forceinline__ void wg_commit() { asm volatile("wgmma.commit_group.sync.aligned;" ::: "memory"); }
template <int N> __device__ __forceinline__ void wg_wait() { asm volatile("wgmma.wait_group.sync.aligned %0;" ::"n"(N) : "memory"); }
template <int N> __device__ __forceinline__ void fence_regs(float (&d)[N]) {
#pragma unroll
  for (int i = 0; i < N; i++) asm volatile("" : "+f"(d[i])::"memory");
}
template <int N> __device__ __forceinline__ void fence_regs(uint32_t (&d)[N]) {
#pragma unroll
  for (int i = 0; i < N; i++) asm volatile("" : "+r"(d[i])::"memory");
}
__device__ __forceinline__ uint64_t mkdesc(uint32_t addr, uint32_t lbo, uint32_t sbo) {
  return (uint64_t)((addr & 0x3FFFF) >> 4) | ((uint64_t)(lbo >> 4) << 16) | ((uint64_t)(sbo >> 4) << 32) | (1ull << 62);
}
__device__ __forceinline__ uint32_t pack_bf16(float lo, float hi) {
  uint32_t r;
  asm("cvt.rn.bf16x2.f32 %0, %1, %2;" : "=r"(r) : "f"(hi), "f"(lo));
  return r;
}
__device__ __forceinline__ uint32_t pack_bf16_relu(float lo, float hi) {
  uint32_t r;
  asm("cvt.rn.relu.bf16x2.f32 %0, %1, %2;" : "=r"(r) : "f"(hi), "f"(lo));
  return r;
}
__device__ __forceinline__ float bf_lo(uint32_t v) { return __uint_as_float(v << 16); }
__device__ __forceinline__ float bf_hi(uint32_t v) { return __uint_as_float(v & 0xFFFF0000u); }
__device__ __forceinline__ float bf_round(float v) { return __bfloat162float(__float2bfloat16_rn(v)); }
__device__ __forceinline__ float ex2(float x) {
  float r;
  asm("ex2.approx.ftz.f32 %0, %1;" : "=f"(r) : "f"(x));
  return r;
}
__device__ __forceinline__ float rcp(float x) {
  float r;
  asm("rcp.approx.ftz.f32 %0, %1;" : "=f"(r) : "f"(x));
  return r;
}
__device__ __forceinline__ uint32_t tid_x() {
  uint32_t t;
  asm volatile("mov.u32 %0, %%tid.x;" : "=r"(t));
  return t;
}
__device__ __forceinline__ void stsm4(uint32_t addr, uint32_t r0, uint32_t r1, uint32_t r2, uint32_t r3) {
  asm volatile("stmatrix.sync.aligned.m8n8.x4.shared.b16 [%0], {%1, %2, %3, %4};" ::"r"(addr), "r"(r0), "r"(r1), "r"(r2), "r"(r3) : "memory");
}
__device__ __forceinline__ void ldsm4(uint32_t addr, uint32_t& r0, uint32_t& r1, uint32_t& r2, uint32_t& r3) {
  asm volatile("ldmatrix.sync.aligned.m8n8.x4.shared.b16 {%0, %1, %2, %3}, [%4];" : "=r"(r0), "=r"(r1), "=r"(r2), "=r"(r3) : "r"(addr) : "memory");
}
__device__ __forceinline__ void sts128(uint32_t addr, uint32_t r0, uint32_t r1, uint32_t r2, uint32_t r3) {
  asm volatile("st.shared.v4.b32 [%0], {%1, %2, %3, %4};" ::"r"(addr), "r"(r0), "r"(r1), "r"(r2), "r"(r3) : "memory");
}
__device__ __forceinline__ void lds128(uint32_t addr, uint32_t& r0, uint32_t& r1, uint32_t& r2, uint32_t& r3) {
  asm volatile("ld.shared.v4.b32 {%0, %1, %2, %3}, [%4];" : "=r"(r0), "=r"(r1), "=r"(r2), "=r"(r3) : "r"(addr) : "memory");
}
__device__ __forceinline__ unsigned long long gtime() {
  unsigned long long t;
  asm volatile("mov.u64 %0, %globaltimer;" : "=l"(t));
  return t;
}

__device__ __forceinline__ void wgmma_ss_n256_tb(float (&d)[128], uint64_t da, uint64_t db, uint32_t sc) {
  asm volatile("{\n.reg .pred p;\nsetp.ne.b32 p, %130, 0;\n"
    "wgmma.mma_async.sync.aligned.m64n256k16.f32.bf16.bf16 "
    "{%0, %1, %2, %3, %4, %5, %6, %7, %8, %9, %10, %11, %12, %13, %14, %15, %16, %17, %18, %19, %20, %21, %22, %23, %24, %25, %26, %27, %28, %29, %30, %31, %32, %33, %34, %35, %36, %37, %38, %39, %40, %41, %42, %43, %44, %45, %46, %47, %48, %49, %50, %51, %52, %53, %54, %55, %56, %57, %58, %59, %60, %61, %62, %63, %64, %65, %66, %67, %68, %69, %70, %71, %72, %73, %74, %75, %76, %77, %78, %79, %80, %81, %82, %83, %84, %85, %86, %87, %88, %89, %90, %91, %92, %93, %94, %95, %96, %97, %98, %99, %100, %101, %102, %103, %104, %105, %106, %107, %108, %109, %110, %111, %112, %113, %114, %115, %116, %117, %118, %119, %120, %121, %122, %123, %124, %125, %126, %127}, %128, %129, p, 1, 1, 0, 1;\n}\n"
    : "+f"(d[0]), "+f"(d[1]), "+f"(d[2]), "+f"(d[3]), "+f"(d[4]), "+f"(d[5]), "+f"(d[6]), "+f"(d[7]), "+f"(d[8]), "+f"(d[9]), "+f"(d[10]), "+f"(d[11]), "+f"(d[12]), "+f"(d[13]), "+f"(d[14]), "+f"(d[15]), "+f"(d[16]), "+f"(d[17]), "+f"(d[18]), "+f"(d[19]), "+f"(d[20]), "+f"(d[21]), "+f"(d[22]), "+f"(d[23]), "+f"(d[24]), "+f"(d[25]), "+f"(d[26]), "+f"(d[27]), "+f"(d[28]), "+f"(d[29]), "+f"(d[30]), "+f"(d[31]), "+f"(d[32]), "+f"(d[33]), "+f"(d[34]), "+f"(d[35]), "+f"(d[36]), "+f"(d[37]), "+f"(d[38]), "+f"(d[39]), "+f"(d[40]), "+f"(d[41]), "+f"(d[42]), "+f"(d[43]), "+f"(d[44]), "+f"(d[45]), "+f"(d[46]), "+f"(d[47]), "+f"(d[48]), "+f"(d[49]), "+f"(d[50]), "+f"(d[51]), "+f"(d[52]), "+f"(d[53]), "+f"(d[54]), "+f"(d[55]), "+f"(d[56]), "+f"(d[57]), "+f"(d[58]), "+f"(d[59]), "+f"(d[60]), "+f"(d[61]), "+f"(d[62]), "+f"(d[63]), "+f"(d[64]), "+f"(d[65]), "+f"(d[66]), "+f"(d[67]), "+f"(d[68]), "+f"(d[69]), "+f"(d[70]), "+f"(d[71]), "+f"(d[72]), "+f"(d[73]), "+f"(d[74]), "+f"(d[75]), "+f"(d[76]), "+f"(d[77]), "+f"(d[78]), "+f"(d[79]), "+f"(d[80]), "+f"(d[81]), "+f"(d[82]), "+f"(d[83]), "+f"(d[84]), "+f"(d[85]), "+f"(d[86]), "+f"(d[87]), "+f"(d[88]), "+f"(d[89]), "+f"(d[90]), "+f"(d[91]), "+f"(d[92]), "+f"(d[93]), "+f"(d[94]), "+f"(d[95]), "+f"(d[96]), "+f"(d[97]), "+f"(d[98]), "+f"(d[99]), "+f"(d[100]), "+f"(d[101]), "+f"(d[102]), "+f"(d[103]), "+f"(d[104]), "+f"(d[105]), "+f"(d[106]), "+f"(d[107]), "+f"(d[108]), "+f"(d[109]), "+f"(d[110]), "+f"(d[111]), "+f"(d[112]), "+f"(d[113]), "+f"(d[114]), "+f"(d[115]), "+f"(d[116]), "+f"(d[117]), "+f"(d[118]), "+f"(d[119]), "+f"(d[120]), "+f"(d[121]), "+f"(d[122]), "+f"(d[123]), "+f"(d[124]), "+f"(d[125]), "+f"(d[126]), "+f"(d[127])
    : "l"(da), "l"(db), "r"(sc));
}
__device__ __forceinline__ void wgmma_ss_n192_tb(float (&d)[128], uint64_t da, uint64_t db, uint32_t sc) {
  asm volatile("{\n.reg .pred p;\nsetp.ne.b32 p, %98, 0;\n"
    "wgmma.mma_async.sync.aligned.m64n192k16.f32.bf16.bf16 "
    "{%0, %1, %2, %3, %4, %5, %6, %7, %8, %9, %10, %11, %12, %13, %14, %15, %16, %17, %18, %19, %20, %21, %22, %23, %24, %25, %26, %27, %28, %29, %30, %31, %32, %33, %34, %35, %36, %37, %38, %39, %40, %41, %42, %43, %44, %45, %46, %47, %48, %49, %50, %51, %52, %53, %54, %55, %56, %57, %58, %59, %60, %61, %62, %63, %64, %65, %66, %67, %68, %69, %70, %71, %72, %73, %74, %75, %76, %77, %78, %79, %80, %81, %82, %83, %84, %85, %86, %87, %88, %89, %90, %91, %92, %93, %94, %95}, %96, %97, p, 1, 1, 0, 1;\n}\n"
    : "+f"(d[0]), "+f"(d[1]), "+f"(d[2]), "+f"(d[3]), "+f"(d[4]), "+f"(d[5]), "+f"(d[6]), "+f"(d[7]), "+f"(d[8]), "+f"(d[9]), "+f"(d[10]), "+f"(d[11]), "+f"(d[12]), "+f"(d[13]), "+f"(d[14]), "+f"(d[15]), "+f"(d[16]), "+f"(d[17]), "+f"(d[18]), "+f"(d[19]), "+f"(d[20]), "+f"(d[21]), "+f"(d[22]), "+f"(d[23]), "+f"(d[24]), "+f"(d[25]), "+f"(d[26]), "+f"(d[27]), "+f"(d[28]), "+f"(d[29]), "+f"(d[30]), "+f"(d[31]), "+f"(d[32]), "+f"(d[33]), "+f"(d[34]), "+f"(d[35]), "+f"(d[36]), "+f"(d[37]), "+f"(d[38]), "+f"(d[39]), "+f"(d[40]), "+f"(d[41]), "+f"(d[42]), "+f"(d[43]), "+f"(d[44]), "+f"(d[45]), "+f"(d[46]), "+f"(d[47]), "+f"(d[48]), "+f"(d[49]), "+f"(d[50]), "+f"(d[51]), "+f"(d[52]), "+f"(d[53]), "+f"(d[54]), "+f"(d[55]), "+f"(d[56]), "+f"(d[57]), "+f"(d[58]), "+f"(d[59]), "+f"(d[60]), "+f"(d[61]), "+f"(d[62]), "+f"(d[63]), "+f"(d[64]), "+f"(d[65]), "+f"(d[66]), "+f"(d[67]), "+f"(d[68]), "+f"(d[69]), "+f"(d[70]), "+f"(d[71]), "+f"(d[72]), "+f"(d[73]), "+f"(d[74]), "+f"(d[75]), "+f"(d[76]), "+f"(d[77]), "+f"(d[78]), "+f"(d[79]), "+f"(d[80]), "+f"(d[81]), "+f"(d[82]), "+f"(d[83]), "+f"(d[84]), "+f"(d[85]), "+f"(d[86]), "+f"(d[87]), "+f"(d[88]), "+f"(d[89]), "+f"(d[90]), "+f"(d[91]), "+f"(d[92]), "+f"(d[93]), "+f"(d[94]), "+f"(d[95])
    : "l"(da), "l"(db), "r"(sc));
}
__device__ __forceinline__ void wgmma_rs_n128(float (&d)[64], uint32_t a0, uint32_t a1, uint32_t a2, uint32_t a3, uint64_t db, uint32_t sc) {
  asm volatile("{\n.reg .pred p;\nsetp.ne.b32 p, %69, 0;\n"
    "wgmma.mma_async.sync.aligned.m64n128k16.f32.bf16.bf16 "
    "{%0, %1, %2, %3, %4, %5, %6, %7, %8, %9, %10, %11, %12, %13, %14, %15, %16, %17, %18, %19, %20, %21, %22, %23, %24, %25, %26, %27, %28, %29, %30, %31, %32, %33, %34, %35, %36, %37, %38, %39, %40, %41, %42, %43, %44, %45, %46, %47, %48, %49, %50, %51, %52, %53, %54, %55, %56, %57, %58, %59, %60, %61, %62, %63}, {%64, %65, %66, %67}, %68, p, 1, 1, 0;\n}\n"
    : "+f"(d[0]), "+f"(d[1]), "+f"(d[2]), "+f"(d[3]), "+f"(d[4]), "+f"(d[5]), "+f"(d[6]), "+f"(d[7]), "+f"(d[8]), "+f"(d[9]), "+f"(d[10]), "+f"(d[11]), "+f"(d[12]), "+f"(d[13]), "+f"(d[14]), "+f"(d[15]), "+f"(d[16]), "+f"(d[17]), "+f"(d[18]), "+f"(d[19]), "+f"(d[20]), "+f"(d[21]), "+f"(d[22]), "+f"(d[23]), "+f"(d[24]), "+f"(d[25]), "+f"(d[26]), "+f"(d[27]), "+f"(d[28]), "+f"(d[29]), "+f"(d[30]), "+f"(d[31]), "+f"(d[32]), "+f"(d[33]), "+f"(d[34]), "+f"(d[35]), "+f"(d[36]), "+f"(d[37]), "+f"(d[38]), "+f"(d[39]), "+f"(d[40]), "+f"(d[41]), "+f"(d[42]), "+f"(d[43]), "+f"(d[44]), "+f"(d[45]), "+f"(d[46]), "+f"(d[47]), "+f"(d[48]), "+f"(d[49]), "+f"(d[50]), "+f"(d[51]), "+f"(d[52]), "+f"(d[53]), "+f"(d[54]), "+f"(d[55]), "+f"(d[56]), "+f"(d[57]), "+f"(d[58]), "+f"(d[59]), "+f"(d[60]), "+f"(d[61]), "+f"(d[62]), "+f"(d[63])
    : "r"(a0), "r"(a1), "r"(a2), "r"(a3), "l"(db), "r"(sc));
}
__device__ __forceinline__ void wgmma_rs_n128_tb(float (&d)[64], uint32_t a0, uint32_t a1, uint32_t a2, uint32_t a3, uint64_t db, uint32_t sc) {
  asm volatile("{\n.reg .pred p;\nsetp.ne.b32 p, %69, 0;\n"
    "wgmma.mma_async.sync.aligned.m64n128k16.f32.bf16.bf16 "
    "{%0, %1, %2, %3, %4, %5, %6, %7, %8, %9, %10, %11, %12, %13, %14, %15, %16, %17, %18, %19, %20, %21, %22, %23, %24, %25, %26, %27, %28, %29, %30, %31, %32, %33, %34, %35, %36, %37, %38, %39, %40, %41, %42, %43, %44, %45, %46, %47, %48, %49, %50, %51, %52, %53, %54, %55, %56, %57, %58, %59, %60, %61, %62, %63}, {%64, %65, %66, %67}, %68, p, 1, 1, 1;\n}\n"
    : "+f"(d[0]), "+f"(d[1]), "+f"(d[2]), "+f"(d[3]), "+f"(d[4]), "+f"(d[5]), "+f"(d[6]), "+f"(d[7]), "+f"(d[8]), "+f"(d[9]), "+f"(d[10]), "+f"(d[11]), "+f"(d[12]), "+f"(d[13]), "+f"(d[14]), "+f"(d[15]), "+f"(d[16]), "+f"(d[17]), "+f"(d[18]), "+f"(d[19]), "+f"(d[20]), "+f"(d[21]), "+f"(d[22]), "+f"(d[23]), "+f"(d[24]), "+f"(d[25]), "+f"(d[26]), "+f"(d[27]), "+f"(d[28]), "+f"(d[29]), "+f"(d[30]), "+f"(d[31]), "+f"(d[32]), "+f"(d[33]), "+f"(d[34]), "+f"(d[35]), "+f"(d[36]), "+f"(d[37]), "+f"(d[38]), "+f"(d[39]), "+f"(d[40]), "+f"(d[41]), "+f"(d[42]), "+f"(d[43]), "+f"(d[44]), "+f"(d[45]), "+f"(d[46]), "+f"(d[47]), "+f"(d[48]), "+f"(d[49]), "+f"(d[50]), "+f"(d[51]), "+f"(d[52]), "+f"(d[53]), "+f"(d[54]), "+f"(d[55]), "+f"(d[56]), "+f"(d[57]), "+f"(d[58]), "+f"(d[59]), "+f"(d[60]), "+f"(d[61]), "+f"(d[62]), "+f"(d[63])
    : "r"(a0), "r"(a1), "r"(a2), "r"(a3), "l"(db), "r"(sc));
}

#define TS(i) do {} while (0)
#define TR(j, i) do {} while (0)
#define TSS(i, c) do {} while (0)

__device__ __forceinline__ uint32_t wrap12(uint32_t p) { return p >= NSLOT ? p - NSLOT : p; }

struct Cons {
  uint32_t sb;
  uint32_t g, pos;
  uint32_t rel;
  uint32_t nstg;
  uint32_t zero;
  int wg, lane;
  __device__ __forceinline__ void wait_full(uint32_t gg) const { mbar_wait(sb + SM_BAR + B_FULL + (gg & 7) * 8, (gg >> 3) & 1); }
  __device__ __forceinline__ void release(uint32_t gg) const { if (lane < 2) mbar_arrive_cluster(rel + (gg & 7) * 8); }
  __device__ __forceinline__ void stg_acquire() { mbar_wait(sb + SM_BAR + B_SEMPTY + wg * 8, (nstg & 1) ^ 1); nstg++; }
  __device__ __forceinline__ void stg_publish() const {
    fence_async_smem();
    __syncwarp();
    if (lane == 0) mbar_arrive(sb + SM_BAR + B_SFULL + wg * 8);
  }
};

__device__ __forceinline__ void frag_addr(uint32_t& rowoff, uint32_t& xr) {
  const uint32_t t = tid_x();
  rowoff = ((t >> 5) & 3) * 2048 + (t & 15) * 128;
  xr = (((t >> 4) & 1) ^ (t & 7)) << 4;
}
template <int NB, int NR>
__device__ __forceinline__ void stage_boxes(const uint32_t (&r)[NR], int r0, const Cons& c) {
  uint32_t rowoff, xr;
  frag_addr(rowoff, xr);
  const uint32_t stg = c.sb + SM_STG + c.wg * 16384 + rowoff;
#pragma unroll
  for (int b = 0; b < NB; b++)
#pragma unroll
    for (int kb = 0; kb < 4; kb++)
      stsm4(stg + b * 8192 + ((32 * kb) ^ xr), r[r0 + b * 16 + kb * 4], r[r0 + b * 16 + kb * 4 + 1], r[r0 + b * 16 + kb * 4 + 2], r[r0 + b * 16 + kb * 4 + 3]);
  c.stg_publish();
}

template <int N, bool FIRST>
__device__ __forceinline__ void gemm_step(float (&acc)[128], Cons& c) {
  const uint32_t p1 = wrap12(c.pos + 1), p2 = wrap12(c.pos + 2);
  const uint64_t da = mkdesc(c.sb + c.wg * 8192 + c.pos * SLOT, 16, 1024);
  const uint64_t b0 = mkdesc(c.sb + p1 * SLOT, 4096, 1024);
  const uint64_t b1 = mkdesc(c.sb + p2 * SLOT, 4096, 1024);
  c.wait_full(c.g);
  wg_fence();
  if (N == 256) {
    wgmma_ss_n256_tb(acc, da, b0, FIRST ? 0 : 1);
    wgmma_ss_n256_tb(acc, da + 2, b0 + 128, 1);
    wgmma_ss_n256_tb(acc, da + 4, b1, 1);
    wgmma_ss_n256_tb(acc, da + 6, b1 + 128, 1);
  } else {
    wgmma_ss_n192_tb(acc, da, b0, FIRST ? 0 : 1);
    wgmma_ss_n192_tb(acc, da + 2, b0 + 128, 1);
    wgmma_ss_n192_tb(acc, da + 4, b1, 1);
    wgmma_ss_n192_tb(acc, da + 6, b1 + 128, 1);
  }
  wg_commit();
  if (!FIRST) {
    wg_wait<1>();
    c.release(c.g - 1);
  }
  c.g++;
  c.pos = wrap12(p2 + 1);
}

template <int N>
__device__ __forceinline__ void gemm_loop(float (&acc)[128], Cons& c, int nk) {
  gemm_step<N, true>(acc, c);
#pragma unroll 1
  for (int k = 1; k < nk; k++) gemm_step<N, false>(acc, c);
  wg_wait<0>();
  c.release(c.g - 1);
  fence_regs(acc);
}
template <int N, int NB>
__device__ __forceinline__ void gemm_loop_flush(float (&acc)[128], Cons& c, const uint32_t (&pend)[NB * 16], bool flush) {
  gemm_step<N, true>(acc, c);
#pragma unroll 1
  for (int k = 1; k < 16; k++) {
    gemm_step<N, false>(acc, c);
    if (k == 3 && flush) {
      c.stg_acquire();
      stage_boxes<NB>(pend, 0, c);
    }
  }
  wg_wait<0>();
  c.release(c.g - 1);
  fence_regs(acc);
}
template <int NB>
__device__ __forceinline__ void h_epilogue(const float (&acc)[128], Cons& c, uint32_t (&pend)[NB * 16]) {
  uint32_t r[32];
#pragma unroll
  for (int i = 0; i < 32; i++) r[i] = pack_bf16_relu(acc[2 * i], acc[2 * i + 1]);
  c.stg_acquire();
  stage_boxes<2>(r, 0, c);
#pragma unroll
  for (int i = 0; i < NB * 16; i++) pend[i] = pack_bf16_relu(acc[64 + 2 * i], acc[65 + 2 * i]);
}

__device__ __forceinline__ uint32_t silu2(float lo, float hi) {
  const uint32_t f2 = pack_bf16(lo, hi);
  const float a = bf_lo(f2), b = bf_hi(f2);
  const float ta = ex2(-1.4426950408889634f * fabsf(a)), tb = ex2(-1.4426950408889634f * fabsf(b));
  const float da = 1.0f + ta, db = 1.0f + tb;
  const float r = rcp(da * db);
  return pack_bf16((a >= 0.f ? a : a * ta) * (r * db), (b >= 0.f ? b : b * tb) * (r * da));
}

constexpr float SM_C = 0.08838834764831845f * 1.4426950408889634f;

#define ONCE(c) _Pragma("unroll 1") for (uint32_t once_ = 0; once_ <= (c).zero; once_++)
__device__ __forceinline__ void row_max2(const float (&S)[64], float& n0, float& n1) {
  float x[4], y[4];
#pragma unroll
  for (int i = 0; i < 4; i++) { x[i] = fmaxf(S[4 * i], S[4 * i + 1]); y[i] = fmaxf(S[4 * i + 2], S[4 * i + 3]); }
#pragma unroll
  for (int i = 4; i < 16; i++) {
    x[i & 3] = fmaxf(x[i & 3], fmaxf(S[4 * i], S[4 * i + 1]));
    y[i & 3] = fmaxf(y[i & 3], fmaxf(S[4 * i + 2], S[4 * i + 3]));
  }
  n0 = fmaxf(fmaxf(x[0], x[1]), fmaxf(x[2], x[3]));
  n1 = fmaxf(fmaxf(y[0], y[1]), fmaxf(y[2], y[3]));
  n0 = fmaxf(n0, __shfl_xor_sync(~0u, n0, 1));
  n1 = fmaxf(n1, __shfl_xor_sync(~0u, n1, 1));
  n0 = fmaxf(n0, __shfl_xor_sync(~0u, n0, 2));
  n1 = fmaxf(n1, __shfl_xor_sync(~0u, n1, 2));
}
__device__ __forceinline__ void to_exponent(float (&S)[64], float cc0, float cc1) {
#pragma unroll
  for (int i = 0; i < 16; i++) {
    S[4 * i] = fmaf(S[4 * i], SM_C, cc0); S[4 * i + 1] = fmaf(S[4 * i + 1], SM_C, cc0);
    S[4 * i + 2] = fmaf(S[4 * i + 2], SM_C, cc1); S[4 * i + 3] = fmaf(S[4 * i + 3], SM_C, cc1);
  }
}
__device__ __forceinline__ void scale_o(float (&O)[64], float f0, float f1) {
#pragma unroll
  for (int i = 0; i < 16; i++) { O[4 * i] *= f0; O[4 * i + 1] *= f0; O[4 * i + 2] *= f1; O[4 * i + 3] *= f1; }
}
__device__ __forceinline__ void exp_stream(float (&S)[64], uint32_t (&p)[32], float (&O)[64], float& cc0, float& cc1, float& l0, float& l1) {
  float s0, s1;
#pragma unroll 1
  for (int pass = 0;; pass++) {
    float a[4] = {0.f, 0.f, 0.f, 0.f};
#pragma unroll
    for (int i = 0; i < 16; i++) {
      const float e0 = ex2(S[4 * i]), e1 = ex2(S[4 * i + 1]), e2 = ex2(S[4 * i + 2]), e3 = ex2(S[4 * i + 3]);
      a[0] += e0; a[1] += e1; a[2] += e2; a[3] += e3;
      p[2 * i] = pack_bf16(e0, e1);
      p[2 * i + 1] = pack_bf16(e2, e3);
    }
    s0 = a[0] + a[1]; s1 = a[2] + a[3];
    if (pass || !__any_sync(~0u, !(fmaxf(s0, s1) <= 65536.f))) break;
    float d0, d1;
    row_max2(S, d0, d1);
    d0 = fmaxf(d0, 0.f); d1 = fmaxf(d1, 0.f);
#pragma unroll
    for (int i = 0; i < 16; i++) { S[4 * i] -= d0; S[4 * i + 1] -= d0; S[4 * i + 2] -= d1; S[4 * i + 3] -= d1; }
    cc0 -= d0; cc1 -= d1;
    const float f0 = ex2(-d0), f1 = ex2(-d1);
    scale_o(O, f0, f1);
    l0 *= f0; l1 *= f1;
  }
  l0 += s0; l1 += s1;
}

__device__ __forceinline__ void inv_rowsum(float l0, float l1, float& i0, float& i1) {
  l0 += __shfl_xor_sync(~0u, l0, 1); l1 += __shfl_xor_sync(~0u, l1, 1);
  l0 += __shfl_xor_sync(~0u, l0, 2); l1 += __shfl_xor_sync(~0u, l1, 2);
  i0 = rcp(l0); i1 = rcp(l1);
}
__device__ __forceinline__ void write_o(const float (&O)[64], const Cons& c) {
  uint32_t rowoff, xr;
  frag_addr(rowoff, xr);
  const uint32_t stg = c.sb + SM_STG + c.wg * 16384 + rowoff;
#pragma unroll
  for (int kb = 0; kb < 8; kb++)
    stsm4(stg + (kb >> 2) * 8192 + ((32 * (kb & 3)) ^ xr),
          pack_bf16(O[8 * kb], O[8 * kb + 1]), pack_bf16(O[8 * kb + 2], O[8 * kb + 3]),
          pack_bf16(O[8 * kb + 4], O[8 * kb + 5]), pack_bf16(O[8 * kb + 6], O[8 * kb + 7]));
  c.stg_publish();
}

__device__ __forceinline__ void issue_qk(float (&S)[64], const uint32_t (&q)[32], uint32_t s0, uint32_t s1, uint32_t zero) {
  const uint64_t d0 = mkdesc(s0, 16, 1024), d1 = mkdesc(s1, 16, 1024);
#pragma unroll
  for (int kk = 0; kk < 8; kk++)
    wgmma_rs_n128(S, q[4 * kk], q[4 * kk + 1], q[4 * kk + 2], q[4 * kk + 3], (kk < 4 ? d0 : d1) + (kk & 3) * 2, kk > 0 ? 1u : zero);
}
__device__ __forceinline__ void issue_pv(float (&O)[64], const uint32_t (&p)[32], uint32_t s0, uint32_t s1, uint32_t accum) {
  const uint64_t d0 = mkdesc(s0, 8192, 1024), d1 = mkdesc(s1, 8192, 1024);
#pragma unroll
  for (int kk = 0; kk < 8; kk++)
    wgmma_rs_n128_tb(O, p[4 * kk], p[4 * kk + 1], p[4 * kk + 2], p[4 * kk + 3], (kk < 4 ? d0 : d1) + (kk & 3) * 128, kk > 0 ? 1u : accum);
}

#define TURN_SYNC()   bar_sync(1 + c.wg, 256)
#define TURN_PASS()   bar_arrive(2 - c.wg, 256)

__device__ __forceinline__ void attn_tile(const float (&acc)[128], Cons& c, int t) {
  uint32_t q[32], p[32];
  float S[64], O[64];
  const uint32_t stash = c.sb + SM_STG + c.wg * 16384 + ((threadIdx.x >> 5) & 3) * 2048 + c.lane * 16;
#pragma unroll
  for (int i = 0; i < 32; i++) q[i] = pack_bf16(acc[2 * i], acc[2 * i + 1]);
  c.stg_acquire();
#pragma unroll
  for (int i = 0; i < 8; i++)
    sts128(stash + (i >> 2) * 8192 + (i & 3) * 512, pack_bf16(acc[64 + 8 * i], acc[65 + 8 * i]), pack_bf16(acc[66 + 8 * i], acc[67 + 8 * i]),
           pack_bf16(acc[68 + 8 * i], acc[69 + 8 * i]), pack_bf16(acc[70 + 8 * i], acc[71 + 8 * i]));
  fence_regs(q);
  TR(0, 0);
  TURN_SYNC();
  TR(0, 1);
  c.wait_full(c.g);
  wg_fence();
  issue_qk(S, q, c.sb + c.pos * SLOT, c.sb + wrap12(c.pos + 1) * SLOT, 0);
  wg_commit();
  TURN_PASS();
  TR(0, 2);
  wg_wait<0>();
  TR(0, 3);
  fence_regs(S);
  c.release(c.g);
  c.g++;
  c.pos = wrap12(c.pos + 2);
  float cc0, cc1, l0 = 0.f, l1 = 0.f;
  row_max2(S, cc0, cc1);
  cc0 *= -SM_C; cc1 *= -SM_C;
  to_exponent(S, cc0, cc1);
#pragma unroll
  for (int i = 0; i < 64; i++) O[i] = 0.f;
  exp_stream(S, p, O, cc0, cc1, l0, l1);
#pragma unroll 1
  for (int j = 0; j < 7 + (int)c.zero; j++) {
    const uint32_t k0 = c.pos, k1 = wrap12(k0 + 1), v0 = wrap12(k0 + 2), v1 = wrap12(k0 + 3);
    TR(j + 1, 0);
    TURN_SYNC();
    TR(j + 1, 1);
    c.wait_full(c.g);
    wg_fence();
    issue_qk(S, q, c.sb + k0 * SLOT, c.sb + k1 * SLOT, 0);
    wg_commit();
    c.wait_full(c.g + 1);
    wg_fence();
    issue_pv(O, p, c.sb + v0 * SLOT, c.sb + v1 * SLOT, j != 4);
    wg_commit();
    TURN_PASS();
    TR(j + 1, 2);
    wg_wait<1>();
    TR(j + 1, 3);
    fence_regs(S);
    fence_regs(q);
    c.release(c.g);
    if (j == 2) {
#pragma unroll
      for (int i = 0; i < 8; i++) lds128(stash + (i >> 2) * 8192 + (i & 3) * 512, q[4 * i], q[4 * i + 1], q[4 * i + 2], q[4 * i + 3]);
      __syncwarp();
    }
    float f0, f1;
    if (j == 3) {
      row_max2(S, cc0, cc1);
      cc0 *= -SM_C; cc1 *= -SM_C;
      inv_rowsum(l0, l1, f0, f1);
      l0 = 0.f; l1 = 0.f;
    }
    ONCE(c) { to_exponent(S, cc0, cc1); }
    TR(j + 1, 4);
    wg_wait<0>();
    TR(j + 1, 5);
    fence_regs(O);
    fence_regs(p);
    c.release(c.g + 1);
    c.g += 2;
    c.pos = wrap12(v1 + 1);
    if (j == 3) {
      scale_o(O, f0, f1);
      write_o(O, c);
    }
    TR(j + 1, 6);
    exp_stream(S, p, O, cc0, cc1, l0, l1);
  }
  TR(8, 0);
  TURN_SYNC();
  TR(8, 1);
  c.wait_full(c.g);
  wg_fence();
  issue_pv(O, p, c.sb + c.pos * SLOT, c.sb + wrap12(c.pos + 1) * SLOT, 1);
  wg_commit();
  TURN_PASS();
  TR(8, 2);
  c.stg_acquire();
  float a0, a1;
  inv_rowsum(l0, l1, a0, a1);
  wg_wait<0>();
  TR(8, 5);
  fence_regs(O);
  fence_regs(p);
  c.release(c.g);
  c.g++;
  c.pos = wrap12(c.pos + 2);
  scale_o(O, a0, a1);
  write_o(O, c);
  TR(9, 0);
}

struct Prod {
  uint32_t sb, g, pos, head, tail_g, tail_pos, hist;
  __device__ __forceinline__ uint32_t full() const { return sb + SM_BAR + B_FULL + (g & 7) * 8; }
  __device__ __forceinline__ uint32_t slot(uint32_t i) const { return sb + wrap12(pos + i) * SLOT; }
  __device__ __forceinline__ void acquire(uint32_t size) {
#pragma unroll 1
    while (head + size - tail_pos > NSLOT) {
      mbar_wait(sb + SM_BAR + B_EMPTY + (tail_g & 7) * 8, (tail_g >> 3) & 1);
      tail_pos += 2 + ((hist >> (tail_g & 31)) & 1);
      tail_g++;
    }
    hist = (hist & ~(1u << (g & 31))) | ((size - 2) << (g & 31));
  }
  __device__ __forceinline__ void advance(uint32_t size) { g++; head += size; pos = wrap12(pos + size); }
};

__device__ __forceinline__ void wait_flag(const unsigned* p, unsigned target) {
  while ((int)(ld_acquire(p) - target) < 0) {}
  fence_async_all();
}

__device__ __forceinline__ void init_barriers(uint32_t sb, int warp) {
  const uint32_t cnt = warp < 4 ? 1 : warp < 8 ? 16 : warp == 8 ? 4 : warp == 9 ? 1 : 11;
  if (warp < 11) mbar_init(sb + SM_BAR + warp * 16, cnt);
  if (warp < 10) mbar_init(sb + SM_BAR + warp * 16 + 8, cnt);
  asm volatile("fence.mbarrier_init.release.cluster;" ::: "memory");
}

#define TSP(i) do {} while (0)

__global__ void __cluster_dims__(2, 1, 1) __launch_bounds__(384, 1) fused_kernel(const __grid_constant__ Params P) {
  extern __shared__ uint8_t smem_raw[];
  const uint32_t sb = (smem_u32(smem_raw) + 1023u) & ~1023u;
  const int warp = __shfl_sync(~0u, (int)(threadIdx.x >> 5), 0);
  const int lane = threadIdx.x & 31;
  const int rank = blockIdx.x & 1;
  const int cl = blockIdx.x >> 1;
  const int j = cl >> 3;
  const int rb = (cl & 7) * 2 + rank;
  const bool is_s = j < 4, spare = j == 8;
  const int row0 = rb * 128;
  Flags* fl = P.flags;

  if (warp >= 8) {
    if (lane == 0) {
      if (warp == 8) prefetch_map(spare ? &P.w1b4 : &P.w1b3);
      if (warp == 9) prefetch_map(&P.act_ld);
      init_barriers(sb, warp);
    }
    __syncwarp();
    cluster_arrive();
    if (warp == 10 && lane == 0) {
      prefetch_map(&P.act_st); prefetch_map(&P.wq); prefetch_map(&P.k_ld); prefetch_map(&P.v_ld);
      prefetch_map(is_s ? &P.wo : &P.w2); prefetch_map(&P.x_ld); prefetch_map(&P.out_st);
    }
    __syncwarp();
    cluster_wait();
    asm volatile("setmaxnreg.dec.sync.aligned.u32 24;");
    if (warp == 8) {
      TSP(17);
      const unsigned ep1 = *(volatile unsigned*)&fl->epoch[blockIdx.x] + 1;
      Prod p{sb, 0, 0, 0, 0, 0, 0};
#define LDW(dst, m, bar, c0, c1, c2) tma_ld3_mc(dst, m, bar, c0, c1, c2)
      {
        const CUtensorMap* mb = spare ? &P.w1b4 : &P.w1b3;
        const uint32_t bytes = spare ? 49152 : 40960;
        const int nt = spare ? 8 : 2;
#pragma unroll 1
        for (int t = 0; t < nt; t++) {
          const int r = spare ? ((cl & 1) * 4 + (t >> 1)) * 2 + rank : rb;
          const int nb0 = spare ? (H_SPARE0 >> 6) + (t & 1) * 4 : j * 6 + t * 3;
          int k = 0;
          if (t == 0) {
#pragma unroll 1
            for (; k < 4; k++) {
              p.acquire(3);
              if (lane == 0) { mbar_expect_tx(p.full(), bytes); LDW(p.slot(1 + rank), mb, p.full(), 0, k * 64 + rank * 32, nb0); }
              p.advance(3);
            }
            TSP(14);
            wait_flag(&fl->ln[r][0], ep1 * 64);
            TSP(15);
            if (lane == 0)
              for (int i = 0; i < 4; i++) tma_ld2(sb + i * 3 * SLOT, &P.act_ld, sb + SM_BAR + B_FULL + i * 8, C_XN + i * 64, r * 128);
          } else if (spare && !(t & 1)) {
            wait_flag(&fl->ln[r][0], ep1 * 64);
          }
#pragma unroll 1
          for (; k < 16; k++) {
            p.acquire(3);
            if (lane == 0) {
              mbar_expect_tx(p.full(), bytes);
              LDW(p.slot(1 + rank), mb, p.full(), 0, k * 64 + rank * 32, nb0);
              tma_ld2(p.slot(0), &P.act_ld, p.full(), C_XN + k * 64, r * 128);
            }
            p.advance(3);
          }
        }
      }
      if (!spare) {
        const int kvrow = (j >> 1) * SK + KV0;
#pragma unroll 1
        for (int t = 0; t < 2; t++) {
          const int nb0 = (4 * j + 2 * t) * 2;
#pragma unroll 1
          for (int k = 0; k < 16; k++) {
            p.acquire(3);
            if (lane == 0) {
              mbar_expect_tx(p.full(), 49152);
              LDW(p.slot(1 + rank), &P.wq, p.full(), 0, k * 64 + rank * 32, nb0);
              tma_ld2(p.slot(0), &P.act_ld, p.full(), C_XN + k * 64, row0);
            }
            p.advance(3);
          }
#pragma unroll 1
          for (int i = 0; i < 16; i++) {
            const bool is_k = i == 0 || (i < 15 && (i & 1));
            const int ch = (is_k ? ((i + 1) >> 1) : (i == 15 ? 7 : (i >> 1) - 1)) & 3;
            p.acquire(2);
            if (lane == 0) {
              mbar_expect_tx(p.full(), 32768);
              if (is_k) tma_ld2_mc(p.slot(rank), &P.k_ld, p.full(), rank * 64, kvrow + ch * 128);
              else      tma_ld3_mc(p.slot(rank), &P.v_ld, p.full(), 0, kvrow + ch * 128 + rank * 64, 0);
            }
            p.advance(2);
            if (t == 1 && i == 8 && !is_s) wait_flag(&fl->h[rb][0], ep1 * 64);
          }
        }
        const int jn = j & 3;
        if (is_s) {
          unsigned ready = 0;
#pragma unroll 1
          for (int i = 0; i < 64; i++) {
            const int hi = i >> 1;
            const int head = 4 * ((hi & 15) >> 1) + (hi & 1) + ((hi >> 4) << 1);
            const int kc = head * 128 + (i & 1) * 64;
            p.acquire(3);
            if (lane == 0) { mbar_expect_tx(p.full(), 49152); LDW(p.slot(1 + rank), &P.wo, p.full(), 0, kc + rank * 32, jn * 4); }
            if (!((ready >> head) & 1)) {
              do { ready = __ballot_sync(~0u, (int)(ld_acquire(&fl->o[rb][lane]) - ep1 * 2) >= 0); } while (!((ready >> head) & 1));
              __syncwarp();
              fence_async_all();
            }
            if (lane == 0) tma_ld2(p.slot(0), &P.act_ld, p.full(), C_O + kc, row0);
            p.advance(3);
          }
          bool g_ready = (int)(ld_acquire(&fl->g[rb][jn]) - ep1 * 4) >= 0;
#pragma unroll 1
          for (int i = 0; i < 4; i++) {
            p.acquire(2);
            if (i == 2) { TSP(20); if (g_ready) fence_async_all(); else wait_flag(&fl->g[rb][jn], ep1 * 4); TSP(21); }
            if (lane == 0) {
              mbar_expect_tx(p.full(), 32768);
              const CUtensorMap* m = i < 2 ? &P.x_ld : &P.act_ld;
              const int c0 = (i < 2 ? 0 : C_G) + jn * 256 + (i & 1) * 128;
              tma_ld2(p.slot(0), m, p.full(), c0, row0);
              tma_ld2(p.slot(1), m, p.full(), c0 + 64, row0);
            }
            p.advance(2);
          }
        } else {
#pragma unroll 1
          for (int k = 0; k < 56; k++) {
            p.acquire(3);
            if (lane == 0) { mbar_expect_tx(p.full(), 49152); LDW(p.slot(1 + rank), &P.w2, p.full(), 0, k * 64 + rank * 32, jn * 4); }
            if (k == H_SPARE0 / 64) wait_flag(&fl->h[rb][16], ep1 * 8);
            if (lane == 0) tma_ld2(p.slot(0), &P.act_ld, p.full(), C_H + k * 64, row0);
            p.advance(3);
          }
        }
      }
      if (lane == 0) { *(volatile unsigned*)&fl->epoch[blockIdx.x] = ep1; mbar_arrive(sb + SM_BAR + B_DONE); }
    } else if (warp < 11) {
      const int wg = warp - 9;
      if (lane == 0) {
        const uint32_t stg = sb + SM_STG + wg * 16384;
        const int nev = spare ? 16 : is_s ? 8 : 10;
#pragma unroll 1
        for (int n = 0; n < nev; n++) {
          int col, row = row0, nbox = 2;
          unsigned* flag;
          if (spare) {
            const int r = ((cl & 1) * 4 + (n >> 2)) * 2 + rank;
            row = r * 128;
            col = C_H + H_SPARE0 + (n & 3) * 128;
            flag = &fl->h[r][16];
          } else if (n < 4) {
            col = C_H + j * H_REG + (n >> 1) * 192 + (n & 1) * 128;
            nbox = 2 - (n & 1);
            flag = &fl->h[rb][0];
          } else if (n < 8) {
            col = C_O + (4 * j + n - 4) * 128;
            flag = &fl->o[rb][4 * j + n - 4];
          } else {
            col = C_G + (j & 3) * 256 + (n - 8) * 128;
            flag = &fl->g[rb][j & 3];
          }
          mbar_wait(sb + SM_BAR + B_SFULL + wg * 8, n & 1);
          if (n == 9 && wg == 0) TSP(20);
          tma_st2(&P.act_st, stg, col, row + wg * 64);
          if (nbox == 2) tma_st2(&P.act_st, stg + 8192, col + 64, row + wg * 64);
          bulk_commit();
          bulk_wait_read0();
          mbar_arrive(sb + SM_BAR + B_SEMPTY + wg * 8);
          if (n == 9 && wg == 0) TSP(21);
          bulk_wait0();
          if (n == 9 && wg == 0) TSP(22);
          fence_async_all();
          red_release(flag, 1);
          if (n == 9 && wg == 0) TSP(23);
        }
        mbar_arrive(sb + SM_BAR + B_DONE);
      }
    } else {
      if (lane == 0) {
        const unsigned long long t0 = gtime();
        while (!mbar_try(sb + SM_BAR + B_DONE, 0)) {
          if (gtime() - t0 > 2000000000ull) __trap();
        }
      }
    }
    __syncwarp();
    cluster_arrive();
    cluster_wait();
  } else {
    const int wg = warp >> 2;
    TS(0);
    if (!spare) {
      const int r = row0 + j * 16 + warp * 2;
      uint32_t v[2][16];
#pragma unroll
      for (int a = 0; a < 2; a++)
#pragma unroll
        for (int i = 0; i < 4; i++)
          *(uint4*)&v[a][4 * i] = __ldg((const uint4*)(P.x + (size_t)(r + a) * DM + i * 256 + lane * 8));
      if (lane == 0) init_barriers(sb, warp);
      __syncwarp();
      cluster_arrive();
      float s[2], q[2];
#pragma unroll
      for (int a = 0; a < 2; a++) {
        float t0 = 0.f, t1 = 0.f;
#pragma unroll
        for (int i = 0; i < 16; i++) { t0 += bf_lo(v[a][i]); t1 += bf_hi(v[a][i]); }
        s[a] = t0 + t1;
      }
#pragma unroll
      for (int o = 16; o; o >>= 1) { s[0] += __shfl_xor_sync(~0u, s[0], o); s[1] += __shfl_xor_sync(~0u, s[1], o); }
#pragma unroll
      for (int a = 0; a < 2; a++) {
        s[a] *= 1.0f / DM;
        float t0 = 0.f, t1 = 0.f;
#pragma unroll
        for (int i = 0; i < 16; i++) {
          const float d0 = bf_lo(v[a][i]) - s[a], d1 = bf_hi(v[a][i]) - s[a];
          t0 = fmaf(d0, d0, t0); t1 = fmaf(d1, d1, t1);
        }
        q[a] = t0 + t1;
      }
#pragma unroll
      for (int o = 16; o; o >>= 1) { q[0] += __shfl_xor_sync(~0u, q[0], o); q[1] += __shfl_xor_sync(~0u, q[1], o); }
#pragma unroll
      for (int a = 0; a < 2; a++) {
        const uint32_t mb2 = pack_bf16(s[a], s[a]);
        const float inv = 1.0f / bf_round(sqrtf(bf_round(bf_round(q[a] * (1.0f / DM)) + 1e-5f)));
#pragma unroll
        for (int i = 0; i < 16; i++) {
          const __nv_bfloat162 d = __hsub2_rn(*(const __nv_bfloat162*)&v[a][i], *(const __nv_bfloat162*)&mb2);
          const uint32_t du = *(const uint32_t*)&d;
          v[a][i] = pack_bf16(bf_lo(du) * inv, bf_hi(du) * inv);
        }
#pragma unroll
        for (int i = 0; i < 4; i++)
          *(uint4*)(P.act + (size_t)(r + a) * ACT_W + C_XN + i * 256 + lane * 8) = *(const uint4*)&v[a][4 * i];
      }
      TS(11);
      fence_async_all();
      __syncwarp();
      if (lane == 0) red_release(&fl->ln[rb][0], 1);
      TS(13);
    } else {
      if (lane == 0) init_barriers(sb, warp);
      __syncwarp();
      cluster_arrive();
    }
    cluster_wait();
    asm volatile("setmaxnreg.inc.sync.aligned.u32 240;");
    Cons c;
    c.zero = blockIdx.y; c.sb = sb; c.g = 0; c.pos = 0; c.nstg = 0; c.wg = wg; c.lane = lane;
    c.rel = mapa(sb + SM_BAR + B_EMPTY, lane & 1);
    float acc[128];
    TS(1);
    if (spare) {
      uint32_t pend[32];
#pragma unroll
      for (int i = 0; i < 32; i++) pend[i] = 0;
#pragma unroll 1
      for (int t = 0; t < 8; t++) {
        gemm_loop_flush<256, 2>(acc, c, pend, t > 0);
        h_epilogue<2>(acc, c, pend);
      }
      c.stg_acquire();
      stage_boxes<2>(pend, 0, c);
      TS(6);
    } else {
      if (wg == 1) bar_arrive(1, 256);
      {
        uint32_t pend[16];
#pragma unroll
        for (int i = 0; i < 16; i++) pend[i] = 0;
#pragma unroll 1
        for (int t = 0; t < 2; t++) {
          gemm_loop_flush<192, 1>(acc, c, pend, t > 0);
          h_epilogue<1>(acc, c, pend);
          TS(2 + t);
        }
        gemm_loop_flush<256, 1>(acc, c, pend, true);
      }
#pragma unroll 1
      for (int t = 0; t < 2; t++) {
        TS(8 + t);
        attn_tile(acc, c, t);
        TS(4 + t);
        gemm_loop<256>(acc, c, t == 0 ? 16 : is_s ? 64 : 56);
      }
      TS(6);
      if (is_s) {
        uint32_t rowoff, xr;
        frag_addr(rowoff, xr);
        const uint32_t x0 = c.pos;
#pragma unroll
        for (int b = 0; b < 4; b++) {
          if ((b & 1) == 0) { c.wait_full(c.g + (b >> 1)); c.wait_full(c.g + 2 + (b >> 1)); }
          if (b == 0) TS(22);
          if (b == 2) TS(23);
          const uint32_t xs = sb + wrap12(x0 + b) * SLOT + wg * 8192;
          const uint32_t sx = xs + rowoff, sg = sb + wrap12(wrap12(x0 + 4) + b) * SLOT + wg * 8192 + rowoff;
          uint32_t xv[16], gv[16];
#pragma unroll
          for (int kb = 0; kb < 4; kb++) {
            ldsm4(sx + ((32 * kb) ^ xr), xv[4 * kb], xv[4 * kb + 1], xv[4 * kb + 2], xv[4 * kb + 3]);
            ldsm4(sg + ((32 * kb) ^ xr), gv[4 * kb], gv[4 * kb + 1], gv[4 * kb + 2], gv[4 * kb + 3]);
          }
#pragma unroll
          for (int i = 0; i < 16; i++) {
            const uint32_t s2 = pack_bf16(acc[32 * b + 2 * i], acc[32 * b + 2 * i + 1]);
            const __nv_bfloat162 pr = __hmul2_rn(*(const __nv_bfloat162*)&s2, *(const __nv_bfloat162*)&gv[i]);
            const __nv_bfloat162 o = __hadd2_rn(*(const __nv_bfloat162*)&xv[i], pr);
            xv[i] = *(const uint32_t*)&o;
          }
#pragma unroll
          for (int kb = 0; kb < 4; kb++) stsm4(sx + ((32 * kb) ^ xr), xv[4 * kb], xv[4 * kb + 1], xv[4 * kb + 2], xv[4 * kb + 3]);
          if (b & 1) {
            fence_async_smem();
            bar_sync(3 + wg, 128);
            if ((threadIdx.x & 127) == 0) {
              tma_st2(&P.out_st, sb + wrap12(x0 + b - 1) * SLOT + wg * 8192, (j & 3) * 256 + b * 64 - 64, row0 + wg * 64);
              tma_st2(&P.out_st, xs, (j & 3) * 256 + b * 64, row0 + wg * 64);
              bulk_commit();
            }
          }
        }
        TS(24);
        if ((threadIdx.x & 127) == 0) bulk_wait_read0();
      } else {
#pragma unroll
        for (int hh = 0; hh < 2; hh++) {
          uint32_t r[32];
#pragma unroll
          for (int i = 0; i < 32; i++) r[i] = silu2(acc[64 * hh + 2 * i], acc[64 * hh + 2 * i + 1]);
          c.stg_acquire();
          stage_boxes<2>(r, 0, c);
          if (hh == 0) TS(22);
        }
      }
    }
    TS(7);
    __syncwarp();
    if (lane == 0) mbar_arrive(sb + SM_BAR + B_DONE);
    cluster_arrive();
    cluster_wait();
  }
}

typedef CUresult (*EncodeFn)(CUtensorMap*, CUtensorMapDataType, cuuint32_t, void*, const cuuint64_t*, const cuuint64_t*,
                             const cuuint32_t*, const cuuint32_t*, CUtensorMapInterleave, CUtensorMapSwizzle,
                             CUtensorMapL2promotion, CUtensorMapFloatOOBfill);

void map2d(EncodeFn enc, CUtensorMap* m, const void* base, uint64_t cols, uint64_t rows, uint32_t box_rows) {
  cuuint64_t dims[2] = {cols, rows};
  cuuint64_t strides[1] = {cols * 2};
  cuuint32_t box[2] = {64, box_rows};
  cuuint32_t es[2] = {1, 1};
  enc(m, CU_TENSOR_MAP_DATA_TYPE_BFLOAT16, 2, (void*)base, dims, strides, box, es, CU_TENSOR_MAP_INTERLEAVE_NONE,
      CU_TENSOR_MAP_SWIZZLE_128B, CU_TENSOR_MAP_L2_PROMOTION_L2_256B, CU_TENSOR_MAP_FLOAT_OOB_FILL_NONE);
}
void map3d(EncodeFn enc, CUtensorMap* m, const void* base, uint64_t cols, uint64_t rows, uint32_t box_rows, uint32_t box_blks) {
  cuuint64_t dims[3] = {64, rows, cols / 64};
  cuuint64_t strides[2] = {cols * 2, 128};
  cuuint32_t box[3] = {64, box_rows, box_blks};
  cuuint32_t es[3] = {1, 1, 1};
  enc(m, CU_TENSOR_MAP_DATA_TYPE_BFLOAT16, 3, (void*)base, dims, strides, box, es, CU_TENSOR_MAP_INTERLEAVE_NONE,
      CU_TENSOR_MAP_SWIZZLE_128B, CU_TENSOR_MAP_L2_PROMOTION_L2_256B, CU_TENSOR_MAP_FLOAT_OOB_FILL_NONE);
}

}

extern "C" void kernel_launch(void* const* d_in, const int* in_sizes, int n_in, void* d_out, int out_size) {
  (void)in_sizes; (void)n_in; (void)out_size;
  static EncodeFn enc = nullptr;
  static void* act = nullptr;
  static void* flags = nullptr;
  if (!enc) {
    void* fn = nullptr;
    cudaDriverEntryPointQueryResult qr;
    cudaGetDriverEntryPoint("cuTensorMapEncodeTiled", &fn, cudaEnableDefault, &qr);
    enc = (EncodeFn)fn;
    cudaGetSymbolAddress(&act, g_act);
    cudaGetSymbolAddress(&flags, g_flags);
    cudaFuncSetAttribute(fused_kernel, cudaFuncAttributeMaxDynamicSharedMemorySize, SMEM_BYTES);
  }
  Params P;
  map2d(enc, &P.act_ld, act, ACT_W, SEQ, 128);
  map2d(enc, &P.act_st, act, ACT_W, SEQ, 64);
  map2d(enc, &P.x_ld, d_in[0], DM, SEQ, 128);
  map2d(enc, &P.out_st, d_out, DM, SEQ, 64);
  map2d(enc, &P.k_ld, d_in[1], 128, 4 * SK, 128);
  map3d(enc, &P.v_ld, d_in[2], 128, 4 * SK, 64, 2);
  map3d(enc, &P.wq, d_in[3], NQ, DM, 32, 4);
  map3d(enc, &P.w1b4, d_in[6], DFF, DM, 32, 4);
  map3d(enc, &P.w1b3, d_in[6], DFF, DM, 32, 3);
  map3d(enc, &P.wo, d_in[4], DM, NQ, 32, 4);
  map3d(enc, &P.w2, d_in[7], DM, DFF, 32, 4);
  P.x = (const __nv_bfloat16*)d_in[0];
  P.act = (__nv_bfloat16*)act;
  P.flags = (Flags*)flags;
  fused_kernel<<<NCLUSTER * 2, 384, SMEM_BYTES>>>(P);
}
```

```cpp
#include <cuda_runtime.h>
#include <cuda_bf16.h>
#include <cuda.h>
#include <stdint.h>

namespace {

constexpr int SEQ    = 2048;
constexpr int DM     = 1024;
constexpr int NQ     = 4096;
constexpr int DFF    = 3584;
constexpr int SK     = 2048;
constexpr int WIN    = 512;
constexpr int KV0    = SK - WIN;
constexpr int C_XN = 0, C_O = 1024, C_H = 5120, C_G = 8704, ACT_W = 9728;

constexpr int H_REG = 384, H_SPARE0 = 8 * H_REG;
static_assert(H_SPARE0 + 512 == DFF, "H split");

constexpr int NSLOT = 12, SLOT = 16384, NBAR = 8;
constexpr int SM_STG = NSLOT * SLOT;
constexpr int SM_BAR = SM_STG + 2 * 16384;
constexpr int SMEM_BYTES = SM_BAR + 256 + 1024;
constexpr int B_FULL = 0, B_EMPTY = 64, B_SFULL = 128, B_SEMPTY = 144, B_DONE = 160;

constexpr int NCLUSTER = 66;

struct Flags {
  unsigned ln[16][32];
  unsigned h[16][32];
  unsigned o[16][32];
  unsigned g[16][32];
  unsigned epoch[160];
};
__device__ __nv_bfloat16 g_act[(size_t)SEQ * ACT_W];
__device__ Flags g_flags;

struct Params {
  CUtensorMap act_ld, act_st, x_ld, out_st, k_ld, v_ld, wq, w1b4, w1b3, wo, w2;
  const __nv_bfloat16* x;
  __nv_bfloat16* act;
  Flags* flags;
};

__device__ __forceinline__ uint32_t smem_u32(const void* p) { return (uint32_t)__cvta_generic_to_shared(p); }
__device__ __forceinline__ void mbar_init(uint32_t bar, uint32_t cnt) {
  asm volatile("mbarrier.init.shared::cta.b64 [%0], %1;" ::"r"(bar), "r"(cnt) : "memory");
}
__device__ __forceinline__ bool mbar_try(uint32_t bar, uint32_t parity) {
  uint32_t ok;
  asm volatile("{\n.reg .pred p;\nmbarrier.try_wait.parity.shared::cta.b64 p, [%1], %2;\nselp.u32 %0, 1, 0, p;\n}\n"
               : "=r"(ok) : "r"(bar), "r"(parity) : "memory");
  return ok;
}
__device__ __forceinline__ void mbar_wait(uint32_t bar, uint32_t parity) {
  asm volatile("{\n.reg .pred p;\nWAIT_%=:\nmbarrier.try_wait.parity.shared::cta.b64 p, [%0], %1;\n@p bra DONE_%=;\nbra WAIT_%=;\nDONE_%=:\n}\n"
               ::"r"(bar), "r"(parity) : "memory");
}
__device__ __forceinline__ void mbar_arrive(uint32_t bar) {
  asm volatile("mbarrier.arrive.shared::cta.b64 _, [%0];" ::"r"(bar) : "memory");
}
__device__ __forceinline__ void mbar_arrive_cluster(uint32_t cluster_addr) {
  asm volatile("mbarrier.arrive.shared::cluster.b64 _, [%0];" ::"r"(cluster_addr) : "memory");
}
__device__ __forceinline__ void mbar_expect_tx(uint32_t bar, uint32_t bytes) {
  asm volatile("mbarrier.arrive.expect_tx.shared::cta.b64 _, [%0], %1;" ::"r"(bar), "r"(bytes) : "memory");
}
__device__ __forceinline__ uint32_t mapa(uint32_t addr, uint32_t rank) {
  uint32_t r;
  asm("mapa.shared::cluster.u32 %0, %1, %2;" : "=r"(r) : "r"(addr), "r"(rank));
  return r;
}
__device__ __forceinline__ void cluster_arrive() { asm volatile("barrier.cluster.arrive.relaxed.aligned;" ::: "memory"); }
__device__ __forceinline__ void cluster_wait() { asm volatile("barrier.cluster.wait.acquire.aligned;" ::: "memory"); }
__device__ __forceinline__ void bar_sync(int id, int n) { asm volatile("bar.sync %0, %1;" ::"r"(id), "r"(n) : "memory"); }
__device__ __forceinline__ void bar_arrive(int id, int n) { asm volatile("bar.arrive %0, %1;" ::"r"(id), "r"(n) : "memory"); }
__device__ __forceinline__ void fence_async_smem() { asm volatile("fence.proxy.async.shared::cta;" ::: "memory"); }
__device__ __forceinline__ void fence_async_all() { asm volatile("fence.proxy.async.global;" ::: "memory"); }

__device__ __forceinline__ void tma_ld2(uint32_t dst, const CUtensorMap* m, uint32_t bar, int c0, int c1) {
  asm volatile("cp.async.bulk.tensor.2d.shared::cluster.global.mbarrier::complete_tx::bytes [%0], [%1, {%3, %4}], [%2];"
               ::"r"(dst), "l"(m), "r"(bar), "r"(c0), "r"(c1) : "memory");
}
__device__ __forceinline__ void tma_ld2_mc(uint32_t dst, const CUtensorMap* m, uint32_t bar, int c0, int c1) {
  asm volatile("cp.async.bulk.tensor.2d.shared::cluster.global.mbarrier::complete_tx::bytes.multicast::cluster [%0], [%1, {%3, %4}], [%2], %5;"
               ::"r"(dst), "l"(m), "r"(bar), "r"(c0), "r"(c1), "h"((uint16_t)3) : "memory");
}
__device__ __forceinline__ void tma_ld3_mc(uint32_t dst, const CUtensorMap* m, uint32_t bar, int c0, int c1, int c2) {
  asm volatile("cp.async.bulk.tensor.3d.shared::cluster.global.mbarrier::complete_tx::bytes.multicast::cluster [%0], [%1, {%3, %4, %5}], [%2], %6;"
               ::"r"(dst), "l"(m), "r"(bar), "r"(c0), "r"(c1), "r"(c2), "h"((uint16_t)3) : "memory");
}
__device__ __forceinline__ void tma_ld3_mc_hint(uint32_t dst, const CUtensorMap* m, uint32_t bar, int c0, int c1, int c2, uint64_t pol) {
  asm volatile("cp.async.bulk.tensor.3d.shared::cluster.global.mbarrier::complete_tx::bytes.multicast::cluster.L2::cache_hint [%0], [%1, {%3, %4, %5}], [%2], %6, %7;"
               ::"r"(dst), "l"(m), "r"(bar), "r"(c0), "r"(c1), "r"(c2), "h"((uint16_t)3), "l"(pol) : "memory");
}
__device__ __forceinline__ void tma_ld2_hint(uint32_t dst, const CUtensorMap* m, uint32_t bar, int c0, int c1, uint64_t pol) {
  asm volatile("cp.async.bulk.tensor.2d.shared::cluster.global.mbarrier::complete_tx::bytes.L2::cache_hint [%0], [%1, {%3, %4}], [%2], %5;"
               ::"r"(dst), "l"(m), "r"(bar), "r"(c0), "r"(c1), "l"(pol) : "memory");
}
__device__ __forceinline__ void tma_st2_hint(const CUtensorMap* m, uint32_t src, int c0, int c1, uint64_t pol) {
  asm volatile("cp.async.bulk.tensor.2d.global.shared::cta.bulk_group.L2::cache_hint [%0, {%2, %3}], [%1], %4;"
               ::"l"(m), "r"(src), "r"(c0), "r"(c1), "l"(pol) : "memory");
}
#define POL_FIRST 0x12F0000000000000ull
__device__ __forceinline__ uint64_t policy_evict_first() {
  uint64_t p;
  asm volatile("createpolicy.fractional.L2::evict_first.b64 %0, 1.0;" : "=l"(p));
  return p;
}
__device__ __forceinline__ void tma_st2(const CUtensorMap* m, uint32_t src, int c0, int c1) {
  asm volatile("cp.async.bulk.tensor.2d.global.shared::cta.bulk_group [%0, {%2, %3}], [%1];"
               ::"l"(m), "r"(src), "r"(c0), "r"(c1) : "memory");
}
__device__ __forceinline__ void tma_pf3(const CUtensorMap* m, int c0, int c1, int c2) {
  asm volatile("cp.async.bulk.prefetch.tensor.3d.L2.global [%0, {%1, %2, %3}];" ::"l"(m), "r"(c0), "r"(c1), "r"(c2) : "memory");
}
__device__ __forceinline__ void bulk_commit() { asm volatile("cp.async.bulk.commit_group;" ::: "memory"); }
__device__ __forceinline__ void bulk_wait_read0() { asm volatile("cp.async.bulk.wait_group.read 0;" ::: "memory"); }
__device__ __forceinline__ void bulk_wait0() { asm volatile("cp.async.bulk.wait_group 0;" ::: "memory"); }
__device__ __forceinline__ void prefetch_map(const CUtensorMap* m) {
  asm volatile("prefetch.tensormap [%0];" ::"l"(m) : "memory");
}
__device__ __forceinline__ unsigned ld_acquire(const unsigned* p) {
  unsigned v;
  asm volatile("ld.acquire.gpu.global.u32 %0, [%1];" : "=r"(v) : "l"(p) : "memory");
  return v;
}
__device__ __forceinline__ void red_release(unsigned* p, unsigned v) {
  asm volatile("red.release.gpu.global.add.u32 [%0], %1;" ::"l"(p), "r"(v) : "memory");
}
__device__ __forceinline__ void wg_fence() { asm volatile("wgmma.fence.sync.aligned;" ::: "memory"); }
__device__ __forceinline__ void wg_commit() { asm volatile("wgmma.commit_group.sync.aligned;" ::: "memory"); }
template <int N> __device__ __forceinline__ void wg_wait() { asm volatile("wgmma.wait_group.sync.aligned %0;" ::"n"(N) : "memory"); }
template <int N> __device__ __forceinline__ void fence_regs(float (&d)[N]) {
#pragma unroll
  for (int i = 0; i < N; i++) asm volatile("" : "+f"(d[i])::"memory");
}
template <int N> __device__ __forceinline__ void fence_regs(uint32_t (&d)[N]) {
#pragma unroll
  for (int i = 0; i < N; i++) asm volatile("" : "+r"(d[i])::"memory");
}
__device__ __forceinline__ uint64_t mkdesc(uint32_t addr, uint32_t lbo, uint32_t sbo) {
  return (uint64_t)((addr & 0x3FFFF) >> 4) | ((uint64_t)(lbo >> 4) << 16) | ((uint64_t)(sbo >> 4) << 32) | (1ull << 62);
}
__device__ __forceinline__ uint32_t pack_bf16(float lo, float hi) {
  uint32_t r;
  asm("cvt.rn.bf16x2.f32 %0, %1, %2;" : "=r"(r) : "f"(hi), "f"(lo));
  return r;
}
__device__ __forceinline__ uint32_t pack_bf16_relu(float lo, float hi) {
  uint32_t r;
  asm("cvt.rn.relu.bf16x2.f32 %0, %1, %2;" : "=r"(r) : "f"(hi), "f"(lo));
  return r;
}
__device__ __forceinline__ float bf_lo(uint32_t v) { return __uint_as_float(v << 16); }
__device__ __forceinline__ float bf_hi(uint32_t v) { return __uint_as_float(v & 0xFFFF0000u); }
__device__ __forceinline__ float bf_round(float v) { return __bfloat162float(__float2bfloat16_rn(v)); }
__device__ __forceinline__ float ex2(float x) {
  float r;
  asm("ex2.approx.ftz.f32 %0, %1;" : "=f"(r) : "f"(x));
  return r;
}
__device__ __forceinline__ float rcp(float x) {
  float r;
  asm("rcp.approx.ftz.f32 %0, %1;" : "=f"(r) : "f"(x));
  return r;
}
__device__ __forceinline__ uint32_t tid_x() {
  uint32_t t;
  asm volatile("mov.u32 %0, %%tid.x;" : "=r"(t));
  return t;
}
__device__ __forceinline__ void stsm4(uint32_t addr, uint32_t r0, uint32_t r1, uint32_t r2, uint32_t r3) {
  asm volatile("stmatrix.sync.aligned.m8n8.x4.shared.b16 [%0], {%1, %2, %3, %4};" ::"r"(addr), "r"(r0), "r"(r1), "r"(r2), "r"(r3) : "memory");
}
__device__ __forceinline__ void ldsm4(uint32_t addr, uint32_t& r0, uint32_t& r1, uint32_t& r2, uint32_t& r3) {
  asm volatile("ldmatrix.sync.aligned.m8n8.x4.shared.b16 {%0, %1, %2, %3}, [%4];" : "=r"(r0), "=r"(r1), "=r"(r2), "=r"(r3) : "r"(addr) : "memory");
}
__device__ __forceinline__ void sts128(uint32_t addr, uint32_t r0, uint32_t r1, uint32_t r2, uint32_t r3) {
  asm volatile("st.shared.v4.b32 [%0], {%1, %2, %3, %4};" ::"r"(addr), "r"(r0), "r"(r1), "r"(r2), "r"(r3) : "memory");
}
__device__ __forceinline__ void lds128(uint32_t addr, uint32_t& r0, uint32_t& r1, uint32_t& r2, uint32_t& r3) {
  asm volatile("ld.shared.v4.b32 {%0, %1, %2, %3}, [%4];" : "=r"(r0), "=r"(r1), "=r"(r2), "=r"(r3) : "r"(addr) : "memory");
}
__device__ __forceinline__ unsigned long long gtime() {
  unsigned long long t;
  asm volatile("mov.u64 %0, %globaltimer;" : "=l"(t));
  return t;
}

__device__ __forceinline__ void wgmma_ss_n256_tb(float (&d)[128], uint64_t da, uint64_t db, uint32_t sc) {
  asm volatile("{\n.reg .pred p;\nsetp.ne.b32 p, %130, 0;\n"
    "wgmma.mma_async.sync.aligned.m64n256k16.f32.bf16.bf16 "
    "{%0, %1, %2, %3, %4, %5, %6, %7, %8, %9, %10, %11, %12, %13, %14, %15, %16, %17, %18, %19, %20, %21, %22, %23, %24, %25, %26, %27, %28, %29, %30, %31, %32, %33, %34, %35, %36, %37, %38, %39, %40, %41, %42, %43, %44, %45, %46, %47, %48, %49, %50, %51, %52, %53, %54, %55, %56, %57, %58, %59, %60, %61, %62, %63, %64, %65, %66, %67, %68, %69, %70, %71, %72, %73, %74, %75, %76, %77, %78, %79, %80, %81, %82, %83, %84, %85, %86, %87, %88, %89, %90, %91, %92, %93, %94, %95, %96, %97, %98, %99, %100, %101, %102, %103, %104, %105, %106, %107, %108, %109, %110, %111, %112, %113, %114, %115, %116, %117, %118, %119, %120, %121, %122, %123, %124, %125, %126, %127}, %128, %129, p, 1, 1, 0, 1;\n}\n"
    : "+f"(d[0]), "+f"(d[1]), "+f"(d[2]), "+f"(d[3]), "+f"(d[4]), "+f"(d[5]), "+f"(d[6]), "+f"(d[7]), "+f"(d[8]), "+f"(d[9]), "+f"(d[10]), "+f"(d[11]), "+f"(d[12]), "+f"(d[13]), "+f"(d[14]), "+f"(d[15]), "+f"(d[16]), "+f"(d[17]), "+f"(d[18]), "+f"(d[19]), "+f"(d[20]), "+f"(d[21]), "+f"(d[22]), "+f"(d[23]), "+f"(d[24]), "+f"(d[25]), "+f"(d[26]), "+f"(d[27]), "+f"(d[28]), "+f"(d[29]), "+f"(d[30]), "+f"(d[31]), "+f"(d[32]), "+f"(d[33]), "+f"(d[34]), "+f"(d[35]), "+f"(d[36]), "+f"(d[37]), "+f"(d[38]), "+f"(d[39]), "+f"(d[40]), "+f"(d[41]), "+f"(d[42]), "+f"(d[43]), "+f"(d[44]), "+f"(d[45]), "+f"(d[46]), "+f"(d[47]), "+f"(d[48]), "+f"(d[49]), "+f"(d[50]), "+f"(d[51]), "+f"(d[52]), "+f"(d[53]), "+f"(d[54]), "+f"(d[55]), "+f"(d[56]), "+f"(d[57]), "+f"(d[58]), "+f"(d[59]), "+f"(d[60]), "+f"(d[61]), "+f"(d[62]), "+f"(d[63]), "+f"(d[64]), "+f"(d[65]), "+f"(d[66]), "+f"(d[67]), "+f"(d[68]), "+f"(d[69]), "+f"(d[70]), "+f"(d[71]), "+f"(d[72]), "+f"(d[73]), "+f"(d[74]), "+f"(d[75]), "+f"(d[76]), "+f"(d[77]), "+f"(d[78]), "+f"(d[79]), "+f"(d[80]), "+f"(d[81]), "+f"(d[82]), "+f"(d[83]), "+f"(d[84]), "+f"(d[85]), "+f"(d[86]), "+f"(d[87]), "+f"(d[88]), "+f"(d[89]), "+f"(d[90]), "+f"(d[91]), "+f"(d[92]), "+f"(d[93]), "+f"(d[94]), "+f"(d[95]), "+f"(d[96]), "+f"(d[97]), "+f"(d[98]), "+f"(d[99]), "+f"(d[100]), "+f"(d[101]), "+f"(d[102]), "+f"(d[103]), "+f"(d[104]), "+f"(d[105]), "+f"(d[106]), "+f"(d[107]), "+f"(d[108]), "+f"(d[109]), "+f"(d[110]), "+f"(d[111]), "+f"(d[112]), "+f"(d[113]), "+f"(d[114]), "+f"(d[115]), "+f"(d[116]), "+f"(d[117]), "+f"(d[118]), "+f"(d[119]), "+f"(d[120]), "+f"(d[121]), "+f"(d[122]), "+f"(d[123]), "+f"(d[124]), "+f"(d[125]), "+f"(d[126]), "+f"(d[127])
    : "l"(da), "l"(db), "r"(sc));
}
__device__ __forceinline__ void wgmma_ss_n192_tb(float (&d)[128], uint64_t da, uint64_t db, uint32_t sc) {
  asm volatile("{\n.reg .pred p;\nsetp.ne.b32 p, %98, 0;\n"
    "wgmma.mma_async.sync.aligned.m64n192k16.f32.bf16.bf16 "
    "{%0, %1, %2, %3, %4, %5, %6, %7, %8, %9, %10, %11, %12, %13, %14, %15, %16, %17, %18, %19, %20, %21, %22, %23, %24, %25, %26, %27, %28, %29, %30, %31, %32, %33, %34, %35, %36, %37, %38, %39, %40, %41, %42, %43, %44, %45, %46, %47, %48, %49, %50, %51, %52, %53, %54, %55, %56, %57, %58, %59, %60, %61, %62, %63, %64, %65, %66, %67, %68, %69, %70, %71, %72, %73, %74, %75, %76, %77, %78, %79, %80, %81, %82, %83, %84, %85, %86, %87, %88, %89, %90, %91, %92, %93, %94, %95}, %96, %97, p, 1, 1, 0, 1;\n}\n"
    : "+f"(d[0]), "+f"(d[1]), "+f"(d[2]), "+f"(d[3]), "+f"(d[4]), "+f"(d[5]), "+f"(d[6]), "+f"(d[7]), "+f"(d[8]), "+f"(d[9]), "+f"(d[10]), "+f"(d[11]), "+f"(d[12]), "+f"(d[13]), "+f"(d[14]), "+f"(d[15]), "+f"(d[16]), "+f"(d[17]), "+f"(d[18]), "+f"(d[19]), "+f"(d[20]), "+f"(d[21]), "+f"(d[22]), "+f"(d[23]), "+f"(d[24]), "+f"(d[25]), "+f"(d[26]), "+f"(d[27]), "+f"(d[28]), "+f"(d[29]), "+f"(d[30]), "+f"(d[31]), "+f"(d[32]), "+f"(d[33]), "+f"(d[34]), "+f"(d[35]), "+f"(d[36]), "+f"(d[37]), "+f"(d[38]), "+f"(d[39]), "+f"(d[40]), "+f"(d[41]), "+f"(d[42]), "+f"(d[43]), "+f"(d[44]), "+f"(d[45]), "+f"(d[46]), "+f"(d[47]), "+f"(d[48]), "+f"(d[49]), "+f"(d[50]), "+f"(d[51]), "+f"(d[52]), "+f"(d[53]), "+f"(d[54]), "+f"(d[55]), "+f"(d[56]), "+f"(d[57]), "+f"(d[58]), "+f"(d[59]), "+f"(d[60]), "+f"(d[61]), "+f"(d[62]), "+f"(d[63]), "+f"(d[64]), "+f"(d[65]), "+f"(d[66]), "+f"(d[67]), "+f"(d[68]), "+f"(d[69]), "+f"(d[70]), "+f"(d[71]), "+f"(d[72]), "+f"(d[73]), "+f"(d[74]), "+f"(d[75]), "+f"(d[76]), "+f"(d[77]), "+f"(d[78]), "+f"(d[79]), "+f"(d[80]), "+f"(d[81]), "+f"(d[82]), "+f"(d[83]), "+f"(d[84]), "+f"(d[85]), "+f"(d[86]), "+f"(d[87]), "+f"(d[88]), "+f"(d[89]), "+f"(d[90]), "+f"(d[91]), "+f"(d[92]), "+f"(d[93]), "+f"(d[94]), "+f"(d[95])
    : "l"(da), "l"(db), "r"(sc));
}
__device__ __forceinline__ void wgmma_rs_n128(float (&d)[64], uint32_t a0, uint32_t a1, uint32_t a2, uint32_t a3, uint64_t db, uint32_t sc) {
  asm volatile("{\n.reg .pred p;\nsetp.ne.b32 p, %69, 0;\n"
    "wgmma.mma_async.sync.aligned.m64n128k16.f32.bf16.bf16 "
    "{%0, %1, %2, %3, %4, %5, %6, %7, %8, %9, %10, %11, %12, %13, %14, %15, %16, %17, %18, %19, %20, %21, %22, %23, %24, %25, %26, %27, %28, %29, %30, %31, %32, %33, %34, %35, %36, %37, %38, %39, %40, %41, %42, %43, %44, %45, %46, %47, %48, %49, %50, %51, %52, %53, %54, %55, %56, %57, %58, %59, %60, %61, %62, %63}, {%64, %65, %66, %67}, %68, p, 1, 1, 0;\n}\n"
    : "+f"(d[0]), "+f"(d[1]), "+f"(d[2]), "+f"(d[3]), "+f"(d[4]), "+f"(d[5]), "+f"(d[6]), "+f"(d[7]), "+f"(d[8]), "+f"(d[9]), "+f"(d[10]), "+f"(d[11]), "+f"(d[12]), "+f"(d[13]), "+f"(d[14]), "+f"(d[15]), "+f"(d[16]), "+f"(d[17]), "+f"(d[18]), "+f"(d[19]), "+f"(d[20]), "+f"(d[21]), "+f"(d[22]), "+f"(d[23]), "+f"(d[24]), "+f"(d[25]), "+f"(d[26]), "+f"(d[27]), "+f"(d[28]), "+f"(d[29]), "+f"(d[30]), "+f"(d[31]), "+f"(d[32]), "+f"(d[33]), "+f"(d[34]), "+f"(d[35]), "+f"(d[36]), "+f"(d[37]), "+f"(d[38]), "+f"(d[39]), "+f"(d[40]), "+f"(d[41]), "+f"(d[42]), "+f"(d[43]), "+f"(d[44]), "+f"(d[45]), "+f"(d[46]), "+f"(d[47]), "+f"(d[48]), "+f"(d[49]), "+f"(d[50]), "+f"(d[51]), "+f"(d[52]), "+f"(d[53]), "+f"(d[54]), "+f"(d[55]), "+f"(d[56]), "+f"(d[57]), "+f"(d[58]), "+f"(d[59]), "+f"(d[60]), "+f"(d[61]), "+f"(d[62]), "+f"(d[63])
    : "r"(a0), "r"(a1), "r"(a2), "r"(a3), "l"(db), "r"(sc));
}
__device__ __forceinline__ void wgmma_rs_n128_tb(float (&d)[64], uint32_t a0, uint32_t a1, uint32_t a2, uint32_t a3, uint64_t db, uint32_t sc) {
  asm volatile("{\n.reg .pred p;\nsetp.ne.b32 p, %69, 0;\n"
    "wgmma.mma_async.sync.aligned.m64n128k16.f32.bf16.bf16 "
    "{%0, %1, %2, %3, %4, %5, %6, %7, %8, %9, %10, %11, %12, %13, %14, %15, %16, %17, %18, %19, %20, %21, %22, %23, %24, %25, %26, %27, %28, %29, %30, %31, %32, %33, %34, %35, %36, %37, %38, %39, %40, %41, %42, %43, %44, %45, %46, %47, %48, %49, %50, %51, %52, %53, %54, %55, %56, %57, %58, %59, %60, %61, %62, %63}, {%64, %65, %66, %67}, %68, p, 1, 1, 1;\n}\n"
    : "+f"(d[0]), "+f"(d[1]), "+f"(d[2]), "+f"(d[3]), "+f"(d[4]), "+f"(d[5]), "+f"(d[6]), "+f"(d[7]), "+f"(d[8]), "+f"(d[9]), "+f"(d[10]), "+f"(d[11]), "+f"(d[12]), "+f"(d[13]), "+f"(d[14]), "+f"(d[15]), "+f"(d[16]), "+f"(d[17]), "+f"(d[18]), "+f"(d[19]), "+f"(d[20]), "+f"(d[21]), "+f"(d[22]), "+f"(d[23]), "+f"(d[24]), "+f"(d[25]), "+f"(d[26]), "+f"(d[27]), "+f"(d[28]), "+f"(d[29]), "+f"(d[30]), "+f"(d[31]), "+f"(d[32]), "+f"(d[33]), "+f"(d[34]), "+f"(d[35]), "+f"(d[36]), "+f"(d[37]), "+f"(d[38]), "+f"(d[39]), "+f"(d[40]), "+f"(d[41]), "+f"(d[42]), "+f"(d[43]), "+f"(d[44]), "+f"(d[45]), "+f"(d[46]), "+f"(d[47]), "+f"(d[48]), "+f"(d[49]), "+f"(d[50]), "+f"(d[51]), "+f"(d[52]), "+f"(d[53]), "+f"(d[54]), "+f"(d[55]), "+f"(d[56]), "+f"(d[57]), "+f"(d[58]), "+f"(d[59]), "+f"(d[60]), "+f"(d[61]), "+f"(d[62]), "+f"(d[63])
    : "r"(a0), "r"(a1), "r"(a2), "r"(a3), "l"(db), "r"(sc));
}

#define TS(i) do {} while (0)
#define TR(j, i) do {} while (0)
#define TSS(i, c) do {} while (0)

__device__ __forceinline__ uint32_t wrap12(uint32_t p) { return p >= NSLOT ? p - NSLOT : p; }

struct Cons {
  uint32_t sb;
  uint32_t g, pos;
  uint32_t rel;
  uint32_t nstg;
  uint32_t zero;
  int wg, lane;
  __device__ __forceinline__ void wait_full(uint32_t gg) const { mbar_wait(sb + SM_BAR + B_FULL + (gg & 7) * 8, (gg >> 3) & 1); }
  __device__ __forceinline__ void release(uint32_t gg) const { if (lane < 2) mbar_arrive_cluster(rel + (gg & 7) * 8); }
  __device__ __forceinline__ void stg_acquire() { mbar_wait(sb + SM_BAR + B_SEMPTY + wg * 8, (nstg & 1) ^ 1); nstg++; }
  __device__ __forceinline__ void stg_publish() const {
    fence_async_smem();
    __syncwarp();
    if (lane == 0) mbar_arrive(sb + SM_BAR + B_SFULL + wg * 8);
  }
};

__device__ __forceinline__ void frag_addr(uint32_t& rowoff, uint32_t& xr) {
  const uint32_t t = tid_x();
  rowoff = ((t >> 5) & 3) * 2048 + (t & 15) * 128;
  xr = (((t >> 4) & 1) ^ (t & 7)) << 4;
}
template <int NB, int NR>
__device__ __forceinline__ void stage_boxes(const uint32_t (&r)[NR], int r0, const Cons& c) {
  uint32_t rowoff, xr;
  frag_addr(rowoff, xr);
  const uint32_t stg = c.sb + SM_STG + c.wg * 16384 + rowoff;
#pragma unroll
  for (int b = 0; b < NB; b++)
#pragma unroll
    for (int kb = 0; kb < 4; kb++)
      stsm4(stg + b * 8192 + ((32 * kb) ^ xr), r[r0 + b * 16 + kb * 4], r[r0 + b * 16 + kb * 4 + 1], r[r0 + b * 16 + kb * 4 + 2], r[r0 + b * 16 + kb * 4 + 3]);
  c.stg_publish();
}

template <int N, bool FIRST>
__device__ __forceinline__ void gemm_step(float (&acc)[128], Cons& c) {
  const uint32_t p1 = wrap12(c.pos + 1), p2 = wrap12(c.pos + 2);
  const uint64_t da = mkdesc(c.sb + c.wg * 8192 + c.pos * SLOT, 16, 1024);
  const uint64_t b0 = mkdesc(c.sb + p1 * SLOT, 4096, 1024);
  const uint64_t b1 = mkdesc(c.sb + p2 * SLOT, 4096, 1024);
  c.wait_full(c.g);
  wg_fence();
  if (N == 256) {
    wgmma_ss_n256_tb(acc, da, b0, FIRST ? 0 : 1);
    wgmma_ss_n256_tb(acc, da + 2, b0 + 128, 1);
    wgmma_ss_n256_tb(acc, da + 4, b1, 1);
    wgmma_ss_n256_tb(acc, da + 6, b1 + 128, 1);
  } else {
    wgmma_ss_n192_tb(acc, da, b0, FIRST ? 0 : 1);
    wgmma_ss_n192_tb(acc, da + 2, b0 + 128, 1);
    wgmma_ss_n192_tb(acc, da + 4, b1, 1);
    wgmma_ss_n192_tb(acc, da + 6, b1 + 128, 1);
  }
  wg_commit();
  if (!FIRST) {
    wg_wait<1>();
    c.release(c.g - 1);
  }
  c.g++;
  c.pos = wrap12(p2 + 1);
}

template <int N>
__device__ __forceinline__ void gemm_loop(float (&acc)[128], Cons& c, int nk) {
  gemm_step<N, true>(acc, c);
#pragma unroll 1
  for (int k = 1; k < nk; k++) gemm_step<N, false>(acc, c);
  wg_wait<0>();
  c.release(c.g - 1);
  fence_regs(acc);
}
template <int N, int NB>
__device__ __forceinline__ void gemm_loop_flush(float (&acc)[128], Cons& c, const uint32_t (&pend)[NB * 16], bool flush) {
  gemm_step<N, true>(acc, c);
#pragma unroll 1
  for (int k = 1; k < 16; k++) {
    gemm_step<N, false>(acc, c);
    if (k == 3 && flush) {
      c.stg_acquire();
      stage_boxes<NB>(pend, 0, c);
    }
  }
  wg_wait<0>();
  c.release(c.g - 1);
  fence_regs(acc);
}
template <int NB>
__device__ __forceinline__ void h_epilogue(const float (&acc)[128], Cons& c, uint32_t (&pend)[NB * 16]) {
  uint32_t r[32];
#pragma unroll
  for (int i = 0; i < 32; i++) r[i] = pack_bf16_relu(acc[2 * i], acc[2 * i + 1]);
  c.stg_acquire();
  stage_boxes<2>(r, 0, c);
#pragma unroll
  for (int i = 0; i < NB * 16; i++) pend[i] = pack_bf16_relu(acc[64 + 2 * i], acc[65 + 2 * i]);
}

__device__ __forceinline__ uint32_t silu2(float lo, float hi) {
  const uint32_t f2 = pack_bf16(lo, hi);
  const float a = bf_lo(f2), b = bf_hi(f2);
  const float ta = ex2(-1.4426950408889634f * fabsf(a)), tb = ex2(-1.4426950408889634f * fabsf(b));
  const float da = 1.0f + ta, db = 1.0f + tb;
  const float r = rcp(da * db);
  return pack_bf16((a >= 0.f ? a : a * ta) * (r * db), (b >= 0.f ? b : b * tb) * (r * da));
}

constexpr float SM_C = 0.08838834764831845f * 1.4426950408889634f;

#define ONCE(c) _Pragma("unroll 1") for (uint32_t once_ = 0; once_ <= (c).zero; once_++)
__device__ __forceinline__ void row_max2(const float (&S)[64], float& n0, float& n1) {
  float x[4], y[4];
#pragma unroll
  for (int i = 0; i < 4; i++) { x[i] = fmaxf(S[4 * i], S[4 * i + 1]); y[i] = fmaxf(S[4 * i + 2], S[4 * i + 3]); }
#pragma unroll
  for (int i = 4; i < 16; i++) {
    x[i & 3] = fmaxf(x[i & 3], fmaxf(S[4 * i], S[4 * i + 1]));
    y[i & 3] = fmaxf(y[i & 3], fmaxf(S[4 * i + 2], S[4 * i + 3]));
  }
  n0 = fmaxf(fmaxf(x[0], x[1]), fmaxf(x[2], x[3]));
  n1 = fmaxf(fmaxf(y[0], y[1]), fmaxf(y[2], y[3]));
  n0 = fmaxf(n0, __shfl_xor_sync(~0u, n0, 1));
  n1 = fmaxf(n1, __shfl_xor_sync(~0u, n1, 1));
  n0 = fmaxf(n0, __shfl_xor_sync(~0u, n0, 2));
  n1 = fmaxf(n1, __shfl_xor_sync(~0u, n1, 2));
}
__device__ __forceinline__ void to_exponent(float (&S)[64], float cc0, float cc1) {
#pragma unroll
  for (int i = 0; i < 16; i++) {
    S[4 * i] = fmaf(S[4 * i], SM_C, cc0); S[4 * i + 1] = fmaf(S[4 * i + 1], SM_C, cc0);
    S[4 * i + 2] = fmaf(S[4 * i + 2], SM_C, cc1); S[4 * i + 3] = fmaf(S[4 * i + 3], SM_C, cc1);
  }
}
__device__ __forceinline__ void scale_o(float (&O)[64], float f0, float f1) {
#pragma unroll
  for (int i = 0; i < 16; i++) { O[4 * i] *= f0; O[4 * i + 1] *= f0; O[4 * i + 2] *= f1; O[4 * i + 3] *= f1; }
}
__device__ __forceinline__ void exp_stream(float (&S)[64], uint32_t (&p)[32], float (&O)[64], float& cc0, float& cc1, float& l0, float& l1) {
  float s0, s1;
#pragma unroll 1
  for (int pass = 0;; pass++) {
    float a[4] = {0.f, 0.f, 0.f, 0.f};
#pragma unroll
    for (int i = 0; i < 16; i++) {
      const float e0 = ex2(S[4 * i]), e1 = ex2(S[4 * i + 1]), e2 = ex2(S[4 * i + 2]), e3 = ex2(S[4 * i + 3]);
      a[0] += e0; a[1] += e1; a[2] += e2; a[3] += e3;
      p[2 * i] = pack_bf16(e0, e1);
      p[2 * i + 1] = pack_bf16(e2, e3);
    }
    s0 = a[0] + a[1]; s1 = a[2] + a[3];
    if (pass || !__any_sync(~0u, !(fmaxf(s0, s1) <= 65536.f))) break;
    float d0, d1;
    row_max2(S, d0, d1);
    d0 = fmaxf(d0, 0.f); d1 = fmaxf(d1, 0.f);
#pragma unroll
    for (int i = 0; i < 16; i++) { S[4 * i] -= d0; S[4 * i + 1] -= d0; S[4 * i + 2] -= d1; S[4 * i + 3] -= d1; }
    cc0 -= d0; cc1 -= d1;
    const float f0 = ex2(-d0), f1 = ex2(-d1);
    scale_o(O, f0, f1);
    l0 *= f0; l1 *= f1;
  }
  l0 += s0; l1 += s1;
}

__device__ __forceinline__ void inv_rowsum(float l0, float l1, float& i0, float& i1) {
  l0 += __shfl_xor_sync(~0u, l0, 1); l1 += __shfl_xor_sync(~0u, l1, 1);
  l0 += __shfl_xor_sync(~0u, l0, 2); l1 += __shfl_xor_sync(~0u, l1, 2);
  i0 = rcp(l0); i1 = rcp(l1);
}
__device__ __forceinline__ void write_o(const float (&O)[64], const Cons& c) {
  uint32_t rowoff, xr;
  frag_addr(rowoff, xr);
  const uint32_t stg = c.sb + SM_STG + c.wg * 16384 + rowoff;
#pragma unroll
  for (int kb = 0; kb < 8; kb++)
    stsm4(stg + (kb >> 2) * 8192 + ((32 * (kb & 3)) ^ xr),
          pack_bf16(O[8 * kb], O[8 * kb + 1]), pack_bf16(O[8 * kb + 2], O[8 * kb + 3]),
          pack_bf16(O[8 * kb + 4], O[8 * kb + 5]), pack_bf16(O[8 * kb + 6], O[8 * kb + 7]));
  c.stg_publish();
}

__device__ __forceinline__ void issue_qk(float (&S)[64], const uint32_t (&q)[32], uint32_t s0, uint32_t s1, uint32_t zero) {
  const uint64_t d0 = mkdesc(s0, 16, 1024), d1 = mkdesc(s1, 16, 1024);
#pragma unroll
  for (int kk = 0; kk < 8; kk++)
    wgmma_rs_n128(S, q[4 * kk], q[4 * kk + 1], q[4 * kk + 2], q[4 * kk + 3], (kk < 4 ? d0 : d1) + (kk & 3) * 2, kk > 0 ? 1u : zero);
}
__device__ __forceinline__ void issue_pv(float (&O)[64], const uint32_t (&p)[32], uint32_t s0, uint32_t s1, uint32_t accum) {
  const uint64_t d0 = mkdesc(s0, 8192, 1024), d1 = mkdesc(s1, 8192, 1024);
#pragma unroll
  for (int kk = 0; kk < 8; kk++)
    wgmma_rs_n128_tb(O, p[4 * kk], p[4 * kk + 1], p[4 * kk + 2], p[4 * kk + 3], (kk < 4 ? d0 : d1) + (kk & 3) * 128, kk > 0 ? 1u : accum);
}

#define TURN_SYNC()   bar_sync(1 + c.wg, 256)
#define TURN_PASS()   bar_arrive(2 - c.wg, 256)

__device__ __forceinline__ void attn_tile(const float (&acc)[128], Cons& c, int t) {
  uint32_t q[32], p[32];
  float S[64], O[64];
  const uint32_t stash = c.sb + SM_STG + c.wg * 16384 + ((threadIdx.x >> 5) & 3) * 2048 + c.lane * 16;
#pragma unroll
  for (int i = 0; i < 32; i++) q[i] = pack_bf16(acc[2 * i], acc[2 * i + 1]);
  c.stg_acquire();
#pragma unroll
  for (int i = 0; i < 8; i++)
    sts128(stash + (i >> 2) * 8192 + (i & 3) * 512, pack_bf16(acc[64 + 8 * i], acc[65 + 8 * i]), pack_bf16(acc[66 + 8 * i], acc[67 + 8 * i]),
           pack_bf16(acc[68 + 8 * i], acc[69 + 8 * i]), pack_bf16(acc[70 + 8 * i], acc[71 + 8 * i]));
  fence_regs(q);
  TR(0, 0);
  TURN_SYNC();
  TR(0, 1);
  c.wait_full(c.g);
  wg_fence();
  issue_qk(S, q, c.sb + c.pos * SLOT, c.sb + wrap12(c.pos + 1) * SLOT, 0);
  wg_commit();
  TURN_PASS();
  TR(0, 2);
  wg_wait<0>();
  TR(0, 3);
  fence_regs(S);
  c.release(c.g);
  c.g++;
  c.pos = wrap12(c.pos + 2);
  float cc0, cc1, l0 = 0.f, l1 = 0.f;
  row_max2(S, cc0, cc1);
  cc0 *= -SM_C; cc1 *= -SM_C;
  to_exponent(S, cc0, cc1);
#pragma unroll
  for (int i = 0; i < 64; i++) O[i] = 0.f;
  exp_stream(S, p, O, cc0, cc1, l0, l1);
#pragma unroll 1
  for (int j = 0; j < 7 + (int)c.zero; j++) {
    const uint32_t k0 = c.pos, k1 = wrap12(k0 + 1), v0 = wrap12(k0 + 2), v1 = wrap12(k0 + 3);
    TR(j + 1, 0);
    TURN_SYNC();
    TR(j + 1, 1);
    c.wait_full(c.g);
    wg_fence();
    issue_qk(S, q, c.sb + k0 * SLOT, c.sb + k1 * SLOT, 0);
    wg_commit();
    c.wait_full(c.g + 1);
    wg_fence();
    issue_pv(O, p, c.sb + v0 * SLOT, c.sb + v1 * SLOT, j != 4);
    wg_commit();
    TURN_PASS();
    TR(j + 1, 2);
    wg_wait<1>();
    TR(j + 1, 3);
    fence_regs(S);
    fence_regs(q);
    c.release(c.g);
    if (j == 2) {
#pragma unroll
      for (int i = 0; i < 8; i++) lds128(stash + (i >> 2) * 8192 + (i & 3) * 512, q[4 * i], q[4 * i + 1], q[4 * i + 2], q[4 * i + 3]);
      __syncwarp();
    }
    float f0, f1;
    if (j == 3) {
      row_max2(S, cc0, cc1);
      cc0 *= -SM_C; cc1 *= -SM_C;
      inv_rowsum(l0, l1, f0, f1);
      l0 = 0.f; l1 = 0.f;
    }
    ONCE(c) { to_exponent(S, cc0, cc1); }
    TR(j + 1, 4);
    wg_wait<0>();
    TR(j + 1, 5);
    fence_regs(O);
    fence_regs(p);
    c.release(c.g + 1);
    c.g += 2;
    c.pos = wrap12(v1 + 1);
    if (j == 3) {
      scale_o(O, f0, f1);
      write_o(O, c);
    }
    TR(j + 1, 6);
    exp_stream(S, p, O, cc0, cc1, l0, l1);
  }
  TR(8, 0);
  TURN_SYNC();
  TR(8, 1);
  c.wait_full(c.g);
  wg_fence();
  issue_pv(O, p, c.sb + c.pos * SLOT, c.sb + wrap12(c.pos + 1) * SLOT, 1);
  wg_commit();
  TURN_PASS();
  TR(8, 2);
  c.stg_acquire();
  float a0, a1;
  inv_rowsum(l0, l1, a0, a1);
  wg_wait<0>();
  TR(8, 5);
  fence_regs(O);
  fence_regs(p);
  c.release(c.g);
  c.g++;
  c.pos = wrap12(c.pos + 2);
  scale_o(O, a0, a1);
  write_o(O, c);
  TR(9, 0);
}

struct Prod {
  uint32_t sb, g, pos, head, tail_g, tail_pos, hist;
  __device__ __forceinline__ uint32_t full() const { return sb + SM_BAR + B_FULL + (g & 7) * 8; }
  __device__ __forceinline__ uint32_t slot(uint32_t i) const { return sb + wrap12(pos + i) * SLOT; }
  __device__ __forceinline__ void acquire(uint32_t size) {
#pragma unroll 1
    while (head + size - tail_pos > NSLOT) {
      mbar_wait(sb + SM_BAR + B_EMPTY + (tail_g & 7) * 8, (tail_g >> 3) & 1);
      tail_pos += 2 + ((hist >> (tail_g & 31)) & 1);
      tail_g++;
    }
    hist = (hist & ~(1u << (g & 31))) | ((size - 2) << (g & 31));
  }
  __device__ __forceinline__ void advance(uint32_t size) { g++; head += size; pos = wrap12(pos + size); }
};

__device__ __forceinline__ void wait_flag(const unsigned* p, unsigned target) {
  while ((int)(ld_acquire(p) - target) < 0) {}
  fence_async_all();
}

__device__ __forceinline__ void init_barriers(uint32_t sb, int warp) {
  const uint32_t cnt = warp < 4 ? 1 : warp < 8 ? 16 : warp == 8 ? 4 : warp == 9 ? 1 : 11;
  if (warp < 11) mbar_init(sb + SM_BAR + warp * 16, cnt);
  if (warp < 10) mbar_init(sb + SM_BAR + warp * 16 + 8, cnt);
  asm volatile("fence.mbarrier_init.release.cluster;" ::: "memory");
}

#define TSP(i) do {} while (0)

__global__ void __cluster_dims__(2, 1, 1) __launch_bounds__(384, 1) fused_kernel(const __grid_constant__ Params P) {
  extern __shared__ uint8_t smem_raw[];
  const uint32_t sb = (smem_u32(smem_raw) + 1023u) & ~1023u;
  const int warp = __shfl_sync(~0u, (int)(threadIdx.x >> 5), 0);
  const int lane = threadIdx.x & 31;
  const int rank = blockIdx.x & 1;
  const int cl = blockIdx.x >> 1;
  const int j = cl >> 3;
  const int rb = (cl & 7) * 2 + rank;
  const bool is_s = j < 4, spare = j == 8;
  const int row0 = rb * 128;
  Flags* fl = P.flags;

  if (warp >= 8) {
    unsigned ep0 = 0;
    if (warp == 8) asm volatile("ld.volatile.global.u32 %0, [%1];" : "=r"(ep0) : "l"(&fl->epoch[blockIdx.x]));
    if (lane == 0) {
      if (warp == 8) prefetch_map(spare ? &P.w1b4 : &P.w1b3);
      if (warp == 9) prefetch_map(&P.act_ld);
      init_barriers(sb, warp);
    }
    __syncwarp();
    cluster_arrive();
    if (warp == 10 && lane == 0) {
      prefetch_map(&P.act_st); prefetch_map(&P.wq); prefetch_map(&P.k_ld); prefetch_map(&P.v_ld);
      prefetch_map(is_s ? &P.wo : &P.w2); prefetch_map(&P.x_ld); prefetch_map(&P.out_st);
    }
    __syncwarp();
    cluster_wait();
    asm volatile("setmaxnreg.dec.sync.aligned.u32 24;");
    if (warp == 8) {
      TSP(17);
#define ep1 (ep0 + 1)
      Prod p{sb, 0, 0, 0, 0, 0, 0};
#define LDA(dst, m, bar, c0, c1) tma_ld2(dst, m, bar, c0, c1)
#define LDW1(dst, m, bar, c0, c1, c2) tma_ld3_mc(dst, m, bar, c0, c1, c2)
#define LDW(dst, m, bar, c0, c1, c2) tma_ld3_mc(dst, m, bar, c0, c1, c2)
      {
        const CUtensorMap* mb = spare ? &P.w1b4 : &P.w1b3;
        const uint32_t bytes = spare ? 49152 : 40960;
        const int nt = spare ? 8 : 2;
#pragma unroll 1
        for (int t = 0; t < nt; t++) {
          const int r = spare ? ((cl & 1) * 4 + (t >> 1)) * 2 + rank : rb;
          const int nb0 = spare ? (H_SPARE0 >> 6) + (t & 1) * 4 : j * 6 + t * 3;
          int k = 0;
          if (t == 0) {
#pragma unroll 1
            for (; k < 4; k++) {
              p.acquire(3);
              if (lane == 0) { mbar_expect_tx(p.full(), bytes); LDW1(p.slot(1 + rank), mb, p.full(), 0, k * 64 + rank * 32, nb0); }
              p.advance(3);
            }
            TSP(14);
            asm volatile("" : "+r"(ep0));
            wait_flag(&fl->ln[r][0], ep1 * 64);
            TSP(15);
            if (lane == 0)
              for (int i = 0; i < 4; i++) tma_ld2(sb + i * 3 * SLOT, &P.act_ld, sb + SM_BAR + B_FULL + i * 8, C_XN + i * 64, r * 128);
          } else if (spare && !(t & 1)) {
            wait_flag(&fl->ln[r][0], ep1 * 64);
          }
#pragma unroll 1
          for (; k < 16; k++) {
            p.acquire(3);
            if (lane == 0) {
              mbar_expect_tx(p.full(), bytes);
              LDW1(p.slot(1 + rank), mb, p.full(), 0, k * 64 + rank * 32, nb0);
              tma_ld2(p.slot(0), &P.act_ld, p.full(), C_XN + k * 64, r * 128);
            }
            p.advance(3);
          }
        }
      }
      if (!spare) {
        const int kvrow = (j >> 1) * SK + KV0;
#pragma unroll 1
        for (int t = 0; t < 2; t++) {
          const int nb0 = (4 * j + 2 * t) * 2;
#pragma unroll 1
          for (int k = 0; k < 16; k++) {
            p.acquire(3);
            if (lane == 0) {
              mbar_expect_tx(p.full(), 49152);
              LDW1(p.slot(1 + rank), &P.wq, p.full(), 0, k * 64 + rank * 32, nb0);
              tma_ld2(p.slot(0), &P.act_ld, p.full(), C_XN + k * 64, row0);
            }
            p.advance(3);
          }
#pragma unroll 1
          for (int i = 0; i < 16; i++) {
            const bool is_k = i == 0 || (i < 15 && (i & 1));
            const int ch = (is_k ? ((i + 1) >> 1) : (i == 15 ? 7 : (i >> 1) - 1)) & 3;
            p.acquire(2);
            if (lane == 0) {
              mbar_expect_tx(p.full(), 32768);
              if (is_k) tma_ld2_mc(p.slot(rank), &P.k_ld, p.full(), rank * 64, kvrow + ch * 128);
              else      tma_ld3_mc(p.slot(rank), &P.v_ld, p.full(), 0, kvrow + ch * 128 + rank * 64, 0);
            }
            p.advance(2);
            if (t == 1 && i == 8 && !is_s) wait_flag(&fl->h[rb][0], ep1 * 64);
          }
        }
        const int jn = j & 3;
        if (is_s) {
          unsigned ready = 0;
#pragma unroll 1
          for (int i = 0; i < 64; i++) {
            const int hi = i >> 1;
            const int head = 4 * ((hi & 15) >> 1) + (hi & 1) + ((hi >> 4) << 1);
            const int kc = head * 128 + (i & 1) * 64;
            p.acquire(3);
            if (lane == 0) { mbar_expect_tx(p.full(), 49152); LDW(p.slot(1 + rank), &P.wo, p.full(), 0, kc + rank * 32, jn * 4); }
            if (!((ready >> head) & 1)) {
              do { ready = __ballot_sync(~0u, (int)(ld_acquire(&fl->o[rb][lane]) - ep1 * 2) >= 0); } while (!((ready >> head) & 1));
              __syncwarp();
              fence_async_all();
            }
            if (lane == 0) LDA(p.slot(0), &P.act_ld, p.full(), C_O + kc, row0);
            p.advance(3);
          }
          bool g_ready = (int)(ld_acquire(&fl->g[rb][jn]) - ep1 * 4) >= 0;
#pragma unroll 1
          for (int i = 0; i < 4; i++) {
            p.acquire(2);
            if (i == 2) { TSP(20); if (g_ready) fence_async_all(); else wait_flag(&fl->g[rb][jn], ep1 * 4); TSP(21); }
            if (lane == 0) {
              mbar_expect_tx(p.full(), 32768);
              const CUtensorMap* m = i < 2 ? &P.x_ld : &P.act_ld;
              const int c0 = (i < 2 ? 0 : C_G) + jn * 256 + (i & 1) * 128;
              tma_ld2(p.slot(0), m, p.full(), c0, row0);
              tma_ld2(p.slot(1), m, p.full(), c0 + 64, row0);
            }
            p.advance(2);
          }
        } else {
#pragma unroll 1
          for (int k = 0; k < 56; k++) {
            p.acquire(3);
            if (lane == 0) { mbar_expect_tx(p.full(), 49152); LDW(p.slot(1 + rank), &P.w2, p.full(), 0, k * 64 + rank * 32, jn * 4); }
            if (k == H_SPARE0 / 64) wait_flag(&fl->h[rb][16], ep1 * 8);
            if (lane == 0) LDA(p.slot(0), &P.act_ld, p.full(), C_H + k * 64, row0);
            p.advance(3);
          }
        }
      }
      if (lane == 0) { *(volatile unsigned*)&fl->epoch[blockIdx.x] = ep1; mbar_arrive(sb + SM_BAR + B_DONE); }
    } else if (warp < 11) {
      const int wg = warp - 9;
      if (lane == 0) {
        const uint32_t stg = sb + SM_STG + wg * 16384;
        const int nev = spare ? 16 : is_s ? 8 : 10;
#pragma unroll 1
        for (int n = 0; n < nev; n++) {
          int col, row = row0, nbox = 2;
          unsigned* flag;
          if (spare) {
            const int r = ((cl & 1) * 4 + (n >> 2)) * 2 + rank;
            row = r * 128;
            col = C_H + H_SPARE0 + (n & 3) * 128;
            flag = &fl->h[r][16];
          } else if (n < 4) {
            col = C_H + j * H_REG + (n >> 1) * 192 + (n & 1) * 128;
            nbox = 2 - (n & 1);
            flag = &fl->h[rb][0];
          } else if (n < 8) {
            col = C_O + (4 * j + n - 4) * 128;
            flag = &fl->o[rb][4 * j + n - 4];
          } else {
            col = C_G + (j & 3) * 256 + (n - 8) * 128;
            flag = &fl->g[rb][j & 3];
          }
          mbar_wait(sb + SM_BAR + B_SFULL + wg * 8, n & 1);
          if (n == 9 && wg == 0) TSP(20);
          tma_st2(&P.act_st, stg, col, row + wg * 64);
          if (nbox == 2) tma_st2(&P.act_st, stg + 8192, col + 64, row + wg * 64);
          bulk_commit();
          bulk_wait_read0();
          mbar_arrive(sb + SM_BAR + B_SEMPTY + wg * 8);
          if (n == 9 && wg == 0) TSP(21);
          bulk_wait0();
          if (n == 9 && wg == 0) TSP(22);
          fence_async_all();
          red_release(flag, 1);
          if (n == 9 && wg == 0) TSP(23);
        }
        mbar_arrive(sb + SM_BAR + B_DONE);
      }
    } else {
      if (lane == 0) {
        const unsigned long long t0 = gtime();
        while (!mbar_try(sb + SM_BAR + B_DONE, 0)) {
          if (gtime() - t0 > 2000000000ull) __trap();
        }
      }
    }
    __syncwarp();
    cluster_arrive();
    cluster_wait();
  } else {
    const int wg = warp >> 2;
    TS(0);
    if (!spare) {
      const int r = row0 + j * 16 + warp * 2;
      uint32_t v[2][16];
#pragma unroll
      for (int a = 0; a < 2; a++)
#pragma unroll
        for (int i = 0; i < 4; i++)
          *(uint4*)&v[a][4 * i] = __ldg((const uint4*)(P.x + (size_t)(r + a) * DM + i * 256 + lane * 8));
      if (lane == 0) init_barriers(sb, warp);
      __syncwarp();
      cluster_arrive();
      float s[2], q[2];
#pragma unroll
      for (int a = 0; a < 2; a++) {
        float t0 = 0.f, t1 = 0.f;
#pragma unroll
        for (int i = 0; i < 16; i++) { t0 += bf_lo(v[a][i]); t1 += bf_hi(v[a][i]); }
        s[a] = t0 + t1;
      }
#pragma unroll
      for (int o = 16; o; o >>= 1) { s[0] += __shfl_xor_sync(~0u, s[0], o); s[1] += __shfl_xor_sync(~0u, s[1], o); }
#pragma unroll
      for (int a = 0; a < 2; a++) {
        s[a] *= 1.0f / DM;
        float t0 = 0.f, t1 = 0.f;
#pragma unroll
        for (int i = 0; i < 16; i++) {
          const float d0 = bf_lo(v[a][i]) - s[a], d1 = bf_hi(v[a][i]) - s[a];
          t0 = fmaf(d0, d0, t0); t1 = fmaf(d1, d1, t1);
        }
        q[a] = t0 + t1;
      }
#pragma unroll
      for (int o = 16; o; o >>= 1) { q[0] += __shfl_xor_sync(~0u, q[0], o); q[1] += __shfl_xor_sync(~0u, q[1], o); }
#pragma unroll
      for (int a = 0; a < 2; a++) {
        const uint32_t mb2 = pack_bf16(s[a], s[a]);
        const float inv = 1.0f / bf_round(sqrtf(bf_round(bf_round(q[a] * (1.0f / DM)) + 1e-5f)));
#pragma unroll
        for (int i = 0; i < 16; i++) {
          const __nv_bfloat162 d = __hsub2_rn(*(const __nv_bfloat162*)&v[a][i], *(const __nv_bfloat162*)&mb2);
          const uint32_t du = *(const uint32_t*)&d;
          v[a][i] = pack_bf16(bf_lo(du) * inv, bf_hi(du) * inv);
        }
#pragma unroll
        for (int i = 0; i < 4; i++)
          *(uint4*)(P.act + (size_t)(r + a) * ACT_W + C_XN + i * 256 + lane * 8) = *(const uint4*)&v[a][4 * i];
      }
      TS(11);
      fence_async_all();
      TS(12);
      __syncwarp();
      if (lane == 0) red_release(&fl->ln[rb][0], 1);
      TS(13);
    } else {
      if (lane == 0) init_barriers(sb, warp);
      __syncwarp();
      cluster_arrive();
    }
    cluster_wait();
    asm volatile("setmaxnreg.inc.sync.aligned.u32 240;");
    Cons c;
    c.zero = blockIdx.y; c.sb = sb; c.g = 0; c.pos = 0; c.nstg = 0; c.wg = wg; c.lane = lane;
    c.rel = mapa(sb + SM_BAR + B_EMPTY, lane & 1);
    float acc[128];
    TS(1);
    if (spare) {
      uint32_t pend[32];
#pragma unroll
      for (int i = 0; i < 32; i++) pend[i] = 0;
#pragma unroll 1
      for (int t = 0; t < 8; t++) {
        gemm_loop_flush<256, 2>(acc, c, pend, t > 0);
        h_epilogue<2>(acc, c, pend);
      }
      c.stg_acquire();
      stage_boxes<2>(pend, 0, c);
      TS(6);
    } else {
      if (wg == 1) bar_arrive(1, 256);
      {
        uint32_t pend[16];
#pragma unroll
        for (int i = 0; i < 16; i++) pend[i] = 0;
#pragma unroll 1
        for (int t = 0; t < 2; t++) {
          gemm_loop_flush<192, 1>(acc, c, pend, t > 0);
          h_epilogue<1>(acc, c, pend);
          TS(2 + t);
        }
        gemm_loop_flush<256, 1>(acc, c, pend, true);
      }
#pragma unroll 1
      for (int t = 0; t < 2; t++) {
        TS(8 + t);
        attn_tile(acc, c, t);
        TS(4 + t);
        gemm_loop<256>(acc, c, t == 0 ? 16 : is_s ? 64 : 56);
      }
      TS(6);
      if (is_s) {
        uint32_t rowoff, xr;
        frag_addr(rowoff, xr);
        const uint32_t x0 = c.pos;
#pragma unroll
        for (int b = 0; b < 4; b++) {
          if ((b & 1) == 0) { c.wait_full(c.g + (b >> 1)); c.wait_full(c.g + 2 + (b >> 1)); }
          if (b == 0) TS(22);
          if (b == 2) TS(23);
          const uint32_t xs = sb + wrap12(x0 + b) * SLOT + wg * 8192;
          const uint32_t sx = xs + rowoff, sg = sb + wrap12(wrap12(x0 + 4) + b) * SLOT + wg * 8192 + rowoff;
          uint32_t xv[16], gv[16];
#pragma unroll
          for (int kb = 0; kb < 4; kb++) {
            ldsm4(sx + ((32 * kb) ^ xr), xv[4 * kb], xv[4 * kb + 1], xv[4 * kb + 2], xv[4 * kb + 3]);
            ldsm4(sg + ((32 * kb) ^ xr), gv[4 * kb], gv[4 * kb + 1], gv[4 * kb + 2], gv[4 * kb + 3]);
          }
#pragma unroll
          for (int i = 0; i < 16; i++) {
            const uint32_t s2 = pack_bf16(acc[32 * b + 2 * i], acc[32 * b + 2 * i + 1]);
            const __nv_bfloat162 pr = __hmul2_rn(*(const __nv_bfloat162*)&s2, *(const __nv_bfloat162*)&gv[i]);
            const __nv_bfloat162 o = __hadd2_rn(*(const __nv_bfloat162*)&xv[i], pr);
            xv[i] = *(const uint32_t*)&o;
          }
#pragma unroll
          for (int kb = 0; kb < 4; kb++) stsm4(sx + ((32 * kb) ^ xr), xv[4 * kb], xv[4 * kb + 1], xv[4 * kb + 2], xv[4 * kb + 3]);
          if (b & 1) {
            fence_async_smem();
            bar_sync(3 + wg, 128);
            if ((threadIdx.x & 127) == 0) {
              tma_st2(&P.out_st, sb + wrap12(x0 + b - 1) * SLOT + wg * 8192, (j & 3) * 256 + b * 64 - 64, row0 + wg * 64);
              tma_st2(&P.out_st, xs, (j & 3) * 256 + b * 64, row0 + wg * 64);
              bulk_commit();
            }
          }
        }
        TS(24);
        if ((threadIdx.x & 127) == 0) bulk_wait_read0();
      } else {
#pragma unroll
        for (int hh = 0; hh < 2; hh++) {
          uint32_t r[32];
#pragma unroll
          for (int i = 0; i < 32; i++) r[i] = silu2(acc[64 * hh + 2 * i], acc[64 * hh + 2 * i + 1]);
          c.stg_acquire();
          stage_boxes<2>(r, 0, c);
          if (hh == 0) TS(22);
        }
      }
    }
    TS(7);
    __syncwarp();
    if (lane == 0) mbar_arrive(sb + SM_BAR + B_DONE);
    cluster_arrive();
    cluster_wait();
  }
}

typedef CUresult (*EncodeFn)(CUtensorMap*, CUtensorMapDataType, cuuint32_t, void*, const cuuint64_t*, const cuuint64_t*,
                             const cuuint32_t*, const cuuint32_t*, CUtensorMapInterleave, CUtensorMapSwizzle,
                             CUtensorMapL2promotion, CUtensorMapFloatOOBfill);

void map2d(EncodeFn enc, CUtensorMap* m, const void* base, uint64_t cols, uint64_t rows, uint32_t box_rows) {
  cuuint64_t dims[2] = {cols, rows};
  cuuint64_t strides[1] = {cols * 2};
  cuuint32_t box[2] = {64, box_rows};
  cuuint32_t es[2] = {1, 1};
  enc(m, CU_TENSOR_MAP_DATA_TYPE_BFLOAT16, 2, (void*)base, dims, strides, box, es, CU_TENSOR_MAP_INTERLEAVE_NONE,
      CU_TENSOR_MAP_SWIZZLE_128B, CU_TENSOR_MAP_L2_PROMOTION_L2_256B, CU_TENSOR_MAP_FLOAT_OOB_FILL_NONE);
}
void map3d(EncodeFn enc, CUtensorMap* m, const void* base, uint64_t cols, uint64_t rows, uint32_t box_rows, uint32_t box_blks) {
  cuuint64_t dims[3] = {64, rows, cols / 64};
  cuuint64_t strides[2] = {cols * 2, 128};
  cuuint32_t box[3] = {64, box_rows, box_blks};
  cuuint32_t es[3] = {1, 1, 1};
  enc(m, CU_TENSOR_MAP_DATA_TYPE_BFLOAT16, 3, (void*)base, dims, strides, box, es, CU_TENSOR_MAP_INTERLEAVE_NONE,
      CU_TENSOR_MAP_SWIZZLE_128B, CU_TENSOR_MAP_L2_PROMOTION_L2_256B, CU_TENSOR_MAP_FLOAT_OOB_FILL_NONE);
}

}

extern "C" void kernel_launch(void* const* d_in, const int* in_sizes, int n_in, void* d_out, int out_size) {
  (void)in_sizes; (void)n_in; (void)out_size;
  static EncodeFn enc = nullptr;
  static void* act = nullptr;
  static void* flags = nullptr;
  if (!enc) {
    void* fn = nullptr;
    cudaDriverEntryPointQueryResult qr;
    cudaGetDriverEntryPoint("cuTensorMapEncodeTiled", &fn, cudaEnableDefault, &qr);
    enc = (EncodeFn)fn;
    cudaGetSymbolAddress(&act, g_act);
    cudaGetSymbolAddress(&flags, g_flags);
    cudaFuncSetAttribute(fused_kernel, cudaFuncAttributeMaxDynamicSharedMemorySize, SMEM_BYTES);
  }
  Params P;
  map2d(enc, &P.act_ld, act, ACT_W, SEQ, 128);
  map2d(enc, &P.act_st, act, ACT_W, SEQ, 64);
  map2d(enc, &P.x_ld, d_in[0], DM, SEQ, 128);
  map2d(enc, &P.out_st, d_out, DM, SEQ, 64);
  map2d(enc, &P.k_ld, d_in[1], 128, 4 * SK, 128);
  map3d(enc, &P.v_ld, d_in[2], 128, 4 * SK, 64, 2);
  map3d(enc, &P.wq, d_in[3], NQ, DM, 32, 4);
  map3d(enc, &P.w1b4, d_in[6], DFF, DM, 32, 4);
  map3d(enc, &P.w1b3, d_in[6], DFF, DM, 32, 3);
  map3d(enc, &P.wo, d_in[4], DM, NQ, 32, 4);
  map3d(enc, &P.w2, d_in[7], DM, DFF, 32, 4);
  P.x = (const __nv_bfloat16*)d_in[0];
  P.act = (__nv_bfloat16*)act;
  P.flags = (Flags*)flags;
  fused_kernel<<<NCLUSTER * 2, 384, SMEM_BYTES>>>(P);
}
```

```cpp
#include <cuda_runtime.h>
#include <cuda_bf16.h>
#include <cuda.h>
#include <stdint.h>

namespace {

constexpr int SEQ    = 2048;
constexpr int DM     = 1024;
constexpr int NQ     = 4096;
constexpr int DFF    = 3584;
constexpr int SK     = 2048;
constexpr int WIN    = 512;
constexpr int KV0    = SK - WIN;
constexpr int C_XN = 0, C_O = 1024, C_H = 5120, C_G = 8704, ACT_W = 9728;

constexpr int H_REG = 384, H_SPARE0 = 8 * H_REG;
static_assert(H_SPARE0 + 512 == DFF, "H split");

constexpr int NSLOT = 12, SLOT = 16384, NBAR = 8;
constexpr int SM_STG = NSLOT * SLOT;
constexpr int SM_BAR = SM_STG + 2 * 16384;
constexpr int SMEM_BYTES = SM_BAR + 256 + 1024;
constexpr int B_FULL = 0, B_EMPTY = 64, B_SFULL = 128, B_SEMPTY = 144, B_DONE = 160;

constexpr int NCLUSTER = 66;

struct Flags {
  unsigned ln[16][32];
  unsigned h[16][32];
  unsigned o[16][32];
  unsigned g[16][32];
  unsigned epoch[160];
};
__device__ __nv_bfloat16 g_act[(size_t)SEQ * ACT_W];
__device__ Flags g_flags;

struct Params {
  CUtensorMap act_ld, act_st, x_ld, out_st, k_ld, v_ld, wq, w1b4, w1b3, wo, w2;
  const __nv_bfloat16* x;
  __nv_bfloat16* act;
  Flags* flags;
};

__device__ __forceinline__ uint32_t smem_u32(const void* p) { return (uint32_t)__cvta_generic_to_shared(p); }
__device__ __forceinline__ void mbar_init(uint32_t bar, uint32_t cnt) {
  asm volatile("mbarrier.init.shared::cta.b64 [%0], %1;" ::"r"(bar), "r"(cnt) : "memory");
}
__device__ __forceinline__ bool mbar_try(uint32_t bar, uint32_t parity) {
  uint32_t ok;
  asm volatile("{\n.reg .pred p;\nmbarrier.try_wait.parity.shared::cta.b64 p, [%1], %2;\nselp.u32 %0, 1, 0, p;\n}\n"
               : "=r"(ok) : "r"(bar), "r"(parity) : "memory");
  return ok;
}
__device__ __forceinline__ void mbar_wait(uint32_t bar, uint32_t parity) {
  asm volatile("{\n.reg .pred p;\nWAIT_%=:\nmbarrier.try_wait.parity.shared::cta.b64 p, [%0], %1;\n@p bra DONE_%=;\nbra WAIT_%=;\nDONE_%=:\n}\n"
               ::"r"(bar), "r"(parity) : "memory");
}
__device__ __forceinline__ void mbar_arrive(uint32_t bar) {
  asm volatile("mbarrier.arrive.shared::cta.b64 _, [%0];" ::"r"(bar) : "memory");
}
__device__ __forceinline__ void mbar_arrive_cluster(uint32_t cluster_addr) {
  asm volatile("mbarrier.arrive.shared::cluster.b64 _, [%0];" ::"r"(cluster_addr) : "memory");
}
__device__ __forceinline__ void mbar_expect_tx(uint32_t bar, uint32_t bytes) {
  asm volatile("mbarrier.arrive.expect_tx.shared::cta.b64 _, [%0], %1;" ::"r"(bar), "r"(bytes) : "memory");
}
__device__ __forceinline__ uint32_t mapa(uint32_t addr, uint32_t rank) {
  uint32_t r;
  asm("mapa.shared::cluster.u32 %0, %1, %2;" : "=r"(r) : "r"(addr), "r"(rank));
  return r;
}
__device__ __forceinline__ void cluster_arrive() { asm volatile("barrier.cluster.arrive.relaxed.aligned;" ::: "memory"); }
__device__ __forceinline__ void cluster_wait() { asm volatile("barrier.cluster.wait.acquire.aligned;" ::: "memory"); }
__device__ __forceinline__ void bar_sync(int id, int n) { asm volatile("bar.sync %0, %1;" ::"r"(id), "r"(n) : "memory"); }
__device__ __forceinline__ void bar_arrive(int id, int n) { asm volatile("bar.arrive %0, %1;" ::"r"(id), "r"(n) : "memory"); }
__device__ __forceinline__ void fence_async_smem() { asm volatile("fence.proxy.async.shared::cta;" ::: "memory"); }
__device__ __forceinline__ void fence_async_all() { asm volatile("fence.proxy.async.global;" ::: "memory"); }

__device__ __forceinline__ void tma_ld2(uint32_t dst, const CUtensorMap* m, uint32_t bar, int c0, int c1) {
  asm volatile("cp.async.bulk.tensor.2d.shared::cluster.global.mbarrier::complete_tx::bytes [%0], [%1, {%3, %4}], [%2];"
               ::"r"(dst), "l"(m), "r"(bar), "r"(c0), "r"(c1) : "memory");
}
__device__ __forceinline__ void tma_ld2_mc(uint32_t dst, const CUtensorMap* m, uint32_t bar, int c0, int c1) {
  asm volatile("cp.async.bulk.tensor.2d.shared::cluster.global.mbarrier::complete_tx::bytes.multicast::cluster [%0], [%1, {%3, %4}], [%2], %5;"
               ::"r"(dst), "l"(m), "r"(bar), "r"(c0), "r"(c1), "h"((uint16_t)3) : "memory");
}
__device__ __forceinline__ void tma_ld3_mc(uint32_t dst, const CUtensorMap* m, uint32_t bar, int c0, int c1, int c2) {
  asm volatile("cp.async.bulk.tensor.3d.shared::cluster.global.mbarrier::complete_tx::bytes.multicast::cluster [%0], [%1, {%3, %4, %5}], [%2], %6;"
               ::"r"(dst), "l"(m), "r"(bar), "r"(c0), "r"(c1), "r"(c2), "h"((uint16_t)3) : "memory");
}
__device__ __forceinline__ void tma_ld3_mc_hint(uint32_t dst, const CUtensorMap* m, uint32_t bar, int c0, int c1, int c2, uint64_t pol) {
  asm volatile("cp.async.bulk.tensor.3d.shared::cluster.global.mbarrier::complete_tx::bytes.multicast::cluster.L2::cache_hint [%0], [%1, {%3, %4, %5}], [%2], %6, %7;"
               ::"r"(dst), "l"(m), "r"(bar), "r"(c0), "r"(c1), "r"(c2), "h"((uint16_t)3), "l"(pol) : "memory");
}
__device__ __forceinline__ void tma_ld2_hint(uint32_t dst, const CUtensorMap* m, uint32_t bar, int c0, int c1, uint64_t pol) {
  asm volatile("cp.async.bulk.tensor.2d.shared::cluster.global.mbarrier::complete_tx::bytes.L2::cache_hint [%0], [%1, {%3, %4}], [%2], %5;"
               ::"r"(dst), "l"(m), "r"(bar), "r"(c0), "r"(c1), "l"(pol) : "memory");
}
__device__ __forceinline__ void tma_st2_hint(const CUtensorMap* m, uint32_t src, int c0, int c1, uint64_t pol) {
  asm volatile("cp.async.bulk.tensor.2d.global.shared::cta.bulk_group.L2::cache_hint [%0, {%2, %3}], [%1], %4;"
               ::"l"(m), "r"(src), "r"(c0), "r"(c1), "l"(pol) : "memory");
}
#define POL_FIRST 0x12F0000000000000ull
__device__ __forceinline__ uint64_t policy_evict_first() {
  uint64_t p;
  asm volatile("createpolicy.fractional.L2::evict_first.b64 %0, 1.0;" : "=l"(p));
  return p;
}
__device__ __forceinline__ void tma_st2(const CUtensorMap* m, uint32_t src, int c0, int c1) {
  asm volatile("cp.async.bulk.tensor.2d.global.shared::cta.bulk_group [%0, {%2, %3}], [%1];"
               ::"l"(m), "r"(src), "r"(c0), "r"(c1) : "memory");
}
__device__ __forceinline__ void tma_pf3(const CUtensorMap* m, int c0, int c1, int c2) {
  asm volatile("cp.async.bulk.prefetch.tensor.3d.L2.global [%0, {%1, %2, %3}];" ::"l"(m), "r"(c0), "r"(c1), "r"(c2) : "memory");
}
__device__ __forceinline__ void bulk_commit() { asm volatile("cp.async.bulk.commit_group;" ::: "memory"); }
__device__ __forceinline__ void bulk_wait_read0() { asm volatile("cp.async.bulk.wait_group.read 0;" ::: "memory"); }
__device__ __forceinline__ void bulk_wait0() { asm volatile("cp.async.bulk.wait_group 0;" ::: "memory"); }
__device__ __forceinline__ void prefetch_map(const CUtensorMap* m) {
  asm volatile("prefetch.tensormap [%0];" ::"l"(m) : "memory");
}
__device__ __forceinline__ unsigned ld_acquire(const unsigned* p) {
  unsigned v;
  asm volatile("ld.acquire.gpu.global.u32 %0, [%1];" : "=r"(v) : "l"(p) : "memory");
  return v;
}
__device__ __forceinline__ void red_release(unsigned* p, unsigned v) {
  asm volatile("red.release.gpu.global.add.u32 [%0], %1;" ::"l"(p), "r"(v) : "memory");
}
__device__ __forceinline__ void wg_fence() { asm volatile("wgmma.fence.sync.aligned;" ::: "memory"); }
__device__ __forceinline__ void wg_commit() { asm volatile("wgmma.commit_group.sync.aligned;" ::: "memory"); }
template <int N> __device__ __forceinline__ void wg_wait() { asm volatile("wgmma.wait_group.sync.aligned %0;" ::"n"(N) : "memory"); }
template <int N> __device__ __forceinline__ void fence_regs(float (&d)[N]) {
#pragma unroll
  for (int i = 0; i < N; i++) asm volatile("" : "+f"(d[i])::"memory");
}
template <int N> __device__ __forceinline__ void fence_regs(uint32_t (&d)[N]) {
#pragma unroll
  for (int i = 0; i < N; i++) asm volatile("" : "+r"(d[i])::"memory");
}
__device__ __forceinline__ uint64_t mkdesc(uint32_t addr, uint32_t lbo, uint32_t sbo) {
  return (uint64_t)((addr & 0x3FFFF) >> 4) | ((uint64_t)(lbo >> 4) << 16) | ((uint64_t)(sbo >> 4) << 32) | (1ull << 62);
}
__device__ __forceinline__ uint32_t pack_bf16(float lo, float hi) {
  uint32_t r;
  asm("cvt.rn.bf16x2.f32 %0, %1, %2;" : "=r"(r) : "f"(hi), "f"(lo));
  return r;
}
__device__ __forceinline__ uint32_t pack_bf16_relu(float lo, float hi) {
  uint32_t r;
  asm("cvt.rn.relu.bf16x2.f32 %0, %1, %2;" : "=r"(r) : "f"(hi), "f"(lo));
  return r;
}
__device__ __forceinline__ float bf_lo(uint32_t v) { return __uint_as_float(v << 16); }
__device__ __forceinline__ float bf_hi(uint32_t v) { return __uint_as_float(v & 0xFFFF0000u); }
__device__ __forceinline__ float bf_round(float v) { return __bfloat162float(__float2bfloat16_rn(v)); }
__device__ __forceinline__ float ex2(float x) {
  float r;
  asm("ex2.approx.ftz.f32 %0, %1;" : "=f"(r) : "f"(x));
  return r;
}
__device__ __forceinline__ float rcp(float x) {
  float r;
  asm("rcp.approx.ftz.f32 %0, %1;" : "=f"(r) : "f"(x));
  return r;
}
__device__ __forceinline__ uint32_t tid_x() {
  uint32_t t;
  asm volatile("mov.u32 %0, %%tid.x;" : "=r"(t));
  return t;
}
__device__ __forceinline__ void stsm4(uint32_t addr, uint32_t r0, uint32_t r1, uint32_t r2, uint32_t r3) {
  asm volatile("stmatrix.sync.aligned.m8n8.x4.shared.b16 [%0], {%1, %2, %3, %4};" ::"r"(addr), "r"(r0), "r"(r1), "r"(r2), "r"(r3) : "memory");
}
__device__ __forceinline__ void ldsm4(uint32_t addr, uint32_t& r0, uint32_t& r1, uint32_t& r2, uint32_t& r3) {
  asm volatile("ldmatrix.sync.aligned.m8n8.x4.shared.b16 {%0, %1, %2, %3}, [%4];" : "=r"(r0), "=r"(r1), "=r"(r2), "=r"(r3) : "r"(addr) : "memory");
}
__device__ __forceinline__ void sts128(uint32_t addr, uint32_t r0, uint32_t r1, uint32_t r2, uint32_t r3) {
  asm volatile("st.shared.v4.b32 [%0], {%1, %2, %3, %4};" ::"r"(addr), "r"(r0), "r"(r1), "r"(r2), "r"(r3) : "memory");
}
__device__ __forceinline__ void lds128(uint32_t addr, uint32_t& r0, uint32_t& r1, uint32_t& r2, uint32_t& r3) {
  asm volatile("ld.shared.v4.b32 {%0, %1, %2, %3}, [%4];" : "=r"(r0), "=r"(r1), "=r"(r2), "=r"(r3) : "r"(addr) : "memory");
}
__device__ __forceinline__ unsigned long long gtime() {
  unsigned long long t;
  asm volatile("mov.u64 %0, %globaltimer;" : "=l"(t));
  return t;
}

__device__ __forceinline__ void wgmma_ss_n256_tb(float (&d)[128], uint64_t da, uint64_t db, uint32_t sc) {
  asm volatile("{\n.reg .pred p;\nsetp.ne.b32 p, %130, 0;\n"
    "wgmma.mma_async.sync.aligned.m64n256k16.f32.bf16.bf16 "
    "{%0, %1, %2, %3, %4, %5, %6, %7, %8, %9, %10, %11, %12, %13, %14, %15, %16, %17, %18, %19, %20, %21, %22, %23, %24, %25, %26, %27, %28, %29, %30, %31, %32, %33, %34, %35, %36, %37, %38, %39, %40, %41, %42, %43, %44, %45, %46, %47, %48, %49, %50, %51, %52, %53, %54, %55, %56, %57, %58, %59, %60, %61, %62, %63, %64, %65, %66, %67, %68, %69, %70, %71, %72, %73, %74, %75, %76, %77, %78, %79, %80, %81, %82, %83, %84, %85, %86, %87, %88, %89, %90, %91, %92, %93, %94, %95, %96, %97, %98, %99, %100, %101, %102, %103, %104, %105, %106, %107, %108, %109, %110, %111, %112, %113, %114, %115, %116, %117, %118, %119, %120, %121, %122, %123, %124, %125, %126, %127}, %128, %129, p, 1, 1, 0, 1;\n}\n"
    : "+f"(d[0]), "+f"(d[1]), "+f"(d[2]), "+f"(d[3]), "+f"(d[4]), "+f"(d[5]), "+f"(d[6]), "+f"(d[7]), "+f"(d[8]), "+f"(d[9]), "+f"(d[10]), "+f"(d[11]), "+f"(d[12]), "+f"(d[13]), "+f"(d[14]), "+f"(d[15]), "+f"(d[16]), "+f"(d[17]), "+f"(d[18]), "+f"(d[19]), "+f"(d[20]), "+f"(d[21]), "+f"(d[22]), "+f"(d[23]), "+f"(d[24]), "+f"(d[25]), "+f"(d[26]), "+f"(d[27]), "+f"(d[28]), "+f"(d[29]), "+f"(d[30]), "+f"(d[31]), "+f"(d[32]), "+f"(d[33]), "+f"(d[34]), "+f"(d[35]), "+f"(d[36]), "+f"(d[37]), "+f"(d[38]), "+f"(d[39]), "+f"(d[40]), "+f"(d[41]), "+f"(d[42]), "+f"(d[43]), "+f"(d[44]), "+f"(d[45]), "+f"(d[46]), "+f"(d[47]), "+f"(d[48]), "+f"(d[49]), "+f"(d[50]), "+f"(d[51]), "+f"(d[52]), "+f"(d[53]), "+f"(d[54]), "+f"(d[55]), "+f"(d[56]), "+f"(d[57]), "+f"(d[58]), "+f"(d[59]), "+f"(d[60]), "+f"(d[61]), "+f"(d[62]), "+f"(d[63]), "+f"(d[64]), "+f"(d[65]), "+f"(d[66]), "+f"(d[67]), "+f"(d[68]), "+f"(d[69]), "+f"(d[70]), "+f"(d[71]), "+f"(d[72]), "+f"(d[73]), "+f"(d[74]), "+f"(d[75]), "+f"(d[76]), "+f"(d[77]), "+f"(d[78]), "+f"(d[79]), "+f"(d[80]), "+f"(d[81]), "+f"(d[82]), "+f"(d[83]), "+f"(d[84]), "+f"(d[85]), "+f"(d[86]), "+f"(d[87]), "+f"(d[88]), "+f"(d[89]), "+f"(d[90]), "+f"(d[91]), "+f"(d[92]), "+f"(d[93]), "+f"(d[94]), "+f"(d[95]), "+f"(d[96]), "+f"(d[97]), "+f"(d[98]), "+f"(d[99]), "+f"(d[100]), "+f"(d[101]), "+f"(d[102]), "+f"(d[103]), "+f"(d[104]), "+f"(d[105]), "+f"(d[106]), "+f"(d[107]), "+f"(d[108]), "+f"(d[109]), "+f"(d[110]), "+f"(d[111]), "+f"(d[112]), "+f"(d[113]), "+f"(d[114]), "+f"(d[115]), "+f"(d[116]), "+f"(d[117]), "+f"(d[118]), "+f"(d[119]), "+f"(d[120]), "+f"(d[121]), "+f"(d[122]), "+f"(d[123]), "+f"(d[124]), "+f"(d[125]), "+f"(d[126]), "+f"(d[127])
    : "l"(da), "l"(db), "r"(sc));
}
__device__ __forceinline__ void wgmma_ss_n192_tb(float (&d)[128], uint64_t da, uint64_t db, uint32_t sc) {
  asm volatile("{\n.reg .pred p;\nsetp.ne.b32 p, %98, 0;\n"
    "wgmma.mma_async.sync.aligned.m64n192k16.f32.bf16.bf16 "
    "{%0, %1, %2, %3, %4, %5, %6, %7, %8, %9, %10, %11, %12, %13, %14, %15, %16, %17, %18, %19, %20, %21, %22, %23, %24, %25, %26, %27, %28, %29, %30, %31, %32, %33, %34, %35, %36, %37, %38, %39, %40, %41, %42, %43, %44, %45, %46, %47, %48, %49, %50, %51, %52, %53, %54, %55, %56, %57, %58, %59, %60, %61, %62, %63, %64, %65, %66, %67, %68, %69, %70, %71, %72, %73, %74, %75, %76, %77, %78, %79, %80, %81, %82, %83, %84, %85, %86, %87, %88, %89, %90, %91, %92, %93, %94, %95}, %96, %97, p, 1, 1, 0, 1;\n}\n"
    : "+f"(d[0]), "+f"(d[1]), "+f"(d[2]), "+f"(d[3]), "+f"(d[4]), "+f"(d[5]), "+f"(d[6]), "+f"(d[7]), "+f"(d[8]), "+f"(d[9]), "+f"(d[10]), "+f"(d[11]), "+f"(d[12]), "+f"(d[13]), "+f"(d[14]), "+f"(d[15]), "+f"(d[16]), "+f"(d[17]), "+f"(d[18]), "+f"(d[19]), "+f"(d[20]), "+f"(d[21]), "+f"(d[22]), "+f"(d[23]), "+f"(d[24]), "+f"(d[25]), "+f"(d[26]), "+f"(d[27]), "+f"(d[28]), "+f"(d[29]), "+f"(d[30]), "+f"(d[31]), "+f"(d[32]), "+f"(d[33]), "+f"(d[34]), "+f"(d[35]), "+f"(d[36]), "+f"(d[37]), "+f"(d[38]), "+f"(d[39]), "+f"(d[40]), "+f"(d[41]), "+f"(d[42]), "+f"(d[43]), "+f"(d[44]), "+f"(d[45]), "+f"(d[46]), "+f"(d[47]), "+f"(d[48]), "+f"(d[49]), "+f"(d[50]), "+f"(d[51]), "+f"(d[52]), "+f"(d[53]), "+f"(d[54]), "+f"(d[55]), "+f"(d[56]), "+f"(d[57]), "+f"(d[58]), "+f"(d[59]), "+f"(d[60]), "+f"(d[61]), "+f"(d[62]), "+f"(d[63]), "+f"(d[64]), "+f"(d[65]), "+f"(d[66]), "+f"(d[67]), "+f"(d[68]), "+f"(d[69]), "+f"(d[70]), "+f"(d[71]), "+f"(d[72]), "+f"(d[73]), "+f"(d[74]), "+f"(d[75]), "+f"(d[76]), "+f"(d[77]), "+f"(d[78]), "+f"(d[79]), "+f"(d[80]), "+f"(d[81]), "+f"(d[82]), "+f"(d[83]), "+f"(d[84]), "+f"(d[85]), "+f"(d[86]), "+f"(d[87]), "+f"(d[88]), "+f"(d[89]), "+f"(d[90]), "+f"(d[91]), "+f"(d[92]), "+f"(d[93]), "+f"(d[94]), "+f"(d[95])
    : "l"(da), "l"(db), "r"(sc));
}
__device__ __forceinline__ void wgmma_rs_n128(float (&d)[64], uint32_t a0, uint32_t a1, uint32_t a2, uint32_t a3, uint64_t db, uint32_t sc) {
  asm volatile("{\n.reg .pred p;\nsetp.ne.b32 p, %69, 0;\n"
    "wgmma.mma_async.sync.aligned.m64n128k16.f32.bf16.bf16 "
    "{%0, %1, %2, %3, %4, %5, %6, %7, %8, %9, %10, %11, %12, %13, %14, %15, %16, %17, %18, %19, %20, %21, %22, %23, %24, %25, %26, %27, %28, %29, %30, %31, %32, %33, %34, %35, %36, %37, %38, %39, %40, %41, %42, %43, %44, %45, %46, %47, %48, %49, %50, %51, %52, %53, %54, %55, %56, %57, %58, %59, %60, %61, %62, %63}, {%64, %65, %66, %67}, %68, p, 1, 1, 0;\n}\n"
    : "+f"(d[0]), "+f"(d[1]), "+f"(d[2]), "+f"(d[3]), "+f"(d[4]), "+f"(d[5]), "+f"(d[6]), "+f"(d[7]), "+f"(d[8]), "+f"(d[9]), "+f"(d[10]), "+f"(d[11]), "+f"(d[12]), "+f"(d[13]), "+f"(d[14]), "+f"(d[15]), "+f"(d[16]), "+f"(d[17]), "+f"(d[18]), "+f"(d[19]), "+f"(d[20]), "+f"(d[21]), "+f"(d[22]), "+f"(d[23]), "+f"(d[24]), "+f"(d[25]), "+f"(d[26]), "+f"(d[27]), "+f"(d[28]), "+f"(d[29]), "+f"(d[30]), "+f"(d[31]), "+f"(d[32]), "+f"(d[33]), "+f"(d[34]), "+f"(d[35]), "+f"(d[36]), "+f"(d[37]), "+f"(d[38]), "+f"(d[39]), "+f"(d[40]), "+f"(d[41]), "+f"(d[42]), "+f"(d[43]), "+f"(d[44]), "+f"(d[45]), "+f"(d[46]), "+f"(d[47]), "+f"(d[48]), "+f"(d[49]), "+f"(d[50]), "+f"(d[51]), "+f"(d[52]), "+f"(d[53]), "+f"(d[54]), "+f"(d[55]), "+f"(d[56]), "+f"(d[57]), "+f"(d[58]), "+f"(d[59]), "+f"(d[60]), "+f"(d[61]), "+f"(d[62]), "+f"(d[63])
    : "r"(a0), "r"(a1), "r"(a2), "r"(a3), "l"(db), "r"(sc));
}
__device__ __forceinline__ void wgmma_rs_n128_tb(float (&d)[64], uint32_t a0, uint32_t a1, uint32_t a2, uint32_t a3, uint64_t db, uint32_t sc) {
  asm volatile("{\n.reg .pred p;\nsetp.ne.b32 p, %69, 0;\n"
    "wgmma.mma_async.sync.aligned.m64n128k16.f32.bf16.bf16 "
    "{%0, %1, %2, %3, %4, %5, %6, %7, %8, %9, %10, %11, %12, %13, %14, %15, %16, %17, %18, %19, %20, %21, %22, %23, %24, %25, %26, %27, %28, %29, %30, %31, %32, %33, %34, %35, %36, %37, %38, %39, %40, %41, %42, %43, %44, %45, %46, %47, %48, %49, %50, %51, %52, %53, %54, %55, %56, %57, %58, %59, %60, %61, %62, %63}, {%64, %65, %66, %67}, %68, p, 1, 1, 1;\n}\n"
    : "+f"(d[0]), "+f"(d[1]), "+f"(d[2]), "+f"(d[3]), "+f"(d[4]), "+f"(d[5]), "+f"(d[6]), "+f"(d[7]), "+f"(d[8]), "+f"(d[9]), "+f"(d[10]), "+f"(d[11]), "+f"(d[12]), "+f"(d[13]), "+f"(d[14]), "+f"(d[15]), "+f"(d[16]), "+f"(d[17]), "+f"(d[18]), "+f"(d[19]), "+f"(d[20]), "+f"(d[21]), "+f"(d[22]), "+f"(d[23]), "+f"(d[24]), "+f"(d[25]), "+f"(d[26]), "+f"(d[27]), "+f"(d[28]), "+f"(d[29]), "+f"(d[30]), "+f"(d[31]), "+f"(d[32]), "+f"(d[33]), "+f"(d[34]), "+f"(d[35]), "+f"(d[36]), "+f"(d[37]), "+f"(d[38]), "+f"(d[39]), "+f"(d[40]), "+f"(d[41]), "+f"(d[42]), "+f"(d[43]), "+f"(d[44]), "+f"(d[45]), "+f"(d[46]), "+f"(d[47]), "+f"(d[48]), "+f"(d[49]), "+f"(d[50]), "+f"(d[51]), "+f"(d[52]), "+f"(d[53]), "+f"(d[54]), "+f"(d[55]), "+f"(d[56]), "+f"(d[57]), "+f"(d[58]), "+f"(d[59]), "+f"(d[60]), "+f"(d[61]), "+f"(d[62]), "+f"(d[63])
    : "r"(a0), "r"(a1), "r"(a2), "r"(a3), "l"(db), "r"(sc));
}

#define TS(i) do {} while (0)
#define TR(j, i) do {} while (0)
#define TSS(i, c) do {} while (0)

__device__ __forceinline__ uint32_t wrap12(uint32_t p) { return p >= NSLOT ? p - NSLOT : p; }

struct Cons {
  uint32_t sb;
  uint32_t g, pos;
  uint32_t rel;
  uint32_t nstg;
  uint32_t zero;
  int wg, lane;
  __device__ __forceinline__ void wait_full(uint32_t gg) const { mbar_wait(sb + SM_BAR + B_FULL + (gg & 7) * 8, (gg >> 3) & 1); }
  __device__ __forceinline__ void release(uint32_t gg) const { if (lane < 2) mbar_arrive_cluster(rel + (gg & 7) * 8); }
  __device__ __forceinline__ void stg_acquire() { mbar_wait(sb + SM_BAR + B_SEMPTY + wg * 8, (nstg & 1) ^ 1); nstg++; }
  __device__ __forceinline__ void stg_publish() const {
    fence_async_smem();
    __syncwarp();
    if (lane == 0) mbar_arrive(sb + SM_BAR + B_SFULL + wg * 8);
  }
};

__device__ __forceinline__ void frag_addr(uint32_t& rowoff, uint32_t& xr) {
  const uint32_t t = tid_x();
  rowoff = ((t >> 5) & 3) * 2048 + (t & 15) * 128;
  xr = (((t >> 4) & 1) ^ (t & 7)) << 4;
}
template <int NB, int NR>
__device__ __forceinline__ void stage_boxes(const uint32_t (&r)[NR], int r0, const Cons& c) {
  uint32_t rowoff, xr;
  frag_addr(rowoff, xr);
  const uint32_t stg = c.sb + SM_STG + c.wg * 16384 + rowoff;
#pragma unroll
  for (int b = 0; b < NB; b++)
#pragma unroll
    for (int kb = 0; kb < 4; kb++)
      stsm4(stg + b * 8192 + ((32 * kb) ^ xr), r[r0 + b * 16 + kb * 4], r[r0 + b * 16 + kb * 4 + 1], r[r0 + b * 16 + kb * 4 + 2], r[r0 + b * 16 + kb * 4 + 3]);
  c.stg_publish();
}

template <int N, bool FIRST>
__device__ __forceinline__ void gemm_step(float (&acc)[128], Cons& c) {
  const uint32_t p1 = wrap12(c.pos + 1), p2 = wrap12(c.pos + 2);
  const uint64_t da = mkdesc(c.sb + c.wg * 8192 + c.pos * SLOT, 16, 1024);
  const uint64_t b0 = mkdesc(c.sb + p1 * SLOT, 4096, 1024);
  const uint64_t b1 = mkdesc(c.sb + p2 * SLOT, 4096, 1024);
  c.wait_full(c.g);
  wg_fence();
  if (N == 256) {
    wgmma_ss_n256_tb(acc, da, b0, FIRST ? 0 : 1);
    wgmma_ss_n256_tb(acc, da + 2, b0 + 128, 1);
    wgmma_ss_n256_tb(acc, da + 4, b1, 1);
    wgmma_ss_n256_tb(acc, da + 6, b1 + 128, 1);
  } else {
    wgmma_ss_n192_tb(acc, da, b0, FIRST ? 0 : 1);
    wgmma_ss_n192_tb(acc, da + 2, b0 + 128, 1);
    wgmma_ss_n192_tb(acc, da + 4, b1, 1);
    wgmma_ss_n192_tb(acc, da + 6, b1 + 128, 1);
  }
  wg_commit();
  if (!FIRST) {
    wg_wait<1>();
    c.release(c.g - 1);
  }
  c.g++;
  c.pos = wrap12(p2 + 1);
}

template <int N>
__device__ __forceinline__ void gemm_loop(float (&acc)[128], Cons& c, int nk) {
  gemm_step<N, true>(acc, c);
#pragma unroll 1
  for (int k = 1; k < nk; k++) gemm_step<N, false>(acc, c);
  wg_wait<0>();
  c.release(c.g - 1);
  fence_regs(acc);
}
template <int N, int NB>
__device__ __forceinline__ void gemm_loop_flush(float (&acc)[128], Cons& c, const uint32_t (&pend)[NB * 16], bool flush) {
  gemm_step<N, true>(acc, c);
#pragma unroll 1
  for (int k = 1; k < 16; k++) {
    gemm_step<N, false>(acc, c);
    if (k == 3 && flush) {
      c.stg_acquire();
      stage_boxes<NB>(pend, 0, c);
    }
  }
  wg_wait<0>();
  c.release(c.g - 1);
  fence_regs(acc);
}
template <int NB>
__device__ __forceinline__ void h_epilogue(const float (&acc)[128], Cons& c, uint32_t (&pend)[NB * 16]) {
  uint32_t r[32];
#pragma unroll
  for (int i = 0; i < 32; i++) r[i] = pack_bf16_relu(acc[2 * i], acc[2 * i + 1]);
  c.stg_acquire();
  stage_boxes<2>(r, 0, c);
#pragma unroll
  for (int i = 0; i < NB * 16; i++) pend[i] = pack_bf16_relu(acc[64 + 2 * i], acc[65 + 2 * i]);
}

__device__ __forceinline__ uint32_t silu2(float lo, float hi) {
  const uint32_t f2 = pack_bf16(lo, hi);
  const float a = bf_lo(f2), b = bf_hi(f2);
  const float ta = ex2(-1.4426950408889634f * fabsf(a)), tb = ex2(-1.4426950408889634f * fabsf(b));
  const float da = 1.0f + ta, db = 1.0f + tb;
  const float r = rcp(da * db);
  return pack_bf16((a >= 0.f ? a : a * ta) * (r * db), (b >= 0.f ? b : b * tb) * (r * da));
}

constexpr float SM_C = 0.08838834764831845f * 1.4426950408889634f;

#define ONCE(c) _Pragma("unroll 1") for (uint32_t once_ = 0; once_ <= (c).zero; once_++)
__device__ __forceinline__ void row_max2(const float (&S)[64], float& n0, float& n1) {
  float x[4], y[4];
#pragma unroll
  for (int i = 0; i < 4; i++) { x[i] = fmaxf(S[4 * i], S[4 * i + 1]); y[i] = fmaxf(S[4 * i + 2], S[4 * i + 3]); }
#pragma unroll
  for (int i = 4; i < 16; i++) {
    x[i & 3] = fmaxf(x[i & 3], fmaxf(S[4 * i], S[4 * i + 1]));
    y[i & 3] = fmaxf(y[i & 3], fmaxf(S[4 * i + 2], S[4 * i + 3]));
  }
  n0 = fmaxf(fmaxf(x[0], x[1]), fmaxf(x[2], x[3]));
  n1 = fmaxf(fmaxf(y[0], y[1]), fmaxf(y[2], y[3]));
  n0 = fmaxf(n0, __shfl_xor_sync(~0u, n0, 1));
  n1 = fmaxf(n1, __shfl_xor_sync(~0u, n1, 1));
  n0 = fmaxf(n0, __shfl_xor_sync(~0u, n0, 2));
  n1 = fmaxf(n1, __shfl_xor_sync(~0u, n1, 2));
}
__device__ __forceinline__ void to_exponent(float (&S)[64], float cc0, float cc1) {
#pragma unroll
  for (int i = 0; i < 16; i++) {
    S[4 * i] = fmaf(S[4 * i], SM_C, cc0); S[4 * i + 1] = fmaf(S[4 * i + 1], SM_C, cc0);
    S[4 * i + 2] = fmaf(S[4 * i + 2], SM_C, cc1); S[4 * i + 3] = fmaf(S[4 * i + 3], SM_C, cc1);
  }
}
__device__ __forceinline__ void scale_o(float (&O)[64], float f0, float f1) {
#pragma unroll
  for (int i = 0; i < 16; i++) { O[4 * i] *= f0; O[4 * i + 1] *= f0; O[4 * i + 2] *= f1; O[4 * i + 3] *= f1; }
}
template <int G0>
__device__ __forceinline__ void exp_pack(const float (&S)[64], uint32_t (&p)[32], float (&a)[4]) {
#pragma unroll
  for (int i = G0; i < 16; i++) {
    const float e0 = ex2(S[4 * i]), e1 = ex2(S[4 * i + 1]), e2 = ex2(S[4 * i + 2]), e3 = ex2(S[4 * i + 3]);
    a[0] += e0; a[1] += e1; a[2] += e2; a[3] += e3;
    p[2 * i] = pack_bf16(e0, e1);
    p[2 * i + 1] = pack_bf16(e2, e3);
  }
}
#define EARLY 4
__device__ __forceinline__ void softmax_early(float (&S)[64], float cc0, float cc1, float (&a)[4], uint32_t (&pe)[2 * EARLY + 1], const Cons& c) {
  a[0] = a[1] = a[2] = a[3] = 0.f;
  ONCE(c) {
    to_exponent(S, cc0, cc1);
#pragma unroll
    for (int i = 0; i < EARLY; i++) {
      const float e0 = ex2(S[4 * i]), e1 = ex2(S[4 * i + 1]), e2 = ex2(S[4 * i + 2]), e3 = ex2(S[4 * i + 3]);
      a[0] += e0; a[1] += e1; a[2] += e2; a[3] += e3;
      pe[2 * i] = pack_bf16(e0, e1);
      pe[2 * i + 1] = pack_bf16(e2, e3);
    }
  }
}
__device__ __forceinline__ void softmax_late(float (&S)[64], uint32_t (&p)[32], float (&O)[64], float& cc0, float& cc1, float& l0, float& l1,
                                             float (&a)[4], const uint32_t (&pe)[2 * EARLY + 1], uint32_t zero) {
#pragma unroll
  for (int i = 0; i < 2 * EARLY; i++) p[i] = pe[i] ^ zero;
  exp_pack<EARLY>(S, p, a);
  if (__any_sync(~0u, !(fmaxf(a[0] + a[1], a[2] + a[3]) <= 65536.f))) {
    float d0, d1;
    row_max2(S, d0, d1);
    d0 = fmaxf(d0, 0.f); d1 = fmaxf(d1, 0.f);
#pragma unroll
    for (int i = 0; i < 16; i++) { S[4 * i] -= d0; S[4 * i + 1] -= d0; S[4 * i + 2] -= d1; S[4 * i + 3] -= d1; }
    cc0 -= d0; cc1 -= d1;
    const float f0 = ex2(-d0), f1 = ex2(-d1);
    scale_o(O, f0, f1);
    l0 *= f0; l1 *= f1;
    a[0] = a[1] = a[2] = a[3] = 0.f;
    exp_pack<0>(S, p, a);
  }
  l0 += a[0] + a[1];
  l1 += a[2] + a[3];
}

__device__ __forceinline__ void inv_rowsum(float l0, float l1, float& i0, float& i1) {
  l0 += __shfl_xor_sync(~0u, l0, 1); l1 += __shfl_xor_sync(~0u, l1, 1);
  l0 += __shfl_xor_sync(~0u, l0, 2); l1 += __shfl_xor_sync(~0u, l1, 2);
  i0 = rcp(l0); i1 = rcp(l1);
}
__device__ __forceinline__ void write_o(const float (&O)[64], const Cons& c) {
  uint32_t rowoff, xr;
  frag_addr(rowoff, xr);
  const uint32_t stg = c.sb + SM_STG + c.wg * 16384 + rowoff;
#pragma unroll
  for (int kb = 0; kb < 8; kb++)
    stsm4(stg + (kb >> 2) * 8192 + ((32 * (kb & 3)) ^ xr),
          pack_bf16(O[8 * kb], O[8 * kb + 1]), pack_bf16(O[8 * kb + 2], O[8 * kb + 3]),
          pack_bf16(O[8 * kb + 4], O[8 * kb + 5]), pack_bf16(O[8 * kb + 6], O[8 * kb + 7]));
  c.stg_publish();
}

__device__ __forceinline__ void issue_qk(float (&S)[64], const uint32_t (&q)[32], uint32_t s0, uint32_t s1, uint32_t zero) {
  const uint64_t d0 = mkdesc(s0, 16, 1024), d1 = mkdesc(s1, 16, 1024);
#pragma unroll
  for (int kk = 0; kk < 8; kk++)
    wgmma_rs_n128(S, q[4 * kk], q[4 * kk + 1], q[4 * kk + 2], q[4 * kk + 3], (kk < 4 ? d0 : d1) + (kk & 3) * 2, kk > 0 ? 1u : zero);
}
__device__ __forceinline__ void issue_pv(float (&O)[64], const uint32_t (&p)[32], uint32_t s0, uint32_t s1, uint32_t accum) {
  const uint64_t d0 = mkdesc(s0, 8192, 1024), d1 = mkdesc(s1, 8192, 1024);
#pragma unroll
  for (int kk = 0; kk < 8; kk++)
    wgmma_rs_n128_tb(O, p[4 * kk], p[4 * kk + 1], p[4 * kk + 2], p[4 * kk + 3], (kk < 4 ? d0 : d1) + (kk & 3) * 128, kk > 0 ? 1u : accum);
}

#define TURN_SYNC()   bar_sync(1 + c.wg, 256)
#define TURN_PASS()   bar_arrive(2 - c.wg, 256)

__device__ __forceinline__ void attn_tile(const float (&acc)[128], Cons& c, int t) {
  uint32_t q[32], p[32];
  float S[64], O[64];
  const uint32_t stash = c.sb + SM_STG + c.wg * 16384 + ((threadIdx.x >> 5) & 3) * 2048 + c.lane * 16;
#pragma unroll
  for (int i = 0; i < 32; i++) q[i] = pack_bf16(acc[2 * i], acc[2 * i + 1]);
  c.stg_acquire();
#pragma unroll
  for (int i = 0; i < 8; i++)
    sts128(stash + (i >> 2) * 8192 + (i & 3) * 512, pack_bf16(acc[64 + 8 * i], acc[65 + 8 * i]), pack_bf16(acc[66 + 8 * i], acc[67 + 8 * i]),
           pack_bf16(acc[68 + 8 * i], acc[69 + 8 * i]), pack_bf16(acc[70 + 8 * i], acc[71 + 8 * i]));
  fence_regs(q);
  TR(0, 0);
  TURN_SYNC();
  TR(0, 1);
  c.wait_full(c.g);
  wg_fence();
  issue_qk(O, q, c.sb + c.pos * SLOT, c.sb + wrap12(c.pos + 1) * SLOT, 0);
  wg_commit();
  c.wait_full(c.g + 1);
  wg_fence();
  issue_qk(S, q, c.sb + wrap12(c.pos + 2) * SLOT, c.sb + wrap12(c.pos + 3) * SLOT, 0);
  wg_commit();
  TURN_PASS();
  TR(0, 2);
  wg_wait<1>();
  TR(0, 3);
  fence_regs(O);
  c.release(c.g);
  float cc0, cc1, l0, l1, f0 = 0.f, f1 = 0.f;
  float a[4] = {0.f, 0.f, 0.f, 0.f};
  uint32_t pe[2 * EARLY + 1];
  row_max2(O, cc0, cc1);
  cc0 *= -SM_C; cc1 *= -SM_C;
  ONCE(c) { to_exponent(O, cc0, cc1); }
  wg_wait<0>();
  fence_regs(S);
  fence_regs(q);
  c.release(c.g + 1);
  exp_pack<0>(O, p, a);
  l0 = a[0] + a[1];
  l1 = a[2] + a[3];
  c.pos = wrap12(c.pos + 4);
  TR(1, 0);
  TURN_SYNC();
  TR(1, 1);
  c.wait_full(c.g + 2);
  wg_fence();
  issue_pv(O, p, c.sb + c.pos * SLOT, c.sb + wrap12(c.pos + 1) * SLOT, 0);
  wg_commit();
  TURN_PASS();
  TR(1, 2);
  softmax_early(S, cc0, cc1, a, pe, c);
  TR(1, 4);
  wg_wait<0>();
  TR(1, 5);
  fence_regs(O);
  fence_regs(p);
  c.release(c.g + 2);
  c.g += 3;
  c.pos = wrap12(c.pos + 2);
  softmax_late(S, p, O, cc0, cc1, l0, l1, a, pe, c.zero);
#pragma unroll 1
  for (int j = 1; j < 7 + (int)c.zero; j++) {
    const uint32_t k0 = c.pos, k1 = wrap12(k0 + 1), v0 = wrap12(k0 + 2), v1 = wrap12(k0 + 3);
    TR(j + 1, 0);
    TURN_SYNC();
    TR(j + 1, 1);
    c.wait_full(c.g);
    wg_fence();
    issue_qk(S, q, c.sb + k0 * SLOT, c.sb + k1 * SLOT, 0);
    wg_commit();
    if (j == 4) {
      scale_o(O, f0, f1);
      write_o(O, c);
    }
    c.wait_full(c.g + 1);
    wg_fence();
    issue_pv(O, p, c.sb + v0 * SLOT, c.sb + v1 * SLOT, j != 4);
    wg_commit();
    TURN_PASS();
    TR(j + 1, 2);
    wg_wait<1>();
    TR(j + 1, 3);
    fence_regs(S);
    fence_regs(q);
    c.release(c.g);
    if (j == 3) {
      row_max2(S, cc0, cc1);
      cc0 *= -SM_C; cc1 *= -SM_C;
      inv_rowsum(l0, l1, f0, f1);
      l0 = 0.f; l1 = 0.f;
    }
    softmax_early(S, cc0, cc1, a, pe, c);
    if (j == 2) {
#pragma unroll
      for (int i = 0; i < 8; i++) lds128(stash + (i >> 2) * 8192 + (i & 3) * 512, q[4 * i], q[4 * i + 1], q[4 * i + 2], q[4 * i + 3]);
      __syncwarp();
    }
    TR(j + 1, 4);
    wg_wait<0>();
    TR(j + 1, 5);
    fence_regs(O);
    fence_regs(p);
    c.release(c.g + 1);
    c.g += 2;
    c.pos = wrap12(v1 + 1);
    softmax_late(S, p, O, cc0, cc1, l0, l1, a, pe, c.zero);
  }
  TR(8, 0);
  TURN_SYNC();
  TR(8, 1);
  c.wait_full(c.g);
  wg_fence();
  issue_pv(O, p, c.sb + c.pos * SLOT, c.sb + wrap12(c.pos + 1) * SLOT, 1);
  wg_commit();
  TURN_PASS();
  TR(8, 2);
  c.stg_acquire();
  float a0, a1;
  inv_rowsum(l0, l1, a0, a1);
  wg_wait<0>();
  TR(8, 5);
  fence_regs(O);
  fence_regs(p);
  c.release(c.g);
  c.g++;
  c.pos = wrap12(c.pos + 2);
  scale_o(O, a0, a1);
  write_o(O, c);
  TR(9, 0);
}

struct Prod {
  uint32_t sb, g, pos, head, tail_g, tail_pos, hist;
  __device__ __forceinline__ uint32_t full() const { return sb + SM_BAR + B_FULL + (g & 7) * 8; }
  __device__ __forceinline__ uint32_t slot(uint32_t i) const { return sb + wrap12(pos + i) * SLOT; }
  __device__ __forceinline__ void acquire(uint32_t size) {
#pragma unroll 1
    while (head + size - tail_pos > NSLOT) {
      mbar_wait(sb + SM_BAR + B_EMPTY + (tail_g & 7) * 8, (tail_g >> 3) & 1);
      tail_pos += 2 + ((hist >> (tail_g & 31)) & 1);
      tail_g++;
    }
    hist = (hist & ~(1u << (g & 31))) | ((size - 2) << (g & 31));
  }
  __device__ __forceinline__ void advance(uint32_t size) { g++; head += size; pos = wrap12(pos + size); }
};

__device__ __forceinline__ void wait_flag(const unsigned* p, unsigned target) {
  while ((int)(ld_acquire(p) - target) < 0) {}
  fence_async_all();
}

__device__ __forceinline__ void init_barriers(uint32_t sb, int warp) {
  const uint32_t cnt = warp < 4 ? 1 : warp < 8 ? 16 : warp == 8 ? 4 : warp == 9 ? 1 : 11;
  if (warp < 11) mbar_init(sb + SM_BAR + warp * 16, cnt);
  if (warp < 10) mbar_init(sb + SM_BAR + warp * 16 + 8, cnt);
  asm volatile("fence.mbarrier_init.release.cluster;" ::: "memory");
}

#define TSP(i) do {} while (0)

__global__ void __cluster_dims__(2, 1, 1) __launch_bounds__(384, 1) fused_kernel(const __grid_constant__ Params P) {
  extern __shared__ uint8_t smem_raw[];
  const uint32_t sb = (smem_u32(smem_raw) + 1023u) & ~1023u;
  const int warp = __shfl_sync(~0u, (int)(threadIdx.x >> 5), 0);
  const int lane = threadIdx.x & 31;
  const int rank = blockIdx.x & 1;
  const int cl = blockIdx.x >> 1;
  const int j = cl >> 3;
  const int rb = (cl & 7) * 2 + rank;
  const bool is_s = j < 4, spare = j == 8;
  const int row0 = rb * 128;
  Flags* fl = P.flags;

  if (warp >= 8) {
    unsigned ep0 = 0;
    if (warp == 8) asm volatile("ld.volatile.global.u32 %0, [%1];" : "=r"(ep0) : "l"(&fl->epoch[blockIdx.x]));
    if (lane == 0) {
      if (warp == 8) prefetch_map(spare ? &P.w1b4 : &P.w1b3);
      if (warp == 9) prefetch_map(&P.act_ld);
      init_barriers(sb, warp);
    }
    __syncwarp();
    cluster_arrive();
    if (warp == 10 && lane == 0) {
      prefetch_map(&P.act_st); prefetch_map(&P.wq); prefetch_map(&P.k_ld); prefetch_map(&P.v_ld);
      prefetch_map(is_s ? &P.wo : &P.w2); prefetch_map(&P.x_ld); prefetch_map(&P.out_st);
    }
    __syncwarp();
    cluster_wait();
    asm volatile("setmaxnreg.dec.sync.aligned.u32 24;");
    if (warp == 8) {
      TSP(17);
#define ep1 (ep0 + 1)
      Prod p{sb, 0, 0, 0, 0, 0, 0};
#define LDA(dst, m, bar, c0, c1) tma_ld2(dst, m, bar, c0, c1)
#define LDW1(dst, m, bar, c0, c1, c2) tma_ld3_mc(dst, m, bar, c0, c1, c2)
#define LDW(dst, m, bar, c0, c1, c2) tma_ld3_mc(dst, m, bar, c0, c1, c2)
      {
        const CUtensorMap* mb = spare ? &P.w1b4 : &P.w1b3;
        const uint32_t bytes = spare ? 49152 : 40960;
        const int nt = spare ? 8 : 2;
#pragma unroll 1
        for (int t = 0; t < nt; t++) {
          const int r = spare ? ((cl & 1) * 4 + (t >> 1)) * 2 + rank : rb;
          const int nb0 = spare ? (H_SPARE0 >> 6) + (t & 1) * 4 : j * 6 + t * 3;
          int k = 0;
          if (t == 0) {
#pragma unroll 1
            for (; k < 4; k++) {
              p.acquire(3);
              if (lane == 0) { mbar_expect_tx(p.full(), bytes); LDW1(p.slot(1 + rank), mb, p.full(), 0, k * 64 + rank * 32, nb0); }
              p.advance(3);
            }
            TSP(14);
            asm volatile("" : "+r"(ep0));
            wait_flag(&fl->ln[r][0], ep1 * 64);
            TSP(15);
            if (lane == 0)
              for (int i = 0; i < 4; i++) tma_ld2(sb + i * 3 * SLOT, &P.act_ld, sb + SM_BAR + B_FULL + i * 8, C_XN + i * 64, r * 128);
          } else if (spare && !(t & 1)) {
            wait_flag(&fl->ln[r][0], ep1 * 64);
          }
#pragma unroll 1
          for (; k < 16; k++) {
            p.acquire(3);
            if (lane == 0) {
              mbar_expect_tx(p.full(), bytes);
              LDW1(p.slot(1 + rank), mb, p.full(), 0, k * 64 + rank * 32, nb0);
              tma_ld2(p.slot(0), &P.act_ld, p.full(), C_XN + k * 64, r * 128);
            }
            p.advance(3);
          }
        }
      }
      if (!spare) {
        const int kvrow = (j >> 1) * SK + KV0;
#pragma unroll 1
        for (int t = 0; t < 2; t++) {
          const int nb0 = (4 * j + 2 * t) * 2;
#pragma unroll 1
          for (int k = 0; k < 16; k++) {
            p.acquire(3);
            if (lane == 0) {
              mbar_expect_tx(p.full(), 49152);
              LDW1(p.slot(1 + rank), &P.wq, p.full(), 0, k * 64 + rank * 32, nb0);
              tma_ld2(p.slot(0), &P.act_ld, p.full(), C_XN + k * 64, row0);
            }
            p.advance(3);
          }
#pragma unroll 1
          for (int i = 0; i < 16; i++) {
            const bool is_k = i == 0 || (i < 15 && (i & 1));
            const int ch = (is_k ? ((i + 1) >> 1) : (i == 15 ? 7 : (i >> 1) - 1)) & 3;
            p.acquire(2);
            if (lane == 0) {
              mbar_expect_tx(p.full(), 32768);
              if (is_k) tma_ld2_mc(p.slot(rank), &P.k_ld, p.full(), rank * 64, kvrow + ch * 128);
              else      tma_ld3_mc(p.slot(rank), &P.v_ld, p.full(), 0, kvrow + ch * 128 + rank * 64, 0);
            }
            p.advance(2);
            if (t == 1 && i == 8 && !is_s) wait_flag(&fl->h[rb][0], ep1 * 64);
          }
        }
        const int jn = j & 3;
        if (is_s) {
          unsigned ready = 0;
#pragma unroll 1
          for (int i = 0; i < 64; i++) {
            const int hi = i >> 1;
            const int head = 4 * ((hi & 15) >> 1) + (hi & 1) + ((hi >> 4) << 1);
            const int kc = head * 128 + (i & 1) * 64;
            p.acquire(3);
            if (lane == 0) { mbar_expect_tx(p.full(), 49152); LDW(p.slot(1 + rank), &P.wo, p.full(), 0, kc + rank * 32, jn * 4); }
            if (!((ready >> head) & 1)) {
              do { ready = __ballot_sync(~0u, (int)(ld_acquire(&fl->o[rb][lane]) - ep1 * 2) >= 0); } while (!((ready >> head) & 1));
              __syncwarp();
              fence_async_all();
            }
            if (lane == 0) LDA(p.slot(0), &P.act_ld, p.full(), C_O + kc, row0);
            p.advance(3);
          }
          bool g_ready = (int)(ld_acquire(&fl->g[rb][jn]) - ep1 * 4) >= 0;
#pragma unroll 1
          for (int i = 0; i < 4; i++) {
            p.acquire(2);
            if (i == 2) { TSP(20); if (g_ready) fence_async_all(); else wait_flag(&fl->g[rb][jn], ep1 * 4); TSP(21); }
            if (lane == 0) {
              mbar_expect_tx(p.full(), 32768);
              const CUtensorMap* m = i < 2 ? &P.x_ld : &P.act_ld;
              const int c0 = (i < 2 ? 0 : C_G) + jn * 256 + (i & 1) * 128;
              tma_ld2(p.slot(0), m, p.full(), c0, row0);
              tma_ld2(p.slot(1), m, p.full(), c0 + 64, row0);
            }
            p.advance(2);
          }
        } else {
#pragma unroll 1
          for (int k = 0; k < 56; k++) {
            p.acquire(3);
            if (lane == 0) { mbar_expect_tx(p.full(), 49152); LDW(p.slot(1 + rank), &P.w2, p.full(), 0, k * 64 + rank * 32, jn * 4); }
            if (k == H_SPARE0 / 64) wait_flag(&fl->h[rb][16], ep1 * 8);
            if (lane == 0) LDA(p.slot(0), &P.act_ld, p.full(), C_H + k * 64, row0);
            p.advance(3);
          }
        }
      }
      if (lane == 0) { *(volatile unsigned*)&fl->epoch[blockIdx.x] = ep1; mbar_arrive(sb + SM_BAR + B_DONE); }
    } else if (warp < 11) {
      const int wg = warp - 9;
      if (lane == 0) {
        const uint32_t stg = sb + SM_STG + wg * 16384;
        const int nev = spare ? 16 : is_s ? 8 : 10;
#pragma unroll 1
        for (int n = 0; n < nev; n++) {
          int col, row = row0, nbox = 2;
          unsigned* flag;
          if (spare) {
            const int r = ((cl & 1) * 4 + (n >> 2)) * 2 + rank;
            row = r * 128;
            col = C_H + H_SPARE0 + (n & 3) * 128;
            flag = &fl->h[r][16];
          } else if (n < 4) {
            col = C_H + j * H_REG + (n >> 1) * 192 + (n & 1) * 128;
            nbox = 2 - (n & 1);
            flag = &fl->h[rb][0];
          } else if (n < 8) {
            col = C_O + (4 * j + n - 4) * 128;
            flag = &fl->o[rb][4 * j + n - 4];
          } else {
            col = C_G + (j & 3) * 256 + (n - 8) * 128;
            flag = &fl->g[rb][j & 3];
          }
          mbar_wait(sb + SM_BAR + B_SFULL + wg * 8, n & 1);
          if (n == 9 && wg == 0) TSP(20);
          tma_st2(&P.act_st, stg, col, row + wg * 64);
          if (nbox == 2) tma_st2(&P.act_st, stg + 8192, col + 64, row + wg * 64);
          bulk_commit();
          bulk_wait_read0();
          mbar_arrive(sb + SM_BAR + B_SEMPTY + wg * 8);
          if (n == 9 && wg == 0) TSP(21);
          bulk_wait0();
          if (n == 9 && wg == 0) TSP(22);
          fence_async_all();
          red_release(flag, 1);
          if (n == 9 && wg == 0) TSP(23);
        }
        mbar_arrive(sb + SM_BAR + B_DONE);
      }
    } else {
      if (lane == 0) {
        const unsigned long long t0 = gtime();
        while (!mbar_try(sb + SM_BAR + B_DONE, 0)) {
          if (gtime() - t0 > 2000000000ull) __trap();
        }
      }
    }
    __syncwarp();
    cluster_arrive();
    cluster_wait();
  } else {
    const int wg = warp >> 2;
    TS(0);
    if (!spare) {
      const int r = row0 + j * 16 + warp * 2;
      uint32_t v[2][16];
#pragma unroll
      for (int a = 0; a < 2; a++)
#pragma unroll
        for (int i = 0; i < 4; i++)
          *(uint4*)&v[a][4 * i] = __ldg((const uint4*)(P.x + (size_t)(r + a) * DM + i * 256 + lane * 8));
      if (lane == 0) init_barriers(sb, warp);
      __syncwarp();
      cluster_arrive();
      float s[2], q[2];
#pragma unroll
      for (int a = 0; a < 2; a++) {
        float t0 = 0.f, t1 = 0.f;
#pragma unroll
        for (int i = 0; i < 16; i++) { t0 += bf_lo(v[a][i]); t1 += bf_hi(v[a][i]); }
        s[a] = t0 + t1;
      }
#pragma unroll
      for (int o = 16; o; o >>= 1) { s[0] += __shfl_xor_sync(~0u, s[0], o); s[1] += __shfl_xor_sync(~0u, s[1], o); }
#pragma unroll
      for (int a = 0; a < 2; a++) {
        s[a] *= 1.0f / DM;
        float t0 = 0.f, t1 = 0.f;
#pragma unroll
        for (int i = 0; i < 16; i++) {
          const float d0 = bf_lo(v[a][i]) - s[a], d1 = bf_hi(v[a][i]) - s[a];
          t0 = fmaf(d0, d0, t0); t1 = fmaf(d1, d1, t1);
        }
        q[a] = t0 + t1;
      }
#pragma unroll
      for (int o = 16; o; o >>= 1) { q[0] += __shfl_xor_sync(~0u, q[0], o); q[1] += __shfl_xor_sync(~0u, q[1], o); }
#pragma unroll
      for (int a = 0; a < 2; a++) {
        const uint32_t mb2 = pack_bf16(s[a], s[a]);
        const float inv = 1.0f / bf_round(sqrtf(bf_round(bf_round(q[a] * (1.0f / DM)) + 1e-5f)));
#pragma unroll
        for (int i = 0; i < 16; i++) {
          const __nv_bfloat162 d = __hsub2_rn(*(const __nv_bfloat162*)&v[a][i], *(const __nv_bfloat162*)&mb2);
          const uint32_t du = *(const uint32_t*)&d;
          v[a][i] = pack_bf16(bf_lo(du) * inv, bf_hi(du) * inv);
        }
#pragma unroll
        for (int i = 0; i < 4; i++)
          *(uint4*)(P.act + (size_t)(r + a) * ACT_W + C_XN + i * 256 + lane * 8) = *(const uint4*)&v[a][4 * i];
      }
      TS(11);
      fence_async_all();
      TS(12);
      __syncwarp();
      if (lane == 0) red_release(&fl->ln[rb][0], 1);
      TS(13);
    } else {
      if (lane == 0) init_barriers(sb, warp);
      __syncwarp();
      cluster_arrive();
    }
    cluster_wait();
    asm volatile("setmaxnreg.inc.sync.aligned.u32 240;");
    Cons c;
    c.zero = blockIdx.y; c.sb = sb; c.g = 0; c.pos = 0; c.nstg = 0; c.wg = wg; c.lane = lane;
    c.rel = mapa(sb + SM_BAR + B_EMPTY, lane & 1);
    float acc[128];
    TS(1);
    if (spare) {
      uint32_t pend[32];
#pragma unroll
      for (int i = 0; i < 32; i++) pend[i] = 0;
#pragma unroll 1
      for (int t = 0; t < 8; t++) {
        gemm_loop_flush<256, 2>(acc, c, pend, t > 0);
        h_epilogue<2>(acc, c, pend);
      }
      c.stg_acquire();
      stage_boxes<2>(pend, 0, c);
      TS(6);
    } else {
      if (wg == 1) bar_arrive(1, 256);
      {
        uint32_t pend[16];
#pragma unroll
        for (int i = 0; i < 16; i++) pend[i] = 0;
#pragma unroll 1
        for (int t = 0; t < 2; t++) {
          gemm_loop_flush<192, 1>(acc, c, pend, t > 0);
          h_epilogue<1>(acc, c, pend);
          TS(2 + t);
        }
        gemm_loop_flush<256, 1>(acc, c, pend, true);
      }
#pragma unroll 1
      for (int t = 0; t < 2; t++) {
        TS(8 + t);
        attn_tile(acc, c, t);
        TS(4 + t);
        gemm_loop<256>(acc, c, t == 0 ? 16 : is_s ? 64 : 56);
      }
      TS(6);
      if (is_s) {
        uint32_t rowoff, xr;
        frag_addr(rowoff, xr);
        const uint32_t x0 = c.pos;
#pragma unroll
        for (int b = 0; b < 4; b++) {
          if ((b & 1) == 0) { c.wait_full(c.g + (b >> 1)); c.wait_full(c.g + 2 + (b >> 1)); }
          if (b == 0) TS(22);
          if (b == 2) TS(23);
          const uint32_t xs = sb + wrap12(x0 + b) * SLOT + wg * 8192;
          const uint32_t sx = xs + rowoff, sg = sb + wrap12(wrap12(x0 + 4) + b) * SLOT + wg * 8192 + rowoff;
          uint32_t xv[16], gv[16];
#pragma unroll
          for (int kb = 0; kb < 4; kb++) {
            ldsm4(sx + ((32 * kb) ^ xr), xv[4 * kb], xv[4 * kb + 1], xv[4 * kb + 2], xv[4 * kb + 3]);
            ldsm4(sg + ((32 * kb) ^ xr), gv[4 * kb], gv[4 * kb + 1], gv[4 * kb + 2], gv[4 * kb + 3]);
          }
#pragma unroll
          for (int i = 0; i < 16; i++) {
            const uint32_t s2 = pack_bf16(acc[32 * b + 2 * i], acc[32 * b + 2 * i + 1]);
            const __nv_bfloat162 pr = __hmul2_rn(*(const __nv_bfloat162*)&s2, *(const __nv_bfloat162*)&gv[i]);
            const __nv_bfloat162 o = __hadd2_rn(*(const __nv_bfloat162*)&xv[i], pr);
            xv[i] = *(const uint32_t*)&o;
          }
#pragma unroll
          for (int kb = 0; kb < 4; kb++) stsm4(sx + ((32 * kb) ^ xr), xv[4 * kb], xv[4 * kb + 1], xv[4 * kb + 2], xv[4 * kb + 3]);
          if (b & 1) {
            fence_async_smem();
            bar_sync(3 + wg, 128);
            if ((threadIdx.x & 127) == 0) {
              tma_st2(&P.out_st, sb + wrap12(x0 + b - 1) * SLOT + wg * 8192, (j & 3) * 256 + b * 64 - 64, row0 + wg * 64);
              tma_st2(&P.out_st, xs, (j & 3) * 256 + b * 64, row0 + wg * 64);
              bulk_commit();
            }
          }
        }
        TS(24);
        if ((threadIdx.x & 127) == 0) bulk_wait_read0();
      } else {
#pragma unroll
        for (int hh = 0; hh < 2; hh++) {
          uint32_t r[32];
#pragma unroll
          for (int i = 0; i < 32; i++) r[i] = silu2(acc[64 * hh + 2 * i], acc[64 * hh + 2 * i + 1]);
          c.stg_acquire();
          stage_boxes<2>(r, 0, c);
          if (hh == 0) TS(22);
        }
      }
    }
    TS(7);
    __syncwarp();
    if (lane == 0) mbar_arrive(sb + SM_BAR + B_DONE);
    cluster_arrive();
    cluster_wait();
  }
}

typedef CUresult (*EncodeFn)(CUtensorMap*, CUtensorMapDataType, cuuint32_t, void*, const cuuint64_t*, const cuuint64_t*,
                             const cuuint32_t*, const cuuint32_t*, CUtensorMapInterleave, CUtensorMapSwizzle,
                             CUtensorMapL2promotion, CUtensorMapFloatOOBfill);

void map2d(EncodeFn enc, CUtensorMap* m, const void* base, uint64_t cols, uint64_t rows, uint32_t box_rows) {
  cuuint64_t dims[2] = {cols, rows};
  cuuint64_t strides[1] = {cols * 2};
  cuuint32_t box[2] = {64, box_rows};
  cuuint32_t es[2] = {1, 1};
  enc(m, CU_TENSOR_MAP_DATA_TYPE_BFLOAT16, 2, (void*)base, dims, strides, box, es, CU_TENSOR_MAP_INTERLEAVE_NONE,
      CU_TENSOR_MAP_SWIZZLE_128B, CU_TENSOR_MAP_L2_PROMOTION_L2_256B, CU_TENSOR_MAP_FLOAT_OOB_FILL_NONE);
}
void map3d(EncodeFn enc, CUtensorMap* m, const void* base, uint64_t cols, uint64_t rows, uint32_t box_rows, uint32_t box_blks) {
  cuuint64_t dims[3] = {64, rows, cols / 64};
  cuuint64_t strides[2] = {cols * 2, 128};
  cuuint32_t box[3] = {64, box_rows, box_blks};
  cuuint32_t es[3] = {1, 1, 1};
  enc(m, CU_TENSOR_MAP_DATA_TYPE_BFLOAT16, 3, (void*)base, dims, strides, box, es, CU_TENSOR_MAP_INTERLEAVE_NONE,
      CU_TENSOR_MAP_SWIZZLE_128B, CU_TENSOR_MAP_L2_PROMOTION_L2_256B, CU_TENSOR_MAP_FLOAT_OOB_FILL_NONE);
}

}

extern "C" void kernel_launch(void* const* d_in, const int* in_sizes, int n_in, void* d_out, int out_size) {
  (void)in_sizes; (void)n_in; (void)out_size;
  static EncodeFn enc = nullptr;
  static void* act = nullptr;
  static void* flags = nullptr;
  if (!enc) {
    void* fn = nullptr;
    cudaDriverEntryPointQueryResult qr;
    cudaGetDriverEntryPoint("cuTensorMapEncodeTiled", &fn, cudaEnableDefault, &qr);
    enc = (EncodeFn)fn;
    cudaGetSymbolAddress(&act, g_act);
    cudaGetSymbolAddress(&flags, g_flags);
    cudaFuncSetAttribute(fused_kernel, cudaFuncAttributeMaxDynamicSharedMemorySize, SMEM_BYTES);
  }
  Params P;
  map2d(enc, &P.act_ld, act, ACT_W, SEQ, 128);
  map2d(enc, &P.act_st, act, ACT_W, SEQ, 64);
  map2d(enc, &P.x_ld, d_in[0], DM, SEQ, 128);
  map2d(enc, &P.out_st, d_out, DM, SEQ, 64);
  map2d(enc, &P.k_ld, d_in[1], 128, 4 * SK, 128);
  map3d(enc, &P.v_ld, d_in[2], 128, 4 * SK, 64, 2);
  map3d(enc, &P.wq, d_in[3], NQ, DM, 32, 4);
  map3d(enc, &P.w1b4, d_in[6], DFF, DM, 32, 4);
  map3d(enc, &P.w1b3, d_in[6], DFF, DM, 32, 3);
  map3d(enc, &P.wo, d_in[4], DM, NQ, 32, 4);
  map3d(enc, &P.w2, d_in[7], DM, DFF, 32, 4);
  P.x = (const __nv_bfloat16*)d_in[0];
  P.act = (__nv_bfloat16*)act;
  P.flags = (Flags*)flags;
  fused_kernel<<<NCLUSTER * 2, 384, SMEM_BYTES>>>(P);
}
```

```cpp
#include <cuda_runtime.h>
#include <cuda_bf16.h>
#include <cuda.h>
#include <stdint.h>

namespace {

constexpr int SEQ    = 2048;
constexpr int DM     = 1024;
constexpr int NQ     = 4096;
constexpr int DFF    = 3584;
constexpr int SK     = 2048;
constexpr int WIN    = 512;
constexpr int KV0    = SK - WIN;
constexpr int C_XN = 0, C_O = 1024, C_H = 5120, C_G = 8704, ACT_W = 9728;

constexpr int H_REG = 384, H_SPARE0 = 8 * H_REG;
static_assert(H_SPARE0 + 512 == DFF, "H split");

constexpr int NSLOT = 12, SLOT = 16384, NBAR = 8;
constexpr int SM_STG = NSLOT * SLOT;
constexpr int SM_BAR = SM_STG + 2 * 16384;
constexpr int SMEM_BYTES = SM_BAR + 256 + 1024;
constexpr int B_FULL = 0, B_EMPTY = 64, B_SFULL = 128, B_SEMPTY = 144, B_DONE = 160;

constexpr int NCLUSTER = 66;

struct Flags {
  unsigned ln[16][32];
  unsigned h[16][32];
  unsigned o[16][32];
  unsigned g[16][32];
  unsigned epoch[160];
};
__device__ __nv_bfloat16 g_act[(size_t)SEQ * ACT_W];
__device__ Flags g_flags;

struct Params {
  CUtensorMap act_ld, act_st, x_ld, out_st, k_ld, v_ld, wq, w1b4, w1b3, wo, w2;
  const __nv_bfloat16* x;
  __nv_bfloat16* act;
  Flags* flags;
};

__device__ __forceinline__ uint32_t smem_u32(const void* p) { return (uint32_t)__cvta_generic_to_shared(p); }
__device__ __forceinline__ void mbar_init(uint32_t bar, uint32_t cnt) {
  asm volatile("mbarrier.init.shared::cta.b64 [%0], %1;" ::"r"(bar), "r"(cnt) : "memory");
}
__device__ __forceinline__ bool mbar_try(uint32_t bar, uint32_t parity) {
  uint32_t ok;
  asm volatile("{\n.reg .pred p;\nmbarrier.try_wait.parity.shared::cta.b64 p, [%1], %2;\nselp.u32 %0, 1, 0, p;\n}\n"
               : "=r"(ok) : "r"(bar), "r"(parity) : "memory");
  return ok;
}
__device__ __forceinline__ void mbar_wait(uint32_t bar, uint32_t parity) {
  asm volatile("{\n.reg .pred p;\nWAIT_%=:\nmbarrier.try_wait.parity.shared::cta.b64 p, [%0], %1;\n@p bra DONE_%=;\nbra WAIT_%=;\nDONE_%=:\n}\n"
               ::"r"(bar), "r"(parity) : "memory");
}
__device__ __forceinline__ void mbar_arrive(uint32_t bar) {
  asm volatile("mbarrier.arrive.shared::cta.b64 _, [%0];" ::"r"(bar) : "memory");
}
__device__ __forceinline__ void mbar_arrive_cluster(uint32_t cluster_addr) {
  asm volatile("mbarrier.arrive.shared::cluster.b64 _, [%0];" ::"r"(cluster_addr) : "memory");
}
__device__ __forceinline__ void mbar_expect_tx(uint32_t bar, uint32_t bytes) {
  asm volatile("mbarrier.arrive.expect_tx.shared::cta.b64 _, [%0], %1;" ::"r"(bar), "r"(bytes) : "memory");
}
__device__ __forceinline__ uint32_t mapa(uint32_t addr, uint32_t rank) {
  uint32_t r;
  asm("mapa.shared::cluster.u32 %0, %1, %2;" : "=r"(r) : "r"(addr), "r"(rank));
  return r;
}
__device__ __forceinline__ void cluster_arrive() { asm volatile("barrier.cluster.arrive.relaxed.aligned;" ::: "memory"); }
__device__ __forceinline__ void cluster_wait() { asm volatile("barrier.cluster.wait.acquire.aligned;" ::: "memory"); }
__device__ __forceinline__ void bar_sync(int id, int n) { asm volatile("bar.sync %0, %1;" ::"r"(id), "r"(n) : "memory"); }
__device__ __forceinline__ void bar_arrive(int id, int n) { asm volatile("bar.arrive %0, %1;" ::"r"(id), "r"(n) : "memory"); }
__device__ __forceinline__ void fence_async_smem() { asm volatile("fence.proxy.async.shared::cta;" ::: "memory"); }
__device__ __forceinline__ void fence_async_all() { asm volatile("fence.proxy.async.global;" ::: "memory"); }

__device__ __forceinline__ void tma_ld2(uint32_t dst, const CUtensorMap* m, uint32_t bar, int c0, int c1) {
  asm volatile("cp.async.bulk.tensor.2d.shared::cluster.global.mbarrier::complete_tx::bytes [%0], [%1, {%3, %4}], [%2];"
               ::"r"(dst), "l"(m), "r"(bar), "r"(c0), "r"(c1) : "memory");
}
__device__ __forceinline__ void tma_ld2_mc(uint32_t dst, const CUtensorMap* m, uint32_t bar, int c0, int c1) {
  asm volatile("cp.async.bulk.tensor.2d.shared::cluster.global.mbarrier::complete_tx::bytes.multicast::cluster [%0], [%1, {%3, %4}], [%2], %5;"
               ::"r"(dst), "l"(m), "r"(bar), "r"(c0), "r"(c1), "h"((uint16_t)3) : "memory");
}
__device__ __forceinline__ void tma_ld3_mc(uint32_t dst, const CUtensorMap* m, uint32_t bar, int c0, int c1, int c2) {
  asm volatile("cp.async.bulk.tensor.3d.shared::cluster.global.mbarrier::complete_tx::bytes.multicast::cluster [%0], [%1, {%3, %4, %5}], [%2], %6;"
               ::"r"(dst), "l"(m), "r"(bar), "r"(c0), "r"(c1), "r"(c2), "h"((uint16_t)3) : "memory");
}
__device__ __forceinline__ void tma_ld3_mc_hint(uint32_t dst, const CUtensorMap* m, uint32_t bar, int c0, int c1, int c2, uint64_t pol) {
  asm volatile("cp.async.bulk.tensor.3d.shared::cluster.global.mbarrier::complete_tx::bytes.multicast::cluster.L2::cache_hint [%0], [%1, {%3, %4, %5}], [%2], %6, %7;"
               ::"r"(dst), "l"(m), "r"(bar), "r"(c0), "r"(c1), "r"(c2), "h"((uint16_t)3), "l"(pol) : "memory");
}
__device__ __forceinline__ void tma_ld2_hint(uint32_t dst, const CUtensorMap* m, uint32_t bar, int c0, int c1, uint64_t pol) {
  asm volatile("cp.async.bulk.tensor.2d.shared::cluster.global.mbarrier::complete_tx::bytes.L2::cache_hint [%0], [%1, {%3, %4}], [%2], %5;"
               ::"r"(dst), "l"(m), "r"(bar), "r"(c0), "r"(c1), "l"(pol) : "memory");
}
__device__ __forceinline__ void tma_st2_hint(const CUtensorMap* m, uint32_t src, int c0, int c1, uint64_t pol) {
  asm volatile("cp.async.bulk.tensor.2d.global.shared::cta.bulk_group.L2::cache_hint [%0, {%2, %3}], [%1], %4;"
               ::"l"(m), "r"(src), "r"(c0), "r"(c1), "l"(pol) : "memory");
}
#define POL_FIRST 0x12F0000000000000ull
__device__ __forceinline__ uint64_t policy_evict_first() {
  uint64_t p;
  asm volatile("createpolicy.fractional.L2::evict_first.b64 %0, 1.0;" : "=l"(p));
  return p;
}
__device__ __forceinline__ void tma_st2(const CUtensorMap* m, uint32_t src, int c0, int c1) {
  asm volatile("cp.async.bulk.tensor.2d.global.shared::cta.bulk_group [%0, {%2, %3}], [%1];"
               ::"l"(m), "r"(src), "r"(c0), "r"(c1) : "memory");
}
__device__ __forceinline__ void tma_pf2(const CUtensorMap* m, int c0, int c1) {
  asm volatile("cp.async.bulk.prefetch.tensor.2d.L2.global [%0, {%1, %2}];" ::"l"(m), "r"(c0), "r"(c1) : "memory");
}
__device__ __forceinline__ void bulk_commit() { asm volatile("cp.async.bulk.commit_group;" ::: "memory"); }
__device__ __forceinline__ void bulk_wait_read0() { asm volatile("cp.async.bulk.wait_group.read 0;" ::: "memory"); }
__device__ __forceinline__ void bulk_wait0() { asm volatile("cp.async.bulk.wait_group 0;" ::: "memory"); }
__device__ __forceinline__ void prefetch_map(const CUtensorMap* m) {
  asm volatile("prefetch.tensormap [%0];" ::"l"(m) : "memory");
}
__device__ __forceinline__ unsigned ld_acquire(const unsigned* p) {
  unsigned v;
  asm volatile("ld.acquire.gpu.global.u32 %0, [%1];" : "=r"(v) : "l"(p) : "memory");
  return v;
}
__device__ __forceinline__ void red_release(unsigned* p, unsigned v) {
  asm volatile("red.release.gpu.global.add.u32 [%0], %1;" ::"l"(p), "r"(v) : "memory");
}
__device__ __forceinline__ void wg_fence() { asm volatile("wgmma.fence.sync.aligned;" ::: "memory"); }
__device__ __forceinline__ void wg_commit() { asm volatile("wgmma.commit_group.sync.aligned;" ::: "memory"); }
template <int N> __device__ __forceinline__ void wg_wait() { asm volatile("wgmma.wait_group.sync.aligned %0;" ::"n"(N) : "memory"); }
template <int N> __device__ __forceinline__ void fence_regs(float (&d)[N]) {
#pragma unroll
  for (int i = 0; i < N; i++) asm volatile("" : "+f"(d[i])::"memory");
}
template <int N> __device__ __forceinline__ void fence_regs(uint32_t (&d)[N]) {
#pragma unroll
  for (int i = 0; i < N; i++) asm volatile("" : "+r"(d[i])::"memory");
}
__device__ __forceinline__ uint64_t mkdesc(uint32_t addr, uint32_t lbo, uint32_t sbo) {
  return (uint64_t)((addr & 0x3FFFF) >> 4) | ((uint64_t)(lbo >> 4) << 16) | ((uint64_t)(sbo >> 4) << 32) | (1ull << 62);
}
__device__ __forceinline__ uint32_t pack_bf16(float lo, float hi) {
  uint32_t r;
  asm("cvt.rn.bf16x2.f32 %0, %1, %2;" : "=r"(r) : "f"(hi), "f"(lo));
  return r;
}
__device__ __forceinline__ uint32_t pack_bf16_relu(float lo, float hi) {
  uint32_t r;
  asm("cvt.rn.relu.bf16x2.f32 %0, %1, %2;" : "=r"(r) : "f"(hi), "f"(lo));
  return r;
}
__device__ __forceinline__ float bf_lo(uint32_t v) { return __uint_as_float(v << 16); }
__device__ __forceinline__ float bf_hi(uint32_t v) { return __uint_as_float(v & 0xFFFF0000u); }
__device__ __forceinline__ float bf_round(float v) { return __bfloat162float(__float2bfloat16_rn(v)); }
__device__ __forceinline__ float ex2(float x) {
  float r;
  asm("ex2.approx.ftz.f32 %0, %1;" : "=f"(r) : "f"(x));
  return r;
}
__device__ __forceinline__ float rcp(float x) {
  float r;
  asm("rcp.approx.ftz.f32 %0, %1;" : "=f"(r) : "f"(x));
  return r;
}
__device__ __forceinline__ uint32_t tid_x() {
  uint32_t t;
  asm volatile("mov.u32 %0, %%tid.x;" : "=r"(t));
  return t;
}
__device__ __forceinline__ void stsm4(uint32_t addr, uint32_t r0, uint32_t r1, uint32_t r2, uint32_t r3) {
  asm volatile("stmatrix.sync.aligned.m8n8.x4.shared.b16 [%0], {%1, %2, %3, %4};" ::"r"(addr), "r"(r0), "r"(r1), "r"(r2), "r"(r3) : "memory");
}
__device__ __forceinline__ void ldsm4(uint32_t addr, uint32_t& r0, uint32_t& r1, uint32_t& r2, uint32_t& r3) {
  asm volatile("ldmatrix.sync.aligned.m8n8.x4.shared.b16 {%0, %1, %2, %3}, [%4];" : "=r"(r0), "=r"(r1), "=r"(r2), "=r"(r3) : "r"(addr) : "memory");
}
__device__ __forceinline__ void sts128(uint32_t addr, uint32_t r0, uint32_t r1, uint32_t r2, uint32_t r3) {
  asm volatile("st.shared.v4.b32 [%0], {%1, %2, %3, %4};" ::"r"(addr), "r"(r0), "r"(r1), "r"(r2), "r"(r3) : "memory");
}
__device__ __forceinline__ void lds128(uint32_t addr, uint32_t& r0, uint32_t& r1, uint32_t& r2, uint32_t& r3) {
  asm volatile("ld.shared.v4.b32 {%0, %1, %2, %3}, [%4];" : "=r"(r0), "=r"(r1), "=r"(r2), "=r"(r3) : "r"(addr) : "memory");
}
__device__ __forceinline__ unsigned long long gtime() {
  unsigned long long t;
  asm volatile("mov.u64 %0, %globaltimer;" : "=l"(t));
  return t;
}

__device__ __forceinline__ void wgmma_ss_n256_tb(float (&d)[128], uint64_t da, uint64_t db, uint32_t sc) {
  asm volatile("{\n.reg .pred p;\nsetp.ne.b32 p, %130, 0;\n"
    "wgmma.mma_async.sync.aligned.m64n256k16.f32.bf16.bf16 "
    "{%0, %1, %2, %3, %4, %5, %6, %7, %8, %9, %10, %11, %12, %13, %14, %15, %16, %17, %18, %19, %20, %21, %22, %23, %24, %25, %26, %27, %28, %29, %30, %31, %32, %33, %34, %35, %36, %37, %38, %39, %40, %41, %42, %43, %44, %45, %46, %47, %48, %49, %50, %51, %52, %53, %54, %55, %56, %57, %58, %59, %60, %61, %62, %63, %64, %65, %66, %67, %68, %69, %70, %71, %72, %73, %74, %75, %76, %77, %78, %79, %80, %81, %82, %83, %84, %85, %86, %87, %88, %89, %90, %91, %92, %93, %94, %95, %96, %97, %98, %99, %100, %101, %102, %103, %104, %105, %106, %107, %108, %109, %110, %111, %112, %113, %114, %115, %116, %117, %118, %119, %120, %121, %122, %123, %124, %125, %126, %127}, %128, %129, p, 1, 1, 0, 1;\n}\n"
    : "+f"(d[0]), "+f"(d[1]), "+f"(d[2]), "+f"(d[3]), "+f"(d[4]), "+f"(d[5]), "+f"(d[6]), "+f"(d[7]), "+f"(d[8]), "+f"(d[9]), "+f"(d[10]), "+f"(d[11]), "+f"(d[12]), "+f"(d[13]), "+f"(d[14]), "+f"(d[15]), "+f"(d[16]), "+f"(d[17]), "+f"(d[18]), "+f"(d[19]), "+f"(d[20]), "+f"(d[21]), "+f"(d[22]), "+f"(d[23]), "+f"(d[24]), "+f"(d[25]), "+f"(d[26]), "+f"(d[27]), "+f"(d[28]), "+f"(d[29]), "+f"(d[30]), "+f"(d[31]), "+f"(d[32]), "+f"(d[33]), "+f"(d[34]), "+f"(d[35]), "+f"(d[36]), "+f"(d[37]), "+f"(d[38]), "+f"(d[39]), "+f"(d[40]), "+f"(d[41]), "+f"(d[42]), "+f"(d[43]), "+f"(d[44]), "+f"(d[45]), "+f"(d[46]), "+f"(d[47]), "+f"(d[48]), "+f"(d[49]), "+f"(d[50]), "+f"(d[51]), "+f"(d[52]), "+f"(d[53]), "+f"(d[54]), "+f"(d[55]), "+f"(d[56]), "+f"(d[57]), "+f"(d[58]), "+f"(d[59]), "+f"(d[60]), "+f"(d[61]), "+f"(d[62]), "+f"(d[63]), "+f"(d[64]), "+f"(d[65]), "+f"(d[66]), "+f"(d[67]), "+f"(d[68]), "+f"(d[69]), "+f"(d[70]), "+f"(d[71]), "+f"(d[72]), "+f"(d[73]), "+f"(d[74]), "+f"(d[75]), "+f"(d[76]), "+f"(d[77]), "+f"(d[78]), "+f"(d[79]), "+f"(d[80]), "+f"(d[81]), "+f"(d[82]), "+f"(d[83]), "+f"(d[84]), "+f"(d[85]), "+f"(d[86]), "+f"(d[87]), "+f"(d[88]), "+f"(d[89]), "+f"(d[90]), "+f"(d[91]), "+f"(d[92]), "+f"(d[93]), "+f"(d[94]), "+f"(d[95]), "+f"(d[96]), "+f"(d[97]), "+f"(d[98]), "+f"(d[99]), "+f"(d[100]), "+f"(d[101]), "+f"(d[102]), "+f"(d[103]), "+f"(d[104]), "+f"(d[105]), "+f"(d[106]), "+f"(d[107]), "+f"(d[108]), "+f"(d[109]), "+f"(d[110]), "+f"(d[111]), "+f"(d[112]), "+f"(d[113]), "+f"(d[114]), "+f"(d[115]), "+f"(d[116]), "+f"(d[117]), "+f"(d[118]), "+f"(d[119]), "+f"(d[120]), "+f"(d[121]), "+f"(d[122]), "+f"(d[123]), "+f"(d[124]), "+f"(d[125]), "+f"(d[126]), "+f"(d[127])
    : "l"(da), "l"(db), "r"(sc));
}
__device__ __forceinline__ void wgmma_ss_n192_tb(float (&d)[128], uint64_t da, uint64_t db, uint32_t sc) {
  asm volatile("{\n.reg .pred p;\nsetp.ne.b32 p, %98, 0;\n"
    "wgmma.mma_async.sync.aligned.m64n192k16.f32.bf16.bf16 "
    "{%0, %1, %2, %3, %4, %5, %6, %7, %8, %9, %10, %11, %12, %13, %14, %15, %16, %17, %18, %19, %20, %21, %22, %23, %24, %25, %26, %27, %28, %29, %30, %31, %32, %33, %34, %35, %36, %37, %38, %39, %40, %41, %42, %43, %44, %45, %46, %47, %48, %49, %50, %51, %52, %53, %54, %55, %56, %57, %58, %59, %60, %61, %62, %63, %64, %65, %66, %67, %68, %69, %70, %71, %72, %73, %74, %75, %76, %77, %78, %79, %80, %81, %82, %83, %84, %85, %86, %87, %88, %89, %90, %91, %92, %93, %94, %95}, %96, %97, p, 1, 1, 0, 1;\n}\n"
    : "+f"(d[0]), "+f"(d[1]), "+f"(d[2]), "+f"(d[3]), "+f"(d[4]), "+f"(d[5]), "+f"(d[6]), "+f"(d[7]), "+f"(d[8]), "+f"(d[9]), "+f"(d[10]), "+f"(d[11]), "+f"(d[12]), "+f"(d[13]), "+f"(d[14]), "+f"(d[15]), "+f"(d[16]), "+f"(d[17]), "+f"(d[18]), "+f"(d[19]), "+f"(d[20]), "+f"(d[21]), "+f"(d[22]), "+f"(d[23]), "+f"(d[24]), "+f"(d[25]), "+f"(d[26]), "+f"(d[27]), "+f"(d[28]), "+f"(d[29]), "+f"(d[30]), "+f"(d[31]), "+f"(d[32]), "+f"(d[33]), "+f"(d[34]), "+f"(d[35]), "+f"(d[36]), "+f"(d[37]), "+f"(d[38]), "+f"(d[39]), "+f"(d[40]), "+f"(d[41]), "+f"(d[42]), "+f"(d[43]), "+f"(d[44]), "+f"(d[45]), "+f"(d[46]), "+f"(d[47]), "+f"(d[48]), "+f"(d[49]), "+f"(d[50]), "+f"(d[51]), "+f"(d[52]), "+f"(d[53]), "+f"(d[54]), "+f"(d[55]), "+f"(d[56]), "+f"(d[57]), "+f"(d[58]), "+f"(d[59]), "+f"(d[60]), "+f"(d[61]), "+f"(d[62]), "+f"(d[63]), "+f"(d[64]), "+f"(d[65]), "+f"(d[66]), "+f"(d[67]), "+f"(d[68]), "+f"(d[69]), "+f"(d[70]), "+f"(d[71]), "+f"(d[72]), "+f"(d[73]), "+f"(d[74]), "+f"(d[75]), "+f"(d[76]), "+f"(d[77]), "+f"(d[78]), "+f"(d[79]), "+f"(d[80]), "+f"(d[81]), "+f"(d[82]), "+f"(d[83]), "+f"(d[84]), "+f"(d[85]), "+f"(d[86]), "+f"(d[87]), "+f"(d[88]), "+f"(d[89]), "+f"(d[90]), "+f"(d[91]), "+f"(d[92]), "+f"(d[93]), "+f"(d[94]), "+f"(d[95])
    : "l"(da), "l"(db), "r"(sc));
}
__device__ __forceinline__ void wgmma_rs_n128(float (&d)[64], uint32_t a0, uint32_t a1, uint32_t a2, uint32_t a3, uint64_t db, uint32_t sc) {
  asm volatile("{\n.reg .pred p;\nsetp.ne.b32 p, %69, 0;\n"
    "wgmma.mma_async.sync.aligned.m64n128k16.f32.bf16.bf16 "
    "{%0, %1, %2, %3, %4, %5, %6, %7, %8, %9, %10, %11, %12, %13, %14, %15, %16, %17, %18, %19, %20, %21, %22, %23, %24, %25, %26, %27, %28, %29, %30, %31, %32, %33, %34, %35, %36, %37, %38, %39, %40, %41, %42, %43, %44, %45, %46, %47, %48, %49, %50, %51, %52, %53, %54, %55, %56, %57, %58, %59, %60, %61, %62, %63}, {%64, %65, %66, %67}, %68, p, 1, 1, 0;\n}\n"
    : "+f"(d[0]), "+f"(d[1]), "+f"(d[2]), "+f"(d[3]), "+f"(d[4]), "+f"(d[5]), "+f"(d[6]), "+f"(d[7]), "+f"(d[8]), "+f"(d[9]), "+f"(d[10]), "+f"(d[11]), "+f"(d[12]), "+f"(d[13]), "+f"(d[14]), "+f"(d[15]), "+f"(d[16]), "+f"(d[17]), "+f"(d[18]), "+f"(d[19]), "+f"(d[20]), "+f"(d[21]), "+f"(d[22]), "+f"(d[23]), "+f"(d[24]), "+f"(d[25]), "+f"(d[26]), "+f"(d[27]), "+f"(d[28]), "+f"(d[29]), "+f"(d[30]), "+f"(d[31]), "+f"(d[32]), "+f"(d[33]), "+f"(d[34]), "+f"(d[35]), "+f"(d[36]), "+f"(d[37]), "+f"(d[38]), "+f"(d[39]), "+f"(d[40]), "+f"(d[41]), "+f"(d[42]), "+f"(d[43]), "+f"(d[44]), "+f"(d[45]), "+f"(d[46]), "+f"(d[47]), "+f"(d[48]), "+f"(d[49]), "+f"(d[50]), "+f"(d[51]), "+f"(d[52]), "+f"(d[53]), "+f"(d[54]), "+f"(d[55]), "+f"(d[56]), "+f"(d[57]), "+f"(d[58]), "+f"(d[59]), "+f"(d[60]), "+f"(d[61]), "+f"(d[62]), "+f"(d[63])
    : "r"(a0), "r"(a1), "r"(a2), "r"(a3), "l"(db), "r"(sc));
}
__device__ __forceinline__ void wgmma_rs_n128_tb(float (&d)[64], uint32_t a0, uint32_t a1, uint32_t a2, uint32_t a3, uint64_t db, uint32_t sc) {
  asm volatile("{\n.reg .pred p;\nsetp.ne.b32 p, %69, 0;\n"
    "wgmma.mma_async.sync.aligned.m64n128k16.f32.bf16.bf16 "
    "{%0, %1, %2, %3, %4, %5, %6, %7, %8, %9, %10, %11, %12, %13, %14, %15, %16, %17, %18, %19, %20, %21, %22, %23, %24, %25, %26, %27, %28, %29, %30, %31, %32, %33, %34, %35, %36, %37, %38, %39, %40, %41, %42, %43, %44, %45, %46, %47, %48, %49, %50, %51, %52, %53, %54, %55, %56, %57, %58, %59, %60, %61, %62, %63}, {%64, %65, %66, %67}, %68, p, 1, 1, 1;\n}\n"
    : "+f"(d[0]), "+f"(d[1]), "+f"(d[2]), "+f"(d[3]), "+f"(d[4]), "+f"(d[5]), "+f"(d[6]), "+f"(d[7]), "+f"(d[8]), "+f"(d[9]), "+f"(d[10]), "+f"(d[11]), "+f"(d[12]), "+f"(d[13]), "+f"(d[14]), "+f"(d[15]), "+f"(d[16]), "+f"(d[17]), "+f"(d[18]), "+f"(d[19]), "+f"(d[20]), "+f"(d[21]), "+f"(d[22]), "+f"(d[23]), "+f"(d[24]), "+f"(d[25]), "+f"(d[26]), "+f"(d[27]), "+f"(d[28]), "+f"(d[29]), "+f"(d[30]), "+f"(d[31]), "+f"(d[32]), "+f"(d[33]), "+f"(d[34]), "+f"(d[35]), "+f"(d[36]), "+f"(d[37]), "+f"(d[38]), "+f"(d[39]), "+f"(d[40]), "+f"(d[41]), "+f"(d[42]), "+f"(d[43]), "+f"(d[44]), "+f"(d[45]), "+f"(d[46]), "+f"(d[47]), "+f"(d[48]), "+f"(d[49]), "+f"(d[50]), "+f"(d[51]), "+f"(d[52]), "+f"(d[53]), "+f"(d[54]), "+f"(d[55]), "+f"(d[56]), "+f"(d[57]), "+f"(d[58]), "+f"(d[59]), "+f"(d[60]), "+f"(d[61]), "+f"(d[62]), "+f"(d[63])
    : "r"(a0), "r"(a1), "r"(a2), "r"(a3), "l"(db), "r"(sc));
}

#define TS(i) do {} while (0)
#define TR(j, i) do {} while (0)
#define TSS(i, c) do {} while (0)

__device__ __forceinline__ uint32_t wrap12(uint32_t p) { return p >= NSLOT ? p - NSLOT : p; }

struct Cons {
  uint32_t sb;
  uint32_t g, pos;
  uint32_t rel;
  uint32_t nstg;
  uint32_t zero;
  int wg, lane;
  __device__ __forceinline__ void wait_full(uint32_t gg) const { mbar_wait(sb + SM_BAR + B_FULL + (gg & 7) * 8, (gg >> 3) & 1); }
  __device__ __forceinline__ void release(uint32_t gg) const { if (lane < 2) mbar_arrive_cluster(rel + (gg & 7) * 8); }
  __device__ __forceinline__ void stg_acquire() { mbar_wait(sb + SM_BAR + B_SEMPTY + wg * 8, (nstg & 1) ^ 1); nstg++; }
  __device__ __forceinline__ void stg_publish() const {
    fence_async_smem();
    __syncwarp();
    if (lane == 0) mbar_arrive(sb + SM_BAR + B_SFULL + wg * 8);
  }
};

__device__ __forceinline__ void frag_addr(uint32_t& rowoff, uint32_t& xr) {
  const uint32_t t = tid_x();
  rowoff = ((t >> 5) & 3) * 2048 + (t & 15) * 128;
  xr = (((t >> 4) & 1) ^ (t & 7)) << 4;
}
template <int NB, int NR>
__device__ __forceinline__ void stage_boxes(const uint32_t (&r)[NR], int r0, const Cons& c) {
  uint32_t rowoff, xr;
  frag_addr(rowoff, xr);
  const uint32_t stg = c.sb + SM_STG + c.wg * 16384 + rowoff;
#pragma unroll
  for (int b = 0; b < NB; b++)
#pragma unroll
    for (int kb = 0; kb < 4; kb++)
      stsm4(stg + b * 8192 + ((32 * kb) ^ xr), r[r0 + b * 16 + kb * 4], r[r0 + b * 16 + kb * 4 + 1], r[r0 + b * 16 + kb * 4 + 2], r[r0 + b * 16 + kb * 4 + 3]);
  c.stg_publish();
}

template <int N, bool FIRST>
__device__ __forceinline__ void gemm_step(float (&acc)[128], Cons& c) {
  const uint32_t p1 = wrap12(c.pos + 1), p2 = wrap12(c.pos + 2);
  const uint64_t da = mkdesc(c.sb + c.wg * 8192 + c.pos * SLOT, 16, 1024);
  const uint64_t b0 = mkdesc(c.sb + p1 * SLOT, 4096, 1024);
  const uint64_t b1 = mkdesc(c.sb + p2 * SLOT, 4096, 1024);
  c.wait_full(c.g);
  wg_fence();
  if (N == 256) {
    wgmma_ss_n256_tb(acc, da, b0, FIRST ? 0 : 1);
    wgmma_ss_n256_tb(acc, da + 2, b0 + 128, 1);
    wgmma_ss_n256_tb(acc, da + 4, b1, 1);
    wgmma_ss_n256_tb(acc, da + 6, b1 + 128, 1);
  } else {
    wgmma_ss_n192_tb(acc, da, b0, FIRST ? 0 : 1);
    wgmma_ss_n192_tb(acc, da + 2, b0 + 128, 1);
    wgmma_ss_n192_tb(acc, da + 4, b1, 1);
    wgmma_ss_n192_tb(acc, da + 6, b1 + 128, 1);
  }
  wg_commit();
  if (!FIRST) {
    wg_wait<1>();
    c.release(c.g - 1);
  }
  c.g++;
  c.pos = wrap12(p2 + 1);
}

template <int N>
__device__ __forceinline__ void gemm_loop(float (&acc)[128], Cons& c, int nk) {
  gemm_step<N, true>(acc, c);
#pragma unroll 1
  for (int k = 1; k < nk; k++) gemm_step<N, false>(acc, c);
  wg_wait<0>();
  c.release(c.g - 1);
  fence_regs(acc);
}
template <int N, int NB>
__device__ __forceinline__ void gemm_loop_flush(float (&acc)[128], Cons& c, const uint32_t (&pend)[NB * 16], bool flush) {
  gemm_step<N, true>(acc, c);
#pragma unroll 1
  for (int k = 1; k < 16; k++) {
    gemm_step<N, false>(acc, c);
    if (k == 3 && flush) {
      c.stg_acquire();
      stage_boxes<NB>(pend, 0, c);
    }
  }
  wg_wait<0>();
  c.release(c.g - 1);
  fence_regs(acc);
}
template <int NB>
__device__ __forceinline__ void h_epilogue(const float (&acc)[128], Cons& c, uint32_t (&pend)[NB * 16]) {
  uint32_t r[32];
#pragma unroll
  for (int i = 0; i < 32; i++) r[i] = pack_bf16_relu(acc[2 * i], acc[2 * i + 1]);
  c.stg_acquire();
  stage_boxes<2>(r, 0, c);
#pragma unroll
  for (int i = 0; i < NB * 16; i++) pend[i] = pack_bf16_relu(acc[64 + 2 * i], acc[65 + 2 * i]);
}

__device__ __forceinline__ uint32_t silu2(float lo, float hi) {
  const uint32_t f2 = pack_bf16(lo, hi);
  const float a = bf_lo(f2), b = bf_hi(f2);
  const float ta = ex2(-1.4426950408889634f * fabsf(a)), tb = ex2(-1.4426950408889634f * fabsf(b));
  const float da = 1.0f + ta, db = 1.0f + tb;
  const float r = rcp(da * db);
  return pack_bf16((a >= 0.f ? a : a * ta) * (r * db), (b >= 0.f ? b : b * tb) * (r * da));
}

constexpr float SM_C = 0.08838834764831845f * 1.4426950408889634f;

#define ONCE(c) _Pragma("unroll 1") for (uint32_t once_ = 0; once_ <= (c).zero; once_++)
__device__ __forceinline__ void row_max2(const float (&S)[64], float& n0, float& n1) {
  float x[4], y[4];
#pragma unroll
  for (int i = 0; i < 4; i++) { x[i] = fmaxf(S[4 * i], S[4 * i + 1]); y[i] = fmaxf(S[4 * i + 2], S[4 * i + 3]); }
#pragma unroll
  for (int i = 4; i < 16; i++) {
    x[i & 3] = fmaxf(x[i & 3], fmaxf(S[4 * i], S[4 * i + 1]));
    y[i & 3] = fmaxf(y[i & 3], fmaxf(S[4 * i + 2], S[4 * i + 3]));
  }
  n0 = fmaxf(fmaxf(x[0], x[1]), fmaxf(x[2], x[3]));
  n1 = fmaxf(fmaxf(y[0], y[1]), fmaxf(y[2], y[3]));
  n0 = fmaxf(n0, __shfl_xor_sync(~0u, n0, 1));
  n1 = fmaxf(n1, __shfl_xor_sync(~0u, n1, 1));
  n0 = fmaxf(n0, __shfl_xor_sync(~0u, n0, 2));
  n1 = fmaxf(n1, __shfl_xor_sync(~0u, n1, 2));
}
__device__ __forceinline__ void to_exponent(float (&S)[64], float cc0, float cc1) {
#pragma unroll
  for (int i = 0; i < 16; i++) {
    S[4 * i] = fmaf(S[4 * i], SM_C, cc0); S[4 * i + 1] = fmaf(S[4 * i + 1], SM_C, cc0);
    S[4 * i + 2] = fmaf(S[4 * i + 2], SM_C, cc1); S[4 * i + 3] = fmaf(S[4 * i + 3], SM_C, cc1);
  }
}
__device__ __forceinline__ void scale_o(float (&O)[64], float f0, float f1) {
#pragma unroll
  for (int i = 0; i < 16; i++) { O[4 * i] *= f0; O[4 * i + 1] *= f0; O[4 * i + 2] *= f1; O[4 * i + 3] *= f1; }
}
template <int G0>
__device__ __forceinline__ void exp_pack(const float (&S)[64], uint32_t (&p)[32], float (&a)[4]) {
#pragma unroll
  for (int i = G0; i < 16; i++) {
    const float e0 = ex2(S[4 * i]), e1 = ex2(S[4 * i + 1]), e2 = ex2(S[4 * i + 2]), e3 = ex2(S[4 * i + 3]);
    a[0] += e0; a[1] += e1; a[2] += e2; a[3] += e3;
    p[2 * i] = pack_bf16(e0, e1);
    p[2 * i + 1] = pack_bf16(e2, e3);
  }
}
#define EARLY 4
__device__ __forceinline__ void softmax_early(float (&S)[64], float cc0, float cc1, float (&a)[4], uint32_t (&pe)[2 * EARLY + 1], const Cons& c) {
  a[0] = a[1] = a[2] = a[3] = 0.f;
  ONCE(c) {
    to_exponent(S, cc0, cc1);
#pragma unroll
    for (int i = 0; i < EARLY; i++) {
      const float e0 = ex2(S[4 * i]), e1 = ex2(S[4 * i + 1]), e2 = ex2(S[4 * i + 2]), e3 = ex2(S[4 * i + 3]);
      a[0] += e0; a[1] += e1; a[2] += e2; a[3] += e3;
      pe[2 * i] = pack_bf16(e0, e1);
      pe[2 * i + 1] = pack_bf16(e2, e3);
    }
  }
}
__device__ __forceinline__ void softmax_late(float (&S)[64], uint32_t (&p)[32], float (&O)[64], float& cc0, float& cc1, float& l0, float& l1,
                                             float (&a)[4], const uint32_t (&pe)[2 * EARLY + 1], uint32_t zero) {
#pragma unroll
  for (int i = 0; i < 2 * EARLY; i++) p[i] = pe[i] ^ zero;
  exp_pack<EARLY>(S, p, a);
  if (__any_sync(~0u, !(fmaxf(a[0] + a[1], a[2] + a[3]) <= 65536.f))) {
    float d0, d1;
    row_max2(S, d0, d1);
    d0 = fmaxf(d0, 0.f); d1 = fmaxf(d1, 0.f);
#pragma unroll
    for (int i = 0; i < 16; i++) { S[4 * i] -= d0; S[4 * i + 1] -= d0; S[4 * i + 2] -= d1; S[4 * i + 3] -= d1; }
    cc0 -= d0; cc1 -= d1;
    const float f0 = ex2(-d0), f1 = ex2(-d1);
    scale_o(O, f0, f1);
    l0 *= f0; l1 *= f1;
    a[0] = a[1] = a[2] = a[3] = 0.f;
    exp_pack<0>(S, p, a);
  }
  l0 += a[0] + a[1];
  l1 += a[2] + a[3];
}

__device__ __forceinline__ void inv_rowsum(float l0, float l1, float& i0, float& i1) {
  l0 += __shfl_xor_sync(~0u, l0, 1); l1 += __shfl_xor_sync(~0u, l1, 1);
  l0 += __shfl_xor_sync(~0u, l0, 2); l1 += __shfl_xor_sync(~0u, l1, 2);
  i0 = rcp(l0); i1 = rcp(l1);
}
__device__ __forceinline__ void write_o(const float (&O)[64], const Cons& c) {
  uint32_t rowoff, xr;
  frag_addr(rowoff, xr);
  const uint32_t stg = c.sb + SM_STG + c.wg * 16384 + rowoff;
#pragma unroll
  for (int kb = 0; kb < 8; kb++)
    stsm4(stg + (kb >> 2) * 8192 + ((32 * (kb & 3)) ^ xr),
          pack_bf16(O[8 * kb], O[8 * kb + 1]), pack_bf16(O[8 * kb + 2], O[8 * kb + 3]),
          pack_bf16(O[8 * kb + 4], O[8 * kb + 5]), pack_bf16(O[8 * kb + 6], O[8 * kb + 7]));
  c.stg_publish();
}

__device__ __forceinline__ void issue_qk(float (&S)[64], const uint32_t (&q)[32], uint32_t s0, uint32_t s1, uint32_t zero) {
  const uint64_t d0 = mkdesc(s0, 16, 1024), d1 = mkdesc(s1, 16, 1024);
#pragma unroll
  for (int kk = 0; kk < 8; kk++)
    wgmma_rs_n128(S, q[4 * kk], q[4 * kk + 1], q[4 * kk + 2], q[4 * kk + 3], (kk < 4 ? d0 : d1) + (kk & 3) * 2, kk > 0 ? 1u : zero);
}
__device__ __forceinline__ void issue_pv(float (&O)[64], const uint32_t (&p)[32], uint32_t s0, uint32_t s1, uint32_t accum) {
  const uint64_t d0 = mkdesc(s0, 8192, 1024), d1 = mkdesc(s1, 8192, 1024);
#pragma unroll
  for (int kk = 0; kk < 8; kk++)
    wgmma_rs_n128_tb(O, p[4 * kk], p[4 * kk + 1], p[4 * kk + 2], p[4 * kk + 3], (kk < 4 ? d0 : d1) + (kk & 3) * 128, kk > 0 ? 1u : accum);
}

#define TURN_SYNC()   bar_sync(1 + c.wg, 256)
#define TURN_PASS()   bar_arrive(2 - c.wg, 256)

__device__ __forceinline__ void attn_tile(const float (&acc)[128], Cons& c, int t) {
  uint32_t q[32], p[32];
  float S[64], O[64];
  const uint32_t stash = c.sb + SM_STG + c.wg * 16384 + ((threadIdx.x >> 5) & 3) * 2048 + c.lane * 16;
#pragma unroll
  for (int i = 0; i < 32; i++) q[i] = pack_bf16(acc[2 * i], acc[2 * i + 1]);
  c.stg_acquire();
#pragma unroll
  for (int i = 0; i < 8; i++)
    sts128(stash + (i >> 2) * 8192 + (i & 3) * 512, pack_bf16(acc[64 + 8 * i], acc[65 + 8 * i]), pack_bf16(acc[66 + 8 * i], acc[67 + 8 * i]),
           pack_bf16(acc[68 + 8 * i], acc[69 + 8 * i]), pack_bf16(acc[70 + 8 * i], acc[71 + 8 * i]));
  fence_regs(q);
  TR(0, 0);
  TURN_SYNC();
  TR(0, 1);
  c.wait_full(c.g);
  wg_fence();
  issue_qk(O, q, c.sb + c.pos * SLOT, c.sb + wrap12(c.pos + 1) * SLOT, 0);
  wg_commit();
  c.wait_full(c.g + 1);
  wg_fence();
  issue_qk(S, q, c.sb + wrap12(c.pos + 2) * SLOT, c.sb + wrap12(c.pos + 3) * SLOT, 0);
  wg_commit();
  TURN_PASS();
  TR(0, 2);
  wg_wait<1>();
  TR(0, 3);
  fence_regs(O);
  c.release(c.g);
  float cc0, cc1, l0, l1, f0 = 0.f, f1 = 0.f;
  float a[4] = {0.f, 0.f, 0.f, 0.f};
  uint32_t pe[2 * EARLY + 1];
  row_max2(O, cc0, cc1);
  cc0 *= -SM_C; cc1 *= -SM_C;
  ONCE(c) { to_exponent(O, cc0, cc1); }
  wg_wait<0>();
  fence_regs(S);
  fence_regs(q);
  c.release(c.g + 1);
  exp_pack<0>(O, p, a);
  l0 = a[0] + a[1];
  l1 = a[2] + a[3];
  c.pos = wrap12(c.pos + 4);
  TR(1, 0);
  TURN_SYNC();
  TR(1, 1);
  c.wait_full(c.g + 2);
  wg_fence();
  issue_pv(O, p, c.sb + c.pos * SLOT, c.sb + wrap12(c.pos + 1) * SLOT, 0);
  wg_commit();
  TURN_PASS();
  TR(1, 2);
  softmax_early(S, cc0, cc1, a, pe, c);
  TR(1, 4);
  wg_wait<0>();
  TR(1, 5);
  fence_regs(O);
  fence_regs(p);
  c.release(c.g + 2);
  c.g += 3;
  c.pos = wrap12(c.pos + 2);
  softmax_late(S, p, O, cc0, cc1, l0, l1, a, pe, c.zero);
#pragma unroll 1
  for (int j = 1; j < 7 + (int)c.zero; j++) {
    const uint32_t k0 = c.pos, k1 = wrap12(k0 + 1), v0 = wrap12(k0 + 2), v1 = wrap12(k0 + 3);
    TR(j + 1, 0);
    TURN_SYNC();
    TR(j + 1, 1);
    c.wait_full(c.g);
    wg_fence();
    issue_qk(S, q, c.sb + k0 * SLOT, c.sb + k1 * SLOT, 0);
    wg_commit();
    if (j == 4) {
      scale_o(O, f0, f1);
      write_o(O, c);
    }
    c.wait_full(c.g + 1);
    wg_fence();
    issue_pv(O, p, c.sb + v0 * SLOT, c.sb + v1 * SLOT, j != 4);
    wg_commit();
    TURN_PASS();
    TR(j + 1, 2);
    wg_wait<1>();
    TR(j + 1, 3);
    fence_regs(S);
    fence_regs(q);
    c.release(c.g);
    if (j == 3) {
      row_max2(S, cc0, cc1);
      cc0 *= -SM_C; cc1 *= -SM_C;
      inv_rowsum(l0, l1, f0, f1);
      l0 = 0.f; l1 = 0.f;
    }
    softmax_early(S, cc0, cc1, a, pe, c);
    if (j == 2) {
#pragma unroll
      for (int i = 0; i < 8; i++) lds128(stash + (i >> 2) * 8192 + (i & 3) * 512, q[4 * i], q[4 * i + 1], q[4 * i + 2], q[4 * i + 3]);
      __syncwarp();
    }
    TR(j + 1, 4);
    wg_wait<0>();
    TR(j + 1, 5);
    fence_regs(O);
    fence_regs(p);
    c.release(c.g + 1);
    c.g += 2;
    c.pos = wrap12(v1 + 1);
    softmax_late(S, p, O, cc0, cc1, l0, l1, a, pe, c.zero);
  }
  TR(8, 0);
  TURN_SYNC();
  TR(8, 1);
  c.wait_full(c.g);
  wg_fence();
  issue_pv(O, p, c.sb + c.pos * SLOT, c.sb + wrap12(c.pos + 1) * SLOT, 1);
  wg_commit();
  TURN_PASS();
  TR(8, 2);
  c.stg_acquire();
  float a0, a1;
  inv_rowsum(l0, l1, a0, a1);
  wg_wait<0>();
  TR(8, 5);
  fence_regs(O);
  fence_regs(p);
  c.release(c.g);
  c.g++;
  c.pos = wrap12(c.pos + 2);
  scale_o(O, a0, a1);
  write_o(O, c);
  TR(9, 0);
}

struct Prod {
  uint32_t sb, g, pos, head, tail_g, tail_pos, hist;
  __device__ __forceinline__ uint32_t full() const { return sb + SM_BAR + B_FULL + (g & 7) * 8; }
  __device__ __forceinline__ uint32_t slot(uint32_t i) const { return sb + wrap12(pos + i) * SLOT; }
  __device__ __forceinline__ void acquire(uint32_t size) {
#pragma unroll 1
    while (head + size - tail_pos > NSLOT) {
      mbar_wait(sb + SM_BAR + B_EMPTY + (tail_g & 7) * 8, (tail_g >> 3) & 1);
      tail_pos += 2 + ((hist >> (tail_g & 31)) & 1);
      tail_g++;
    }
    hist = (hist & ~(1u << (g & 31))) | ((size - 2) << (g & 31));
  }
  __device__ __forceinline__ void advance(uint32_t size) { g++; head += size; pos = wrap12(pos + size); }
};

__device__ __forceinline__ void wait_flag(const unsigned* p, unsigned target) {
  while ((int)(ld_acquire(p) - target) < 0) {}
  fence_async_all();
}

__device__ __forceinline__ void init_barriers(uint32_t sb, int warp) {
  const uint32_t cnt = warp < 4 ? 1 : warp < 8 ? 16 : warp == 8 ? 4 : warp == 9 ? 1 : 11;
  if (warp < 11) mbar_init(sb + SM_BAR + warp * 16, cnt);
  if (warp < 10) mbar_init(sb + SM_BAR + warp * 16 + 8, cnt);
  asm volatile("fence.mbarrier_init.release.cluster;" ::: "memory");
}

#define TSP(i) do {} while (0)

__global__ void __cluster_dims__(2, 1, 1) __launch_bounds__(384, 1) fused_kernel(const __grid_constant__ Params P) {
  extern __shared__ uint8_t smem_raw[];
  const uint32_t sb = (smem_u32(smem_raw) + 1023u) & ~1023u;
  const int warp = __shfl_sync(~0u, (int)(threadIdx.x >> 5), 0);
  const int lane = threadIdx.x & 31;
  const int rank = blockIdx.x & 1;
  const int cl = blockIdx.x >> 1;
  const int j = cl >> 3;
  const int rb = (cl & 7) * 2 + rank;
  const bool is_s = j < 4, spare = j == 8;
  const int row0 = rb * 128;
  Flags* fl = P.flags;

  if (warp >= 8) {
    unsigned ep0 = 0;
    if (warp == 8) asm volatile("ld.volatile.global.u32 %0, [%1];" : "=r"(ep0) : "l"(&fl->epoch[blockIdx.x]));
    if (lane == 0) {
      if (warp == 8) prefetch_map(spare ? &P.w1b4 : &P.w1b3);
      if (warp == 9) prefetch_map(&P.act_ld);
      init_barriers(sb, warp);
    }
    __syncwarp();
    cluster_arrive();
    if (warp == 10 && lane == 0) {
      prefetch_map(&P.act_st); prefetch_map(&P.wq); prefetch_map(&P.k_ld); prefetch_map(&P.v_ld);
      prefetch_map(is_s ? &P.wo : &P.w2); prefetch_map(&P.x_ld); prefetch_map(&P.out_st);
    }
    __syncwarp();
    cluster_wait();
    asm volatile("setmaxnreg.dec.sync.aligned.u32 24;");
    if (warp == 8) {
      TSP(17);
#define ep1 (ep0 + 1)
      Prod p{sb, 0, 0, 0, 0, 0, 0};
#define LDA(dst, m, bar, c0, c1) tma_ld2(dst, m, bar, c0, c1)
#define LDW1(dst, m, bar, c0, c1, c2) tma_ld3_mc(dst, m, bar, c0, c1, c2)
#define LDW(dst, m, bar, c0, c1, c2) tma_ld3_mc(dst, m, bar, c0, c1, c2)
      {
        const CUtensorMap* mb = spare ? &P.w1b4 : &P.w1b3;
        const uint32_t bytes = spare ? 49152 : 40960;
        const int nt = spare ? 8 : 2;
#pragma unroll 1
        for (int t = 0; t < nt; t++) {
          const int r = spare ? ((cl & 1) * 4 + (t >> 1)) * 2 + rank : rb;
          const int nb0 = spare ? (H_SPARE0 >> 6) + (t & 1) * 4 : j * 6 + t * 3;
          int k = 0;
          if (t == 0) {
#pragma unroll 1
            for (; k < 4; k++) {
              p.acquire(3);
              if (lane == 0) { mbar_expect_tx(p.full(), bytes); LDW1(p.slot(1 + rank), mb, p.full(), 0, k * 64 + rank * 32, nb0); }
              p.advance(3);
            }
            TSP(14);
            asm volatile("" : "+r"(ep0));
            wait_flag(&fl->ln[r][0], ep1 * 64);
            TSP(15);
            if (lane == 0)
              for (int i = 0; i < 4; i++) tma_ld2(sb + i * 3 * SLOT, &P.act_ld, sb + SM_BAR + B_FULL + i * 8, C_XN + i * 64, r * 128);
          } else if (spare && !(t & 1)) {
            wait_flag(&fl->ln[r][0], ep1 * 64);
          }
#pragma unroll 1
          for (; k < 16; k++) {
            p.acquire(3);
            if (lane == 0) {
              mbar_expect_tx(p.full(), bytes);
              LDW1(p.slot(1 + rank), mb, p.full(), 0, k * 64 + rank * 32, nb0);
              tma_ld2(p.slot(0), &P.act_ld, p.full(), C_XN + k * 64, r * 128);
            }
            p.advance(3);
          }
        }
      }
      if (!spare) {
        const int kvrow = (j >> 1) * SK + KV0;
#pragma unroll 1
        for (int t = 0; t < 2; t++) {
          const int nb0 = (4 * j + 2 * t) * 2;
#pragma unroll 1
          for (int k = 0; k < 16; k++) {
            p.acquire(3);
            if (lane == 0) {
              mbar_expect_tx(p.full(), 49152);
              LDW1(p.slot(1 + rank), &P.wq, p.full(), 0, k * 64 + rank * 32, nb0);
              tma_ld2(p.slot(0), &P.act_ld, p.full(), C_XN + k * 64, row0);
            }
            p.advance(3);
          }
#pragma unroll 1
          for (int i = 0; i < 16; i++) {
            const bool is_k = i == 0 || (i < 15 && (i & 1));
            const int ch = (is_k ? ((i + 1) >> 1) : (i == 15 ? 7 : (i >> 1) - 1)) & 3;
            p.acquire(2);
            if (lane == 0) {
              mbar_expect_tx(p.full(), 32768);
              if (is_k) tma_ld2_mc(p.slot(rank), &P.k_ld, p.full(), rank * 64, kvrow + ch * 128);
              else      tma_ld3_mc(p.slot(rank), &P.v_ld, p.full(), 0, kvrow + ch * 128 + rank * 64, 0);
            }
            p.advance(2);
            if (t == 1 && i == 8 && !is_s) wait_flag(&fl->h[rb][0], ep1 * 64);
          }
        }
        const int jn = j & 3;
        if (is_s) {
          unsigned ready = 0;
#pragma unroll 1
          for (int i = 0; i < 64; i++) {
            const int hi = i >> 1;
            const int head = 4 * ((hi & 15) >> 1) + (hi & 1) + ((hi >> 4) << 1);
            const int kc = head * 128 + (i & 1) * 64;
            p.acquire(3);
            if (lane == 0) { mbar_expect_tx(p.full(), 49152); LDW(p.slot(1 + rank), &P.wo, p.full(), 0, kc + rank * 32, jn * 4); }
            if (!((ready >> head) & 1)) {
              do { ready = __ballot_sync(~0u, (int)(ld_acquire(&fl->o[rb][lane]) - ep1 * 2) >= 0); } while (!((ready >> head) & 1));
              __syncwarp();
              fence_async_all();
            }
            if (lane == 0) LDA(p.slot(0), &P.act_ld, p.full(), C_O + kc, row0);
            if (i == 56 && lane == 0) {
              prefetch_map(&P.x_ld); prefetch_map(&P.out_st);
              for (int q = 0; q < 4; q++) tma_pf2(&P.x_ld, jn * 256 + q * 64, row0);
            }
            p.advance(3);
          }
          bool g_ready = (int)(ld_acquire(&fl->g[rb][jn]) - ep1 * 4) >= 0;
#pragma unroll 1
          for (int i = 0; i < 4; i++) {
            p.acquire(2);
            if (i == 2) { TSP(20); if (g_ready) fence_async_all(); else wait_flag(&fl->g[rb][jn], ep1 * 4); TSP(21); }
            if (lane == 0) {
              mbar_expect_tx(p.full(), 32768);
              const CUtensorMap* m = i < 2 ? &P.x_ld : &P.act_ld;
              const int c0 = (i < 2 ? 0 : C_G) + jn * 256 + (i & 1) * 128;
              tma_ld2(p.slot(0), m, p.full(), c0, row0);
              tma_ld2(p.slot(1), m, p.full(), c0 + 64, row0);
            }
            p.advance(2);
          }
        } else {
#pragma unroll 1
          for (int k = 0; k < 56; k++) {
            p.acquire(3);
            if (lane == 0) { mbar_expect_tx(p.full(), 49152); LDW(p.slot(1 + rank), &P.w2, p.full(), 0, k * 64 + rank * 32, jn * 4); }
            if (k == H_SPARE0 / 64) wait_flag(&fl->h[rb][16], ep1 * 8);
            if (lane == 0) LDA(p.slot(0), &P.act_ld, p.full(), C_H + k * 64, row0);
            p.advance(3);
          }
        }
      }
      if (lane == 0) { *(volatile unsigned*)&fl->epoch[blockIdx.x] = ep1; mbar_arrive(sb + SM_BAR + B_DONE); }
    } else if (warp < 11) {
      const int wg = warp - 9;
      if (lane == 0) {
        const uint32_t stg = sb + SM_STG + wg * 16384;
        const int nev = spare ? 16 : is_s ? 8 : 10;
#pragma unroll 1
        for (int n = 0; n < nev; n++) {
          int col, row = row0, nbox = 2;
          unsigned* flag;
          if (spare) {
            const int r = ((cl & 1) * 4 + (n >> 2)) * 2 + rank;
            row = r * 128;
            col = C_H + H_SPARE0 + (n & 3) * 128;
            flag = &fl->h[r][16];
          } else if (n < 4) {
            col = C_H + j * H_REG + (n >> 1) * 192 + (n & 1) * 128;
            nbox = 2 - (n & 1);
            flag = &fl->h[rb][0];
          } else if (n < 8) {
            col = C_O + (4 * j + n - 4) * 128;
            flag = &fl->o[rb][4 * j + n - 4];
          } else {
            col = C_G + (j & 3) * 256 + (n - 8) * 128;
            flag = &fl->g[rb][j & 3];
          }
          mbar_wait(sb + SM_BAR + B_SFULL + wg * 8, n & 1);
          if (n == 9 && wg == 0) TSP(20);
          tma_st2(&P.act_st, stg, col, row + wg * 64);
          if (nbox == 2) tma_st2(&P.act_st, stg + 8192, col + 64, row + wg * 64);
          bulk_commit();
          bulk_wait_read0();
          mbar_arrive(sb + SM_BAR + B_SEMPTY + wg * 8);
          if (n == 9 && wg == 0) TSP(21);
          bulk_wait0();
          if (n == 9 && wg == 0) TSP(22);
          fence_async_all();
          red_release(flag, 1);
          if (n == 9 && wg == 0) TSP(23);
        }
        mbar_arrive(sb + SM_BAR + B_DONE);
      }
    } else {
      if (lane == 0) {
        const unsigned long long t0 = gtime();
        while (!mbar_try(sb + SM_BAR + B_DONE, 0)) {
          if (gtime() - t0 > 2000000000ull) __trap();
        }
      }
    }
    __syncwarp();
    cluster_arrive();
    cluster_wait();
  } else {
    const int wg = warp >> 2;
    TS(0);
    if (!spare) {
      const int r = row0 + j * 16 + warp * 2;
      uint32_t v[2][16];
#pragma unroll
      for (int a = 0; a < 2; a++)
#pragma unroll
        for (int i = 0; i < 4; i++)
          *(uint4*)&v[a][4 * i] = __ldg((const uint4*)(P.x + (size_t)(r + a) * DM + i * 256 + lane * 8));
      if (lane == 0) init_barriers(sb, warp);
      __syncwarp();
      cluster_arrive();
      float s[2], q[2];
#pragma unroll
      for (int a = 0; a < 2; a++) {
        float t0 = 0.f, t1 = 0.f;
#pragma unroll
        for (int i = 0; i < 16; i++) { t0 += bf_lo(v[a][i]); t1 += bf_hi(v[a][i]); }
        s[a] = t0 + t1;
      }
#pragma unroll
      for (int o = 16; o; o >>= 1) { s[0] += __shfl_xor_sync(~0u, s[0], o); s[1] += __shfl_xor_sync(~0u, s[1], o); }
#pragma unroll
      for (int a = 0; a < 2; a++) {
        s[a] *= 1.0f / DM;
        float t0 = 0.f, t1 = 0.f;
#pragma unroll
        for (int i = 0; i < 16; i++) {
          const float d0 = bf_lo(v[a][i]) - s[a], d1 = bf_hi(v[a][i]) - s[a];
          t0 = fmaf(d0, d0, t0); t1 = fmaf(d1, d1, t1);
        }
        q[a] = t0 + t1;
      }
#pragma unroll
      for (int o = 16; o; o >>= 1) { q[0] += __shfl_xor_sync(~0u, q[0], o); q[1] += __shfl_xor_sync(~0u, q[1], o); }
#pragma unroll
      for (int a = 0; a < 2; a++) {
        const uint32_t mb2 = pack_bf16(s[a], s[a]);
        const float inv = 1.0f / bf_round(sqrtf(bf_round(bf_round(q[a] * (1.0f / DM)) + 1e-5f)));
#pragma unroll
        for (int i = 0; i < 16; i++) {
          const __nv_bfloat162 d = __hsub2_rn(*(const __nv_bfloat162*)&v[a][i], *(const __nv_bfloat162*)&mb2);
          const uint32_t du = *(const uint32_t*)&d;
          v[a][i] = pack_bf16(bf_lo(du) * inv, bf_hi(du) * inv);
        }
#pragma unroll
        for (int i = 0; i < 4; i++)
          *(uint4*)(P.act + (size_t)(r + a) * ACT_W + C_XN + i * 256 + lane * 8) = *(const uint4*)&v[a][4 * i];
      }
      TS(11);
      fence_async_all();
      TS(12);
      __syncwarp();
      if (lane == 0) red_release(&fl->ln[rb][0], 1);
      TS(13);
    } else {
      if (lane == 0) init_barriers(sb, warp);
      __syncwarp();
      cluster_arrive();
    }
    cluster_wait();
    asm volatile("setmaxnreg.inc.sync.aligned.u32 240;");
    Cons c;
    c.zero = blockIdx.y; c.sb = sb; c.g = 0; c.pos = 0; c.nstg = 0; c.wg = wg; c.lane = lane;
    c.rel = mapa(sb + SM_BAR + B_EMPTY, lane & 1);
    float acc[128];
    TS(1);
    if (spare) {
      uint32_t pend[32];
#pragma unroll
      for (int i = 0; i < 32; i++) pend[i] = 0;
#pragma unroll 1
      for (int t = 0; t < 8; t++) {
        gemm_loop_flush<256, 2>(acc, c, pend, t > 0);
        h_epilogue<2>(acc, c, pend);
      }
      c.stg_acquire();
      stage_boxes<2>(pend, 0, c);
      TS(6);
    } else {
      if (wg == 1) bar_arrive(1, 256);
      {
        uint32_t pend[16];
#pragma unroll
        for (int i = 0; i < 16; i++) pend[i] = 0;
#pragma unroll 1
        for (int t = 0; t < 2; t++) {
          gemm_loop_flush<192, 1>(acc, c, pend, t > 0);
          h_epilogue<1>(acc, c, pend);
          TS(2 + t);
        }
        gemm_loop_flush<256, 1>(acc, c, pend, true);
      }
#pragma unroll 1
      for (int t = 0; t < 2; t++) {
        TS(8 + t);
        attn_tile(acc, c, t);
        TS(4 + t);
        gemm_loop<256>(acc, c, t == 0 ? 16 : is_s ? 64 : 56);
      }
      TS(6);
      if (is_s) {
        uint32_t rowoff, xr;
        frag_addr(rowoff, xr);
        const uint32_t x0 = c.pos;
        uint32_t s2[64];
#pragma unroll
        for (int i = 0; i < 64; i++) s2[i] = pack_bf16(acc[2 * i], acc[2 * i + 1]);
        fence_regs(s2);
#pragma unroll
        for (int b = 0; b < 4; b++) {
          if ((b & 1) == 0) { c.wait_full(c.g + (b >> 1)); c.wait_full(c.g + 2 + (b >> 1)); }
          if (b == 0) TS(22);
          if (b == 2) TS(23);
          const uint32_t xs = sb + wrap12(x0 + b) * SLOT + wg * 8192;
          const uint32_t sx = xs + rowoff, sg = sb + wrap12(wrap12(x0 + 4) + b) * SLOT + wg * 8192 + rowoff;
          uint32_t xv[16], gv[16];
#pragma unroll
          for (int kb = 0; kb < 4; kb++) {
            ldsm4(sx + ((32 * kb) ^ xr), xv[4 * kb], xv[4 * kb + 1], xv[4 * kb + 2], xv[4 * kb + 3]);
            ldsm4(sg + ((32 * kb) ^ xr), gv[4 * kb], gv[4 * kb + 1], gv[4 * kb + 2], gv[4 * kb + 3]);
          }
#pragma unroll
          for (int i = 0; i < 16; i++) {
            const __nv_bfloat162 pr = __hmul2_rn(*(const __nv_bfloat162*)&s2[16 * b + i], *(const __nv_bfloat162*)&gv[i]);
            const __nv_bfloat162 o = __hadd2_rn(*(const __nv_bfloat162*)&xv[i], pr);
            xv[i] = *(const uint32_t*)&o;
          }
#pragma unroll
          for (int kb = 0; kb < 4; kb++) stsm4(sx + ((32 * kb) ^ xr), xv[4 * kb], xv[4 * kb + 1], xv[4 * kb + 2], xv[4 * kb + 3]);
          if (b & 1) {
            fence_async_smem();
            bar_sync(3 + wg, 128);
            if ((threadIdx.x & 127) == 0) {
              tma_st2(&P.out_st, sb + wrap12(x0 + b - 1) * SLOT + wg * 8192, (j & 3) * 256 + b * 64 - 64, row0 + wg * 64);
              tma_st2(&P.out_st, xs, (j & 3) * 256 + b * 64, row0 + wg * 64);
              bulk_commit();
            }
          }
        }
        TS(24);
        if ((threadIdx.x & 127) == 0) bulk_wait_read0();
      } else {
        uint32_t rowoff, xr;
        frag_addr(rowoff, xr);
        const uint32_t stg = sb + SM_STG + wg * 16384 + rowoff;
#pragma unroll
        for (int hh = 0; hh < 2; hh++) {
          c.stg_acquire();
#pragma unroll
          for (int kb = 0; kb < 8; kb++)
            stsm4(stg + (kb >> 2) * 8192 + ((32 * (kb & 3)) ^ xr),
                  silu2(acc[64 * hh + 8 * kb], acc[64 * hh + 8 * kb + 1]), silu2(acc[64 * hh + 8 * kb + 2], acc[64 * hh + 8 * kb + 3]),
                  silu2(acc[64 * hh + 8 * kb + 4], acc[64 * hh + 8 * kb + 5]), silu2(acc[64 * hh + 8 * kb + 6], acc[64 * hh + 8 * kb + 7]));
          c.stg_publish();
          if (hh == 0) TS(22);
        }
      }
    }
    TS(7);
    __syncwarp();
    if (lane == 0) mbar_arrive(sb + SM_BAR + B_DONE);
    cluster_arrive();
    cluster_wait();
  }
}

typedef CUresult (*EncodeFn)(CUtensorMap*, CUtensorMapDataType, cuuint32_t, void*, const cuuint64_t*, const cuuint64_t*,
                             const cuuint32_t*, const cuuint32_t*, CUtensorMapInterleave, CUtensorMapSwizzle,
                             CUtensorMapL2promotion, CUtensorMapFloatOOBfill);

void map2d(EncodeFn enc, CUtensorMap* m, const void* base, uint64_t cols, uint64_t rows, uint32_t box_rows) {
  cuuint64_t dims[2] = {cols, rows};
  cuuint64_t strides[1] = {cols * 2};
  cuuint32_t box[2] = {64, box_rows};
  cuuint32_t es[2] = {1, 1};
  enc(m, CU_TENSOR_MAP_DATA_TYPE_BFLOAT16, 2, (void*)base, dims, strides, box, es, CU_TENSOR_MAP_INTERLEAVE_NONE,
      CU_TENSOR_MAP_SWIZZLE_128B, CU_TENSOR_MAP_L2_PROMOTION_L2_256B, CU_TENSOR_MAP_FLOAT_OOB_FILL_NONE);
}
void map3d(EncodeFn enc, CUtensorMap* m, const void* base, uint64_t cols, uint64_t rows, uint32_t box_rows, uint32_t box_blks) {
  cuuint64_t dims[3] = {64, rows, cols / 64};
  cuuint64_t strides[2] = {cols * 2, 128};
  cuuint32_t box[3] = {64, box_rows, box_blks};
  cuuint32_t es[3] = {1, 1, 1};
  enc(m, CU_TENSOR_MAP_DATA_TYPE_BFLOAT16, 3, (void*)base, dims, strides, box, es, CU_TENSOR_MAP_INTERLEAVE_NONE,
      CU_TENSOR_MAP_SWIZZLE_128B, CU_TENSOR_MAP_L2_PROMOTION_L2_256B, CU_TENSOR_MAP_FLOAT_OOB_FILL_NONE);
}

}

extern "C" void kernel_launch(void* const* d_in, const int* in_sizes, int n_in, void* d_out, int out_size) {
  (void)in_sizes; (void)n_in; (void)out_size;
  static EncodeFn enc = nullptr;
  static void* act = nullptr;
  static void* flags = nullptr;
  if (!enc) {
    void* fn = nullptr;
    cudaDriverEntryPointQueryResult qr;
    cudaGetDriverEntryPoint("cuTensorMapEncodeTiled", &fn, cudaEnableDefault, &qr);
    enc = (EncodeFn)fn;
    cudaGetSymbolAddress(&act, g_act);
    cudaGetSymbolAddress(&flags, g_flags);
    cudaFuncSetAttribute(fused_kernel, cudaFuncAttributeMaxDynamicSharedMemorySize, SMEM_BYTES);
  }
  Params P;
  map2d(enc, &P.act_ld, act, ACT_W, SEQ, 128);
  map2d(enc, &P.act_st, act, ACT_W, SEQ, 64);
  map2d(enc, &P.x_ld, d_in[0], DM, SEQ, 128);
  map2d(enc, &P.out_st, d_out, DM, SEQ, 64);
  map2d(enc, &P.k_ld, d_in[1], 128, 4 * SK, 128);
  map3d(enc, &P.v_ld, d_in[2], 128, 4 * SK, 64, 2);
  map3d(enc, &P.wq, d_in[3], NQ, DM, 32, 4);
  map3d(enc, &P.w1b4, d_in[6], DFF, DM, 32, 4);
  map3d(enc, &P.w1b3, d_in[6], DFF, DM, 32, 3);
  map3d(enc, &P.wo, d_in[4], DM, NQ, 32, 4);
  map3d(enc, &P.w2, d_in[7], DM, DFF, 32, 4);
  P.x = (const __nv_bfloat16*)d_in[0];
  P.act = (__nv_bfloat16*)act;
  P.flags = (Flags*)flags;
  fused_kernel<<<NCLUSTER * 2, 384, SMEM_BYTES>>>(P);
}
```

```cpp
#include <cuda_runtime.h>
#include <cuda_bf16.h>
#include <cuda.h>
#include <stdint.h>

namespace {

constexpr int SEQ    = 2048;
constexpr int DM     = 1024;
constexpr int NQ     = 4096;
constexpr int DFF    = 3584;
constexpr int SK     = 2048;
constexpr int WIN    = 512;
constexpr int KV0    = SK - WIN;
constexpr int C_XN = 0, C_O = 1024, C_H = 5120, C_G = 8704, ACT_W = 9728;

constexpr int H_REG = 384, H_SPARE0 = 8 * H_REG;
static_assert(H_SPARE0 + 512 == DFF, "H split");

constexpr int NSLOT = 12, SLOT = 16384, NBAR = 8;
constexpr int SM_STG = NSLOT * SLOT;
constexpr int SM_BAR = SM_STG + 2 * 16384;
constexpr int SMEM_BYTES = SM_BAR + 256 + 1024;
constexpr int B_FULL = 0, B_EMPTY = 64, B_SFULL = 128, B_SEMPTY = 144, B_DONE = 160;

constexpr int NCLUSTER = 66;

struct Flags {
  unsigned ln[16][32];
  unsigned h[16][32];
  unsigned o[16][32];
  unsigned g[16][32];
  unsigned epoch[160];
};
__device__ __nv_bfloat16 g_act[(size_t)SEQ * ACT_W];
__device__ Flags g_flags;

struct Params {
  CUtensorMap act_ld, act_st, x_ld, out_st, k_ld, v_ld, wq, w1b4, w1b3, wo, w2;
  const __nv_bfloat16* x;
  __nv_bfloat16* act;
  Flags* flags;
};

__device__ __forceinline__ uint32_t smem_u32(const void* p) { return (uint32_t)__cvta_generic_to_shared(p); }
__device__ __forceinline__ void mbar_init(uint32_t bar, uint32_t cnt) {
  asm volatile("mbarrier.init.shared::cta.b64 [%0], %1;" ::"r"(bar), "r"(cnt) : "memory");
}
__device__ __forceinline__ bool mbar_try(uint32_t bar, uint32_t parity) {
  uint32_t ok;
  asm volatile("{\n.reg .pred p;\nmbarrier.try_wait.parity.shared::cta.b64 p, [%1], %2;\nselp.u32 %0, 1, 0, p;\n}\n"
               : "=r"(ok) : "r"(bar), "r"(parity) : "memory");
  return ok;
}
__device__ __forceinline__ void mbar_wait(uint32_t bar, uint32_t parity) {
  asm volatile("{\n.reg .pred p;\nWAIT_%=:\nmbarrier.try_wait.parity.shared::cta.b64 p, [%0], %1;\n@p bra DONE_%=;\nbra WAIT_%=;\nDONE_%=:\n}\n"
               ::"r"(bar), "r"(parity) : "memory");
}
__device__ __forceinline__ void mbar_arrive(uint32_t bar) {
  asm volatile("mbarrier.arrive.shared::cta.b64 _, [%0];" ::"r"(bar) : "memory");
}
__device__ __forceinline__ void mbar_arrive_cluster(uint32_t cluster_addr) {
  asm volatile("mbarrier.arrive.shared::cluster.b64 _, [%0];" ::"r"(cluster_addr) : "memory");
}
__device__ __forceinline__ void mbar_expect_tx(uint32_t bar, uint32_t bytes) {
  asm volatile("mbarrier.arrive.expect_tx.shared::cta.b64 _, [%0], %1;" ::"r"(bar), "r"(bytes) : "memory");
}
__device__ __forceinline__ uint32_t mapa(uint32_t addr, uint32_t rank) {
  uint32_t r;
  asm("mapa.shared::cluster.u32 %0, %1, %2;" : "=r"(r) : "r"(addr), "r"(rank));
  return r;
}
__device__ __forceinline__ void cluster_arrive() { asm volatile("barrier.cluster.arrive.relaxed.aligned;" ::: "memory"); }
__device__ __forceinline__ void cluster_wait() { asm volatile("barrier.cluster.wait.acquire.aligned;" ::: "memory"); }
__device__ __forceinline__ void bar_sync(int id, int n) { asm volatile("bar.sync %0, %1;" ::"r"(id), "r"(n) : "memory"); }
__device__ __forceinline__ void bar_arrive(int id, int n) { asm volatile("bar.arrive %0, %1;" ::"r"(id), "r"(n) : "memory"); }
__device__ __forceinline__ void fence_async_smem() { asm volatile("fence.proxy.async.shared::cta;" ::: "memory"); }
__device__ __forceinline__ void fence_async_all() { asm volatile("fence.proxy.async.global;" ::: "memory"); }

__device__ __forceinline__ void tma_ld2(uint32_t dst, const CUtensorMap* m, uint32_t bar, int c0, int c1) {
  asm volatile("cp.async.bulk.tensor.2d.shared::cluster.global.mbarrier::complete_tx::bytes [%0], [%1, {%3, %4}], [%2];"
               ::"r"(dst), "l"(m), "r"(bar), "r"(c0), "r"(c1) : "memory");
}
__device__ __forceinline__ void tma_ld2_mc(uint32_t dst, const CUtensorMap* m, uint32_t bar, int c0, int c1) {
  asm volatile("cp.async.bulk.tensor.2d.shared::cluster.global.mbarrier::complete_tx::bytes.multicast::cluster [%0], [%1, {%3, %4}], [%2], %5;"
               ::"r"(dst), "l"(m), "r"(bar), "r"(c0), "r"(c1), "h"((uint16_t)3) : "memory");
}
__device__ __forceinline__ void tma_ld3_mc(uint32_t dst, const CUtensorMap* m, uint32_t bar, int c0, int c1, int c2) {
  asm volatile("cp.async.bulk.tensor.3d.shared::cluster.global.mbarrier::complete_tx::bytes.multicast::cluster [%0], [%1, {%3, %4, %5}], [%2], %6;"
               ::"r"(dst), "l"(m), "r"(bar), "r"(c0), "r"(c1), "r"(c2), "h"((uint16_t)3) : "memory");
}
__device__ __forceinline__ void tma_ld3_mc_hint(uint32_t dst, const CUtensorMap* m, uint32_t bar, int c0, int c1, int c2, uint64_t pol) {
  asm volatile("cp.async.bulk.tensor.3d.shared::cluster.global.mbarrier::complete_tx::bytes.multicast::cluster.L2::cache_hint [%0], [%1, {%3, %4, %5}], [%2], %6, %7;"
               ::"r"(dst), "l"(m), "r"(bar), "r"(c0), "r"(c1), "r"(c2), "h"((uint16_t)3), "l"(pol) : "memory");
}
__device__ __forceinline__ void tma_ld2_hint(uint32_t dst, const CUtensorMap* m, uint32_t bar, int c0, int c1, uint64_t pol) {
  asm volatile("cp.async.bulk.tensor.2d.shared::cluster.global.mbarrier::complete_tx::bytes.L2::cache_hint [%0], [%1, {%3, %4}], [%2], %5;"
               ::"r"(dst), "l"(m), "r"(bar), "r"(c0), "r"(c1), "l"(pol) : "memory");
}
__device__ __forceinline__ void tma_st2_hint(const CUtensorMap* m, uint32_t src, int c0, int c1, uint64_t pol) {
  asm volatile("cp.async.bulk.tensor.2d.global.shared::cta.bulk_group.L2::cache_hint [%0, {%2, %3}], [%1], %4;"
               ::"l"(m), "r"(src), "r"(c0), "r"(c1), "l"(pol) : "memory");
}
#define POL_FIRST 0x12F0000000000000ull
__device__ __forceinline__ uint64_t policy_evict_first() {
  uint64_t p;
  asm volatile("createpolicy.fractional.L2::evict_first.b64 %0, 1.0;" : "=l"(p));
  return p;
}
__device__ __forceinline__ void tma_st2(const CUtensorMap* m, uint32_t src, int c0, int c1) {
  asm volatile("cp.async.bulk.tensor.2d.global.shared::cta.bulk_group [%0, {%2, %3}], [%1];"
               ::"l"(m), "r"(src), "r"(c0), "r"(c1) : "memory");
}
__device__ __forceinline__ void tma_pf2(const CUtensorMap* m, int c0, int c1) {
  asm volatile("cp.async.bulk.prefetch.tensor.2d.L2.global [%0, {%1, %2}];" ::"l"(m), "r"(c0), "r"(c1) : "memory");
}
__device__ __forceinline__ void bulk_commit() { asm volatile("cp.async.bulk.commit_group;" ::: "memory"); }
__device__ __forceinline__ void bulk_wait_read0() { asm volatile("cp.async.bulk.wait_group.read 0;" ::: "memory"); }
__device__ __forceinline__ void bulk_wait0() { asm volatile("cp.async.bulk.wait_group 0;" ::: "memory"); }
__device__ __forceinline__ void prefetch_map(const CUtensorMap* m) {
  asm volatile("prefetch.tensormap [%0];" ::"l"(m) : "memory");
}
__device__ __forceinline__ unsigned ld_acquire(const unsigned* p) {
  unsigned v;
  asm volatile("ld.acquire.gpu.global.u32 %0, [%1];" : "=r"(v) : "l"(p) : "memory");
  return v;
}
__device__ __forceinline__ void red_release(unsigned* p, unsigned v) {
  asm volatile("red.release.gpu.global.add.u32 [%0], %1;" ::"l"(p), "r"(v) : "memory");
}
__device__ __forceinline__ void wg_fence() { asm volatile("wgmma.fence.sync.aligned;" ::: "memory"); }
__device__ __forceinline__ void wg_commit() { asm volatile("wgmma.commit_group.sync.aligned;" ::: "memory"); }
template <int N> __device__ __forceinline__ void wg_wait() { asm volatile("wgmma.wait_group.sync.aligned %0;" ::"n"(N) : "memory"); }
template <int N> __device__ __forceinline__ void fence_regs(float (&d)[N]) {
#pragma unroll
  for (int i = 0; i < N; i++) asm volatile("" : "+f"(d[i])::"memory");
}
template <int N> __device__ __forceinline__ void fence_regs(uint32_t (&d)[N]) {
#pragma unroll
  for (int i = 0; i < N; i++) asm volatile("" : "+r"(d[i])::"memory");
}
__device__ __forceinline__ uint64_t mkdesc(uint32_t addr, uint32_t lbo, uint32_t sbo) {
  return (uint64_t)((addr & 0x3FFFF) >> 4) | ((uint64_t)(lbo >> 4) << 16) | ((uint64_t)(sbo >> 4) << 32) | (1ull << 62);
}
__device__ __forceinline__ uint32_t pack_bf16(float lo, float hi) {
  uint32_t r;
  asm("cvt.rn.bf16x2.f32 %0, %1, %2;" : "=r"(r) : "f"(hi), "f"(lo));
  return r;
}
__device__ __forceinline__ uint32_t pack_bf16_relu(float lo, float hi) {
  uint32_t r;
  asm("cvt.rn.relu.bf16x2.f32 %0, %1, %2;" : "=r"(r) : "f"(hi), "f"(lo));
  return r;
}
__device__ __forceinline__ float bf_lo(uint32_t v) { return __uint_as_float(v << 16); }
__device__ __forceinline__ float bf_hi(uint32_t v) { return __uint_as_float(v & 0xFFFF0000u); }
__device__ __forceinline__ float bf_round(float v) { return __bfloat162float(__float2bfloat16_rn(v)); }
__device__ __forceinline__ float ex2(float x) {
  float r;
  asm("ex2.approx.ftz.f32 %0, %1;" : "=f"(r) : "f"(x));
  return r;
}
__device__ __forceinline__ float rcp(float x) {
  float r;
  asm("rcp.approx.ftz.f32 %0, %1;" : "=f"(r) : "f"(x));
  return r;
}
__device__ __forceinline__ uint32_t tid_x() {
  uint32_t t;
  asm volatile("mov.u32 %0, %%tid.x;" : "=r"(t));
  return t;
}
__device__ __forceinline__ void stsm4(uint32_t addr, uint32_t r0, uint32_t r1, uint32_t r2, uint32_t r3) {
  asm volatile("stmatrix.sync.aligned.m8n8.x4.shared.b16 [%0], {%1, %2, %3, %4};" ::"r"(addr), "r"(r0), "r"(r1), "r"(r2), "r"(r3) : "memory");
}
__device__ __forceinline__ void ldsm4(uint32_t addr, uint32_t& r0, uint32_t& r1, uint32_t& r2, uint32_t& r3) {
  asm volatile("ldmatrix.sync.aligned.m8n8.x4.shared.b16 {%0, %1, %2, %3}, [%4];" : "=r"(r0), "=r"(r1), "=r"(r2), "=r"(r3) : "r"(addr) : "memory");
}
__device__ __forceinline__ void sts128(uint32_t addr, uint32_t r0, uint32_t r1, uint32_t r2, uint32_t r3) {
  asm volatile("st.shared.v4.b32 [%0], {%1, %2, %3, %4};" ::"r"(addr), "r"(r0), "r"(r1), "r"(r2), "r"(r3) : "memory");
}
__device__ __forceinline__ void lds128(uint32_t addr, uint32_t& r0, uint32_t& r1, uint32_t& r2, uint32_t& r3) {
  asm volatile("ld.shared.v4.b32 {%0, %1, %2, %3}, [%4];" : "=r"(r0), "=r"(r1), "=r"(r2), "=r"(r3) : "r"(addr) : "memory");
}
__device__ __forceinline__ unsigned long long gtime() {
  unsigned long long t;
  asm volatile("mov.u64 %0, %globaltimer;" : "=l"(t));
  return t;
}

__device__ __forceinline__ void wgmma_ss_n256_tb(float (&d)[128], uint64_t da, uint64_t db, uint32_t sc) {
  asm volatile("{\n.reg .pred p;\nsetp.ne.b32 p, %130, 0;\n"
    "wgmma.mma_async.sync.aligned.m64n256k16.f32.bf16.bf16 "
    "{%0, %1, %2, %3, %4, %5, %6, %7, %8, %9, %10, %11, %12, %13, %14, %15, %16, %17, %18, %19, %20, %21, %22, %23, %24, %25, %26, %27, %28, %29, %30, %31, %32, %33, %34, %35, %36, %37, %38, %39, %40, %41, %42, %43, %44, %45, %46, %47, %48, %49, %50, %51, %52, %53, %54, %55, %56, %57, %58, %59, %60, %61, %62, %63, %64, %65, %66, %67, %68, %69, %70, %71, %72, %73, %74, %75, %76, %77, %78, %79, %80, %81, %82, %83, %84, %85, %86, %87, %88, %89, %90, %91, %92, %93, %94, %95, %96, %97, %98, %99, %100, %101, %102, %103, %104, %105, %106, %107, %108, %109, %110, %111, %112, %113, %114, %115, %116, %117, %118, %119, %120, %121, %122, %123, %124, %125, %126, %127}, %128, %129, p, 1, 1, 0, 1;\n}\n"
    : "+f"(d[0]), "+f"(d[1]), "+f"(d[2]), "+f"(d[3]), "+f"(d[4]), "+f"(d[5]), "+f"(d[6]), "+f"(d[7]), "+f"(d[8]), "+f"(d[9]), "+f"(d[10]), "+f"(d[11]), "+f"(d[12]), "+f"(d[13]), "+f"(d[14]), "+f"(d[15]), "+f"(d[16]), "+f"(d[17]), "+f"(d[18]), "+f"(d[19]), "+f"(d[20]), "+f"(d[21]), "+f"(d[22]), "+f"(d[23]), "+f"(d[24]), "+f"(d[25]), "+f"(d[26]), "+f"(d[27]), "+f"(d[28]), "+f"(d[29]), "+f"(d[30]), "+f"(d[31]), "+f"(d[32]), "+f"(d[33]), "+f"(d[34]), "+f"(d[35]), "+f"(d[36]), "+f"(d[37]), "+f"(d[38]), "+f"(d[39]), "+f"(d[40]), "+f"(d[41]), "+f"(d[42]), "+f"(d[43]), "+f"(d[44]), "+f"(d[45]), "+f"(d[46]), "+f"(d[47]), "+f"(d[48]), "+f"(d[49]), "+f"(d[50]), "+f"(d[51]), "+f"(d[52]), "+f"(d[53]), "+f"(d[54]), "+f"(d[55]), "+f"(d[56]), "+f"(d[57]), "+f"(d[58]), "+f"(d[59]), "+f"(d[60]), "+f"(d[61]), "+f"(d[62]), "+f"(d[63]), "+f"(d[64]), "+f"(d[65]), "+f"(d[66]), "+f"(d[67]), "+f"(d[68]), "+f"(d[69]), "+f"(d[70]), "+f"(d[71]), "+f"(d[72]), "+f"(d[73]), "+f"(d[74]), "+f"(d[75]), "+f"(d[76]), "+f"(d[77]), "+f"(d[78]), "+f"(d[79]), "+f"(d[80]), "+f"(d[81]), "+f"(d[82]), "+f"(d[83]), "+f"(d[84]), "+f"(d[85]), "+f"(d[86]), "+f"(d[87]), "+f"(d[88]), "+f"(d[89]), "+f"(d[90]), "+f"(d[91]), "+f"(d[92]), "+f"(d[93]), "+f"(d[94]), "+f"(d[95]), "+f"(d[96]), "+f"(d[97]), "+f"(d[98]), "+f"(d[99]), "+f"(d[100]), "+f"(d[101]), "+f"(d[102]), "+f"(d[103]), "+f"(d[104]), "+f"(d[105]), "+f"(d[106]), "+f"(d[107]), "+f"(d[108]), "+f"(d[109]), "+f"(d[110]), "+f"(d[111]), "+f"(d[112]), "+f"(d[113]), "+f"(d[114]), "+f"(d[115]), "+f"(d[116]), "+f"(d[117]), "+f"(d[118]), "+f"(d[119]), "+f"(d[120]), "+f"(d[121]), "+f"(d[122]), "+f"(d[123]), "+f"(d[124]), "+f"(d[125]), "+f"(d[126]), "+f"(d[127])
    : "l"(da), "l"(db), "r"(sc));
}
__device__ __forceinline__ void wgmma_ss_n192_tb(float (&d)[128], uint64_t da, uint64_t db, uint32_t sc) {
  asm volatile("{\n.reg .pred p;\nsetp.ne.b32 p, %98, 0;\n"
    "wgmma.mma_async.sync.aligned.m64n192k16.f32.bf16.bf16 "
    "{%0, %1, %2, %3, %4, %5, %6, %7, %8, %9, %10, %11, %12, %13, %14, %15, %16, %17, %18, %19, %20, %21, %22, %23, %24, %25, %26, %27, %28, %29, %30, %31, %32, %33, %34, %35, %36, %37, %38, %39, %40, %41, %42, %43, %44, %45, %46, %47, %48, %49, %50, %51, %52, %53, %54, %55, %56, %57, %58, %59, %60, %61, %62, %63, %64, %65, %66, %67, %68, %69, %70, %71, %72, %73, %74, %75, %76, %77, %78, %79, %80, %81, %82, %83, %84, %85, %86, %87, %88, %89, %90, %91, %92, %93, %94, %95}, %96, %97, p, 1, 1, 0, 1;\n}\n"
    : "+f"(d[0]), "+f"(d[1]), "+f"(d[2]), "+f"(d[3]), "+f"(d[4]), "+f"(d[5]), "+f"(d[6]), "+f"(d[7]), "+f"(d[8]), "+f"(d[9]), "+f"(d[10]), "+f"(d[11]), "+f"(d[12]), "+f"(d[13]), "+f"(d[14]), "+f"(d[15]), "+f"(d[16]), "+f"(d[17]), "+f"(d[18]), "+f"(d[19]), "+f"(d[20]), "+f"(d[21]), "+f"(d[22]), "+f"(d[23]), "+f"(d[24]), "+f"(d[25]), "+f"(d[26]), "+f"(d[27]), "+f"(d[28]), "+f"(d[29]), "+f"(d[30]), "+f"(d[31]), "+f"(d[32]), "+f"(d[33]), "+f"(d[34]), "+f"(d[35]), "+f"(d[36]), "+f"(d[37]), "+f"(d[38]), "+f"(d[39]), "+f"(d[40]), "+f"(d[41]), "+f"(d[42]), "+f"(d[43]), "+f"(d[44]), "+f"(d[45]), "+f"(d[46]), "+f"(d[47]), "+f"(d[48]), "+f"(d[49]), "+f"(d[50]), "+f"(d[51]), "+f"(d[52]), "+f"(d[53]), "+f"(d[54]), "+f"(d[55]), "+f"(d[56]), "+f"(d[57]), "+f"(d[58]), "+f"(d[59]), "+f"(d[60]), "+f"(d[61]), "+f"(d[62]), "+f"(d[63]), "+f"(d[64]), "+f"(d[65]), "+f"(d[66]), "+f"(d[67]), "+f"(d[68]), "+f"(d[69]), "+f"(d[70]), "+f"(d[71]), "+f"(d[72]), "+f"(d[73]), "+f"(d[74]), "+f"(d[75]), "+f"(d[76]), "+f"(d[77]), "+f"(d[78]), "+f"(d[79]), "+f"(d[80]), "+f"(d[81]), "+f"(d[82]), "+f"(d[83]), "+f"(d[84]), "+f"(d[85]), "+f"(d[86]), "+f"(d[87]), "+f"(d[88]), "+f"(d[89]), "+f"(d[90]), "+f"(d[91]), "+f"(d[92]), "+f"(d[93]), "+f"(d[94]), "+f"(d[95])
    : "l"(da), "l"(db), "r"(sc));
}
__device__ __forceinline__ void wgmma_rs_n128(float (&d)[64], uint32_t a0, uint32_t a1, uint32_t a2, uint32_t a3, uint64_t db, uint32_t sc) {
  asm volatile("{\n.reg .pred p;\nsetp.ne.b32 p, %69, 0;\n"
    "wgmma.mma_async.sync.aligned.m64n128k16.f32.bf16.bf16 "
    "{%0, %1, %2, %3, %4, %5, %6, %7, %8, %9, %10, %11, %12, %13, %14, %15, %16, %17, %18, %19, %20, %21, %22, %23, %24, %25, %26, %27, %28, %29, %30, %31, %32, %33, %34, %35, %36, %37, %38, %39, %40, %41, %42, %43, %44, %45, %46, %47, %48, %49, %50, %51, %52, %53, %54, %55, %56, %57, %58, %59, %60, %61, %62, %63}, {%64, %65, %66, %67}, %68, p, 1, 1, 0;\n}\n"
    : "+f"(d[0]), "+f"(d[1]), "+f"(d[2]), "+f"(d[3]), "+f"(d[4]), "+f"(d[5]), "+f"(d[6]), "+f"(d[7]), "+f"(d[8]), "+f"(d[9]), "+f"(d[10]), "+f"(d[11]), "+f"(d[12]), "+f"(d[13]), "+f"(d[14]), "+f"(d[15]), "+f"(d[16]), "+f"(d[17]), "+f"(d[18]), "+f"(d[19]), "+f"(d[20]), "+f"(d[21]), "+f"(d[22]), "+f"(d[23]), "+f"(d[24]), "+f"(d[25]), "+f"(d[26]), "+f"(d[27]), "+f"(d[28]), "+f"(d[29]), "+f"(d[30]), "+f"(d[31]), "+f"(d[32]), "+f"(d[33]), "+f"(d[34]), "+f"(d[35]), "+f"(d[36]), "+f"(d[37]), "+f"(d[38]), "+f"(d[39]), "+f"(d[40]), "+f"(d[41]), "+f"(d[42]), "+f"(d[43]), "+f"(d[44]), "+f"(d[45]), "+f"(d[46]), "+f"(d[47]), "+f"(d[48]), "+f"(d[49]), "+f"(d[50]), "+f"(d[51]), "+f"(d[52]), "+f"(d[53]), "+f"(d[54]), "+f"(d[55]), "+f"(d[56]), "+f"(d[57]), "+f"(d[58]), "+f"(d[59]), "+f"(d[60]), "+f"(d[61]), "+f"(d[62]), "+f"(d[63])
    : "r"(a0), "r"(a1), "r"(a2), "r"(a3), "l"(db), "r"(sc));
}
__device__ __forceinline__ void wgmma_rs_n128_tb(float (&d)[64], uint32_t a0, uint32_t a1, uint32_t a2, uint32_t a3, uint64_t db, uint32_t sc) {
  asm volatile("{\n.reg .pred p;\nsetp.ne.b32 p, %69, 0;\n"
    "wgmma.mma_async.sync.aligned.m64n128k16.f32.bf16.bf16 "
    "{%0, %1, %2, %3, %4, %5, %6, %7, %8, %9, %10, %11, %12, %13, %14, %15, %16, %17, %18, %19, %20, %21, %22, %23, %24, %25, %26, %27, %28, %29, %30, %31, %32, %33, %34, %35, %36, %37, %38, %39, %40, %41, %42, %43, %44, %45, %46, %47, %48, %49, %50, %51, %52, %53, %54, %55, %56, %57, %58, %59, %60, %61, %62, %63}, {%64, %65, %66, %67}, %68, p, 1, 1, 1;\n}\n"
    : "+f"(d[0]), "+f"(d[1]), "+f"(d[2]), "+f"(d[3]), "+f"(d[4]), "+f"(d[5]), "+f"(d[6]), "+f"(d[7]), "+f"(d[8]), "+f"(d[9]), "+f"(d[10]), "+f"(d[11]), "+f"(d[12]), "+f"(d[13]), "+f"(d[14]), "+f"(d[15]), "+f"(d[16]), "+f"(d[17]), "+f"(d[18]), "+f"(d[19]), "+f"(d[20]), "+f"(d[21]), "+f"(d[22]), "+f"(d[23]), "+f"(d[24]), "+f"(d[25]), "+f"(d[26]), "+f"(d[27]), "+f"(d[28]), "+f"(d[29]), "+f"(d[30]), "+f"(d[31]), "+f"(d[32]), "+f"(d[33]), "+f"(d[34]), "+f"(d[35]), "+f"(d[36]), "+f"(d[37]), "+f"(d[38]), "+f"(d[39]), "+f"(d[40]), "+f"(d[41]), "+f"(d[42]), "+f"(d[43]), "+f"(d[44]), "+f"(d[45]), "+f"(d[46]), "+f"(d[47]), "+f"(d[48]), "+f"(d[49]), "+f"(d[50]), "+f"(d[51]), "+f"(d[52]), "+f"(d[53]), "+f"(d[54]), "+f"(d[55]), "+f"(d[56]), "+f"(d[57]), "+f"(d[58]), "+f"(d[59]), "+f"(d[60]), "+f"(d[61]), "+f"(d[62]), "+f"(d[63])
    : "r"(a0), "r"(a1), "r"(a2), "r"(a3), "l"(db), "r"(sc));
}

#define TS(i) do {} while (0)
#define TR(j, i) do {} while (0)
#define TSS(i, c) do {} while (0)

__device__ __forceinline__ uint32_t wrap12(uint32_t p) { return p >= NSLOT ? p - NSLOT : p; }

struct Cons {
  uint32_t sb;
  uint32_t g, pos;
  uint32_t rel;
  uint32_t nstg;
  uint32_t zero;
  int wg, lane;
  __device__ __forceinline__ void wait_full(uint32_t gg) const { mbar_wait(sb + SM_BAR + B_FULL + (gg & 7) * 8, (gg >> 3) & 1); }
  __device__ __forceinline__ void release(uint32_t gg) const { if (lane < 2) mbar_arrive_cluster(rel + (gg & 7) * 8); }
  __device__ __forceinline__ void stg_acquire() { mbar_wait(sb + SM_BAR + B_SEMPTY + wg * 8, (nstg & 1) ^ 1); nstg++; }
  __device__ __forceinline__ void stg_publish() const {
    fence_async_smem();
    __syncwarp();
    if (lane == 0) mbar_arrive(sb + SM_BAR + B_SFULL + wg * 8);
  }
};

__device__ __forceinline__ void frag_addr(uint32_t& rowoff, uint32_t& xr) {
  const uint32_t t = tid_x();
  rowoff = ((t >> 5) & 3) * 2048 + (t & 15) * 128;
  xr = (((t >> 4) & 1) ^ (t & 7)) << 4;
}
template <int NB, int NR>
__device__ __forceinline__ void stage_boxes(const uint32_t (&r)[NR], int r0, const Cons& c) {
  uint32_t rowoff, xr;
  frag_addr(rowoff, xr);
  const uint32_t stg = c.sb + SM_STG + c.wg * 16384 + rowoff;
#pragma unroll
  for (int b = 0; b < NB; b++)
#pragma unroll
    for (int kb = 0; kb < 4; kb++)
      stsm4(stg + b * 8192 + ((32 * kb) ^ xr), r[r0 + b * 16 + kb * 4], r[r0 + b * 16 + kb * 4 + 1], r[r0 + b * 16 + kb * 4 + 2], r[r0 + b * 16 + kb * 4 + 3]);
  c.stg_publish();
}

template <int N, bool FIRST>
__device__ __forceinline__ void gemm_step(float (&acc)[128], Cons& c) {
  const uint32_t p1 = wrap12(c.pos + 1), p2 = wrap12(c.pos + 2);
  const uint64_t da = mkdesc(c.sb + c.wg * 8192 + c.pos * SLOT, 16, 1024);
  const uint64_t b0 = mkdesc(c.sb + p1 * SLOT, 4096, 1024);
  const uint64_t b1 = mkdesc(c.sb + p2 * SLOT, 4096, 1024);
  c.wait_full(c.g);
  wg_fence();
  if (N == 256) {
    wgmma_ss_n256_tb(acc, da, b0, FIRST ? 0 : 1);
    wgmma_ss_n256_tb(acc, da + 2, b0 + 128, 1);
    wgmma_ss_n256_tb(acc, da + 4, b1, 1);
    wgmma_ss_n256_tb(acc, da + 6, b1 + 128, 1);
  } else {
    wgmma_ss_n192_tb(acc, da, b0, FIRST ? 0 : 1);
    wgmma_ss_n192_tb(acc, da + 2, b0 + 128, 1);
    wgmma_ss_n192_tb(acc, da + 4, b1, 1);
    wgmma_ss_n192_tb(acc, da + 6, b1 + 128, 1);
  }
  wg_commit();
  if (!FIRST) {
    wg_wait<1>();
    c.release(c.g - 1);
  }
  c.g++;
  c.pos = wrap12(p2 + 1);
}

template <int N>
__device__ __forceinline__ void gemm_loop(float (&acc)[128], Cons& c, int nk) {
  gemm_step<N, true>(acc, c);
#pragma unroll 1
  for (int k = 1; k < nk; k++) gemm_step<N, false>(acc, c);
  wg_wait<0>();
  c.release(c.g - 1);
  fence_regs(acc);
}
template <int N, int NB>
__device__ __forceinline__ void gemm_loop_flush(float (&acc)[128], Cons& c, const uint32_t (&pend)[NB * 16], bool flush) {
  gemm_step<N, true>(acc, c);
#pragma unroll 1
  for (int k = 1; k < 16; k++) {
    gemm_step<N, false>(acc, c);
    if (k == 3 && flush) {
      c.stg_acquire();
      stage_boxes<NB>(pend, 0, c);
    }
  }
  wg_wait<0>();
  c.release(c.g - 1);
  fence_regs(acc);
}
template <int NB>
__device__ __forceinline__ void h_epilogue(const float (&acc)[128], Cons& c, uint32_t (&pend)[NB * 16]) {
  uint32_t r[32];
#pragma unroll
  for (int i = 0; i < 32; i++) r[i] = pack_bf16_relu(acc[2 * i], acc[2 * i + 1]);
  c.stg_acquire();
  stage_boxes<2>(r, 0, c);
#pragma unroll
  for (int i = 0; i < NB * 16; i++) pend[i] = pack_bf16_relu(acc[64 + 2 * i], acc[65 + 2 * i]);
}

__device__ __forceinline__ uint32_t silu2(uint32_t f2) {
  const float a = bf_lo(f2), b = bf_hi(f2);
  const float ta = ex2(-1.4426950408889634f * fabsf(a)), tb = ex2(-1.4426950408889634f * fabsf(b));
  const float da = 1.0f + ta, db = 1.0f + tb;
  const float r = rcp(da * db);
  return pack_bf16((a >= 0.f ? a : a * ta) * (r * db), (b >= 0.f ? b : b * tb) * (r * da));
}

constexpr float SM_C = 0.08838834764831845f * 1.4426950408889634f;

#define ONCE(c) _Pragma("unroll 1") for (uint32_t once_ = 0; once_ <= (c).zero; once_++)
__device__ __forceinline__ void row_max2(const float (&S)[64], float& n0, float& n1) {
  float x[4], y[4];
#pragma unroll
  for (int i = 0; i < 4; i++) { x[i] = fmaxf(S[4 * i], S[4 * i + 1]); y[i] = fmaxf(S[4 * i + 2], S[4 * i + 3]); }
#pragma unroll
  for (int i = 4; i < 16; i++) {
    x[i & 3] = fmaxf(x[i & 3], fmaxf(S[4 * i], S[4 * i + 1]));
    y[i & 3] = fmaxf(y[i & 3], fmaxf(S[4 * i + 2], S[4 * i + 3]));
  }
  n0 = fmaxf(fmaxf(x[0], x[1]), fmaxf(x[2], x[3]));
  n1 = fmaxf(fmaxf(y[0], y[1]), fmaxf(y[2], y[3]));
  n0 = fmaxf(n0, __shfl_xor_sync(~0u, n0, 1));
  n1 = fmaxf(n1, __shfl_xor_sync(~0u, n1, 1));
  n0 = fmaxf(n0, __shfl_xor_sync(~0u, n0, 2));
  n1 = fmaxf(n1, __shfl_xor_sync(~0u, n1, 2));
}
__device__ __forceinline__ void to_exponent(float (&S)[64], float cc0, float cc1) {
#pragma unroll
  for (int i = 0; i < 16; i++) {
    S[4 * i] = fmaf(S[4 * i], SM_C, cc0); S[4 * i + 1] = fmaf(S[4 * i + 1], SM_C, cc0);
    S[4 * i + 2] = fmaf(S[4 * i + 2], SM_C, cc1); S[4 * i + 3] = fmaf(S[4 * i + 3], SM_C, cc1);
  }
}
__device__ __forceinline__ void scale_o(float (&O)[64], float f0, float f1) {
#pragma unroll
  for (int i = 0; i < 16; i++) { O[4 * i] *= f0; O[4 * i + 1] *= f0; O[4 * i + 2] *= f1; O[4 * i + 3] *= f1; }
}
template <int G0>
__device__ __forceinline__ void exp_pack(const float (&S)[64], uint32_t (&p)[32], float (&a)[4]) {
#pragma unroll
  for (int i = G0; i < 16; i++) {
    const float e0 = ex2(S[4 * i]), e1 = ex2(S[4 * i + 1]), e2 = ex2(S[4 * i + 2]), e3 = ex2(S[4 * i + 3]);
    a[0] += e0; a[1] += e1; a[2] += e2; a[3] += e3;
    p[2 * i] = pack_bf16(e0, e1);
    p[2 * i + 1] = pack_bf16(e2, e3);
  }
}
#define EARLY 4
__device__ __forceinline__ void softmax_early(float (&S)[64], float cc0, float cc1, float (&a)[4], uint32_t (&pe)[2 * EARLY + 1], const Cons& c) {
  a[0] = a[1] = a[2] = a[3] = 0.f;
  ONCE(c) {
    to_exponent(S, cc0, cc1);
#pragma unroll
    for (int i = 0; i < EARLY; i++) {
      const float e0 = ex2(S[4 * i]), e1 = ex2(S[4 * i + 1]), e2 = ex2(S[4 * i + 2]), e3 = ex2(S[4 * i + 3]);
      a[0] += e0; a[1] += e1; a[2] += e2; a[3] += e3;
      pe[2 * i] = pack_bf16(e0, e1);
      pe[2 * i + 1] = pack_bf16(e2, e3);
    }
  }
}
__device__ __forceinline__ void softmax_late(float (&S)[64], uint32_t (&p)[32], float (&O)[64], float& cc0, float& cc1, float& l0, float& l1,
                                             float (&a)[4], const uint32_t (&pe)[2 * EARLY + 1], uint32_t zero) {
#pragma unroll
  for (int i = 0; i < 2 * EARLY; i++) p[i] = pe[i] ^ zero;
  exp_pack<EARLY>(S, p, a);
  if (__any_sync(~0u, !(fmaxf(a[0] + a[1], a[2] + a[3]) <= 65536.f))) {
    float d0, d1;
    row_max2(S, d0, d1);
    d0 = fmaxf(d0, 0.f); d1 = fmaxf(d1, 0.f);
#pragma unroll
    for (int i = 0; i < 16; i++) { S[4 * i] -= d0; S[4 * i + 1] -= d0; S[4 * i + 2] -= d1; S[4 * i + 3] -= d1; }
    cc0 -= d0; cc1 -= d1;
    const float f0 = ex2(-d0), f1 = ex2(-d1);
    scale_o(O, f0, f1);
    l0 *= f0; l1 *= f1;
    a[0] = a[1] = a[2] = a[3] = 0.f;
    exp_pack<0>(S, p, a);
  }
  l0 += a[0] + a[1];
  l1 += a[2] + a[3];
}

__device__ __forceinline__ void inv_rowsum(float l0, float l1, float& i0, float& i1) {
  l0 += __shfl_xor_sync(~0u, l0, 1); l1 += __shfl_xor_sync(~0u, l1, 1);
  l0 += __shfl_xor_sync(~0u, l0, 2); l1 += __shfl_xor_sync(~0u, l1, 2);
  i0 = rcp(l0); i1 = rcp(l1);
}
__device__ __forceinline__ void write_o(const float (&O)[64], const Cons& c) {
  uint32_t rowoff, xr;
  frag_addr(rowoff, xr);
  const uint32_t stg = c.sb + SM_STG + c.wg * 16384 + rowoff;
#pragma unroll
  for (int kb = 0; kb < 8; kb++)
    stsm4(stg + (kb >> 2) * 8192 + ((32 * (kb & 3)) ^ xr),
          pack_bf16(O[8 * kb], O[8 * kb + 1]), pack_bf16(O[8 * kb + 2], O[8 * kb + 3]),
          pack_bf16(O[8 * kb + 4], O[8 * kb + 5]), pack_bf16(O[8 * kb + 6], O[8 * kb + 7]));
  c.stg_publish();
}

__device__ __forceinline__ void issue_qk(float (&S)[64], const uint32_t (&q)[32], uint32_t s0, uint32_t s1, uint32_t zero) {
  const uint64_t d0 = mkdesc(s0, 16, 1024), d1 = mkdesc(s1, 16, 1024);
#pragma unroll
  for (int kk = 0; kk < 8; kk++)
    wgmma_rs_n128(S, q[4 * kk], q[4 * kk + 1], q[4 * kk + 2], q[4 * kk + 3], (kk < 4 ? d0 : d1) + (kk & 3) * 2, kk > 0 ? 1u : zero);
}
__device__ __forceinline__ void issue_pv(float (&O)[64], const uint32_t (&p)[32], uint32_t s0, uint32_t s1, uint32_t accum) {
  const uint64_t d0 = mkdesc(s0, 8192, 1024), d1 = mkdesc(s1, 8192, 1024);
#pragma unroll
  for (int kk = 0; kk < 8; kk++)
    wgmma_rs_n128_tb(O, p[4 * kk], p[4 * kk + 1], p[4 * kk + 2], p[4 * kk + 3], (kk < 4 ? d0 : d1) + (kk & 3) * 128, kk > 0 ? 1u : accum);
}

#define TURN_SYNC()   bar_sync(1 + c.wg, 256)
#define TURN_PASS()   bar_arrive(2 - c.wg, 256)

__device__ __forceinline__ void attn_tile(const float (&acc)[128], Cons& c, int t) {
  uint32_t q[32], p[32];
  float S[64], O[64];
  const uint32_t stash = c.sb + SM_STG + c.wg * 16384 + ((threadIdx.x >> 5) & 3) * 2048 + c.lane * 16;
#pragma unroll
  for (int i = 0; i < 32; i++) q[i] = pack_bf16(acc[2 * i], acc[2 * i + 1]);
  c.stg_acquire();
#pragma unroll
  for (int i = 0; i < 8; i++)
    sts128(stash + (i >> 2) * 8192 + (i & 3) * 512, pack_bf16(acc[64 + 8 * i], acc[65 + 8 * i]), pack_bf16(acc[66 + 8 * i], acc[67 + 8 * i]),
           pack_bf16(acc[68 + 8 * i], acc[69 + 8 * i]), pack_bf16(acc[70 + 8 * i], acc[71 + 8 * i]));
  fence_regs(q);
  TR(0, 0);
  TURN_SYNC();
  TR(0, 1);
  c.wait_full(c.g);
  wg_fence();
  issue_qk(O, q, c.sb + c.pos * SLOT, c.sb + wrap12(c.pos + 1) * SLOT, 0);
  wg_commit();
  c.wait_full(c.g + 1);
  wg_fence();
  issue_qk(S, q, c.sb + wrap12(c.pos + 2) * SLOT, c.sb + wrap12(c.pos + 3) * SLOT, 0);
  wg_commit();
  TURN_PASS();
  TR(0, 2);
  wg_wait<1>();
  TR(0, 3);
  fence_regs(O);
  c.release(c.g);
  float cc0, cc1, l0, l1, f0 = 0.f, f1 = 0.f;
  float a[4] = {0.f, 0.f, 0.f, 0.f};
  uint32_t pe[2 * EARLY + 1];
  row_max2(O, cc0, cc1);
  cc0 *= -SM_C; cc1 *= -SM_C;
  ONCE(c) { to_exponent(O, cc0, cc1); }
  wg_wait<0>();
  fence_regs(S);
  fence_regs(q);
  c.release(c.g + 1);
  exp_pack<0>(O, p, a);
  l0 = a[0] + a[1];
  l1 = a[2] + a[3];
  c.pos = wrap12(c.pos + 4);
  TR(1, 0);
  TURN_SYNC();
  TR(1, 1);
  c.wait_full(c.g + 2);
  wg_fence();
  issue_pv(O, p, c.sb + c.pos * SLOT, c.sb + wrap12(c.pos + 1) * SLOT, 0);
  wg_commit();
  TURN_PASS();
  TR(1, 2);
  softmax_early(S, cc0, cc1, a, pe, c);
  TR(1, 4);
  wg_wait<0>();
  TR(1, 5);
  fence_regs(O);
  fence_regs(p);
  c.release(c.g + 2);
  c.g += 3;
  c.pos = wrap12(c.pos + 2);
  softmax_late(S, p, O, cc0, cc1, l0, l1, a, pe, c.zero);
#pragma unroll 1
  for (int j = 1; j < 7 + (int)c.zero; j++) {
    const uint32_t k0 = c.pos, k1 = wrap12(k0 + 1), v0 = wrap12(k0 + 2), v1 = wrap12(k0 + 3);
    TR(j + 1, 0);
    TURN_SYNC();
    TR(j + 1, 1);
    c.wait_full(c.g);
    wg_fence();
    issue_qk(S, q, c.sb + k0 * SLOT, c.sb + k1 * SLOT, 0);
    wg_commit();
    if (j == 4) {
      scale_o(O, f0, f1);
      write_o(O, c);
    }
    c.wait_full(c.g + 1);
    wg_fence();
    issue_pv(O, p, c.sb + v0 * SLOT, c.sb + v1 * SLOT, j != 4);
    wg_commit();
    TURN_PASS();
    TR(j + 1, 2);
    wg_wait<1>();
    TR(j + 1, 3);
    fence_regs(S);
    fence_regs(q);
    c.release(c.g);
    if (j == 3) {
      row_max2(S, cc0, cc1);
      cc0 *= -SM_C; cc1 *= -SM_C;
      inv_rowsum(l0, l1, f0, f1);
      l0 = 0.f; l1 = 0.f;
    }
    softmax_early(S, cc0, cc1, a, pe, c);
    if (j == 2) {
#pragma unroll
      for (int i = 0; i < 8; i++) lds128(stash + (i >> 2) * 8192 + (i & 3) * 512, q[4 * i], q[4 * i + 1], q[4 * i + 2], q[4 * i + 3]);
      __syncwarp();
    }
    TR(j + 1, 4);
    wg_wait<0>();
    TR(j + 1, 5);
    fence_regs(O);
    fence_regs(p);
    c.release(c.g + 1);
    c.g += 2;
    c.pos = wrap12(v1 + 1);
    softmax_late(S, p, O, cc0, cc1, l0, l1, a, pe, c.zero);
  }
  TR(8, 0);
  TURN_SYNC();
  TR(8, 1);
  c.wait_full(c.g);
  wg_fence();
  issue_pv(O, p, c.sb + c.pos * SLOT, c.sb + wrap12(c.pos + 1) * SLOT, 1);
  wg_commit();
  TURN_PASS();
  TR(8, 2);
  c.stg_acquire();
  float a0, a1;
  inv_rowsum(l0, l1, a0, a1);
  wg_wait<0>();
  TR(8, 5);
  fence_regs(O);
  fence_regs(p);
  c.release(c.g);
  c.g++;
  c.pos = wrap12(c.pos + 2);
  scale_o(O, a0, a1);
  write_o(O, c);
  TR(9, 0);
}

struct Prod {
  uint32_t sb, g, pos, head, tail_g, tail_pos, hist;
  __device__ __forceinline__ uint32_t full() const { return sb + SM_BAR + B_FULL + (g & 7) * 8; }
  __device__ __forceinline__ uint32_t slot(uint32_t i) const { return sb + wrap12(pos + i) * SLOT; }
  __device__ __forceinline__ void acquire(uint32_t size) {
#pragma unroll 1
    while (head + size - tail_pos > NSLOT) {
      mbar_wait(sb + SM_BAR + B_EMPTY + (tail_g & 7) * 8, (tail_g >> 3) & 1);
      tail_pos += 2 + ((hist >> (tail_g & 31)) & 1);
      tail_g++;
    }
    hist = (hist & ~(1u << (g & 31))) | ((size - 2) << (g & 31));
  }
  __device__ __forceinline__ void advance(uint32_t size) { g++; head += size; pos = wrap12(pos + size); }
};

__device__ __forceinline__ void wait_flag(const unsigned* p, unsigned target) {
  while ((int)(ld_acquire(p) - target) < 0) {}
  fence_async_all();
}

__device__ __forceinline__ void init_barriers(uint32_t sb, int warp) {
  const uint32_t cnt = warp < 4 ? 1 : warp < 8 ? 16 : warp == 8 ? 4 : warp == 9 ? 1 : 11;
  if (warp < 11) mbar_init(sb + SM_BAR + warp * 16, cnt);
  if (warp < 10) mbar_init(sb + SM_BAR + warp * 16 + 8, cnt);
  asm volatile("fence.mbarrier_init.release.cluster;" ::: "memory");
}

#define TSP(i) do {} while (0)

__global__ void __cluster_dims__(2, 1, 1) __launch_bounds__(384, 1) fused_kernel(const __grid_constant__ Params P) {
  extern __shared__ uint8_t smem_raw[];
  const uint32_t sb = (smem_u32(smem_raw) + 1023u) & ~1023u;
  const int warp = __shfl_sync(~0u, (int)(threadIdx.x >> 5), 0);
  const int lane = threadIdx.x & 31;
  const int rank = blockIdx.x & 1;
  const int cl = blockIdx.x >> 1;
  const int j = cl >> 3;
  const int rb = (cl & 7) * 2 + rank;
  const bool is_s = j < 4, spare = j == 8;
  const int row0 = rb * 128;
  Flags* fl = P.flags;

  if (warp >= 8) {
    unsigned ep0 = 0;
    if (warp == 8) asm volatile("ld.volatile.global.u32 %0, [%1];" : "=r"(ep0) : "l"(&fl->epoch[blockIdx.x]));
    if (lane == 0) {
      if (warp == 8) prefetch_map(spare ? &P.w1b4 : &P.w1b3);
      if (warp == 9) prefetch_map(&P.act_ld);
      init_barriers(sb, warp);
    }
    __syncwarp();
    cluster_arrive();
    if (warp == 10 && lane == 0) {
      prefetch_map(&P.act_st); prefetch_map(&P.wq); prefetch_map(&P.k_ld); prefetch_map(&P.v_ld);
      prefetch_map(is_s ? &P.wo : &P.w2); prefetch_map(&P.x_ld); prefetch_map(&P.out_st);
    }
    __syncwarp();
    cluster_wait();
    asm volatile("setmaxnreg.dec.sync.aligned.u32 24;");
    if (warp == 8) {
      TSP(17);
#define ep1 (ep0 + 1)
      Prod p{sb, 0, 0, 0, 0, 0, 0};
#define LDA(dst, m, bar, c0, c1) tma_ld2(dst, m, bar, c0, c1)
#define LDW1(dst, m, bar, c0, c1, c2) tma_ld3_mc(dst, m, bar, c0, c1, c2)
#define LDW(dst, m, bar, c0, c1, c2) tma_ld3_mc(dst, m, bar, c0, c1, c2)
      {
        const CUtensorMap* mb = spare ? &P.w1b4 : &P.w1b3;
        const uint32_t bytes = spare ? 49152 : 40960;
        const int nt = spare ? 8 : 2;
#pragma unroll 1
        for (int t = 0; t < nt; t++) {
          const int r = spare ? ((cl & 1) * 4 + (t >> 1)) * 2 + rank : rb;
          const int nb0 = spare ? (H_SPARE0 >> 6) + (t & 1) * 4 : j * 6 + t * 3;
          int k = 0;
          if (t == 0) {
#pragma unroll 1
            for (; k < 4; k++) {
              p.acquire(3);
              if (lane == 0) { mbar_expect_tx(p.full(), bytes); LDW1(p.slot(1 + rank), mb, p.full(), 0, k * 64 + rank * 32, nb0); }
              p.advance(3);
            }
            TSP(14);
            asm volatile("" : "+r"(ep0));
            wait_flag(&fl->ln[r][0], ep1 * 64);
            TSP(15);
            if (lane == 0)
              for (int i = 0; i < 4; i++) tma_ld2(sb + i * 3 * SLOT, &P.act_ld, sb + SM_BAR + B_FULL + i * 8, C_XN + i * 64, r * 128);
          } else if (spare && !(t & 1)) {
            wait_flag(&fl->ln[r][0], ep1 * 64);
          }
#pragma unroll 1
          for (; k < 16; k++) {
            p.acquire(3);
            if (lane == 0) {
              mbar_expect_tx(p.full(), bytes);
              LDW1(p.slot(1 + rank), mb, p.full(), 0, k * 64 + rank * 32, nb0);
              tma_ld2(p.slot(0), &P.act_ld, p.full(), C_XN + k * 64, r * 128);
            }
            p.advance(3);
          }
        }
      }
      if (!spare) {
        const int kvrow = (j >> 1) * SK + KV0;
#pragma unroll 1
        for (int t = 0; t < 2; t++) {
          const int nb0 = (4 * j + 2 * t) * 2;
#pragma unroll 1
          for (int k = 0; k < 16; k++) {
            p.acquire(3);
            if (lane == 0) {
              mbar_expect_tx(p.full(), 49152);
              LDW1(p.slot(1 + rank), &P.wq, p.full(), 0, k * 64 + rank * 32, nb0);
              tma_ld2(p.slot(0), &P.act_ld, p.full(), C_XN + k * 64, row0);
            }
            p.advance(3);
          }
#pragma unroll 1
          for (int i = 0; i < 16; i++) {
            const bool is_k = i == 0 || (i < 15 && (i & 1));
            const int ch = (is_k ? ((i + 1) >> 1) : (i == 15 ? 7 : (i >> 1) - 1)) & 3;
            p.acquire(2);
            if (lane == 0) {
              mbar_expect_tx(p.full(), 32768);
              if (is_k) tma_ld2_mc(p.slot(rank), &P.k_ld, p.full(), rank * 64, kvrow + ch * 128);
              else      tma_ld3_mc(p.slot(rank), &P.v_ld, p.full(), 0, kvrow + ch * 128 + rank * 64, 0);
            }
            p.advance(2);
            if (t == 1 && i == 8 && !is_s) wait_flag(&fl->h[rb][0], ep1 * 64);
          }
        }
        const int jn = j & 3;
        if (is_s) {
          unsigned ready = 0;
#pragma unroll 1
          for (int i = 0; i < 64; i++) {
            const int hi = i >> 1;
            const int head = 4 * ((hi & 15) >> 1) + (hi & 1) + ((hi >> 4) << 1);
            const int kc = head * 128 + (i & 1) * 64;
            p.acquire(3);
            if (lane == 0) { mbar_expect_tx(p.full(), 49152); LDW(p.slot(1 + rank), &P.wo, p.full(), 0, kc + rank * 32, jn * 4); }
            if (!((ready >> head) & 1)) {
              do { ready = __ballot_sync(~0u, (int)(ld_acquire(&fl->o[rb][lane]) - ep1 * 2) >= 0); } while (!((ready >> head) & 1));
              __syncwarp();
              fence_async_all();
            }
            if (lane == 0) LDA(p.slot(0), &P.act_ld, p.full(), C_O + kc, row0);
            if (i == 56 && lane == 0) {
              prefetch_map(&P.x_ld); prefetch_map(&P.out_st);
              for (int q = 0; q < 4; q++) tma_pf2(&P.x_ld, jn * 256 + q * 64, row0);
            }
            p.advance(3);
          }
          bool g_ready = (int)(ld_acquire(&fl->g[rb][jn]) - ep1 * 4) >= 0;
#pragma unroll 1
          for (int i = 0; i < 4; i++) {
            p.acquire(2);
            if (i == 2) { TSP(20); if (g_ready) fence_async_all(); else wait_flag(&fl->g[rb][jn], ep1 * 4); TSP(21); }
            if (lane == 0) {
              mbar_expect_tx(p.full(), 32768);
              const CUtensorMap* m = i < 2 ? &P.x_ld : &P.act_ld;
              const int c0 = (i < 2 ? 0 : C_G) + jn * 256 + (i & 1) * 128;
              tma_ld2(p.slot(0), m, p.full(), c0, row0);
              tma_ld2(p.slot(1), m, p.full(), c0 + 64, row0);
            }
            p.advance(2);
          }
        } else {
#pragma unroll 1
          for (int k = 0; k < 56; k++) {
            p.acquire(3);
            if (lane == 0) { mbar_expect_tx(p.full(), 49152); LDW(p.slot(1 + rank), &P.w2, p.full(), 0, k * 64 + rank * 32, jn * 4); }
            if (k == H_SPARE0 / 64) wait_flag(&fl->h[rb][16], ep1 * 8);
            if (lane == 0) LDA(p.slot(0), &P.act_ld, p.full(), C_H + k * 64, row0);
            p.advance(3);
          }
        }
      }
      if (lane == 0) { *(volatile unsigned*)&fl->epoch[blockIdx.x] = ep1; mbar_arrive(sb + SM_BAR + B_DONE); }
    } else if (warp < 11) {
      const int wg = warp - 9;
      if (lane == 0) {
        const uint32_t stg = sb + SM_STG + wg * 16384;
        const int nev = spare ? 16 : is_s ? 8 : 10;
#pragma unroll 1
        for (int n = 0; n < nev; n++) {
          int col, row = row0, nbox = 2;
          unsigned* flag;
          if (spare) {
            const int r = ((cl & 1) * 4 + (n >> 2)) * 2 + rank;
            row = r * 128;
            col = C_H + H_SPARE0 + (n & 3) * 128;
            flag = &fl->h[r][16];
          } else if (n < 4) {
            col = C_H + j * H_REG + (n >> 1) * 192 + (n & 1) * 128;
            nbox = 2 - (n & 1);
            flag = &fl->h[rb][0];
          } else if (n < 8) {
            col = C_O + (4 * j + n - 4) * 128;
            flag = &fl->o[rb][4 * j + n - 4];
          } else {
            col = C_G + (j & 3) * 256 + (n - 8) * 128;
            flag = &fl->g[rb][j & 3];
          }
          mbar_wait(sb + SM_BAR + B_SFULL + wg * 8, n & 1);
          if (n == 9 && wg == 0) TSP(20);
          tma_st2(&P.act_st, stg, col, row + wg * 64);
          if (nbox == 2) tma_st2(&P.act_st, stg + 8192, col + 64, row + wg * 64);
          bulk_commit();
          bulk_wait_read0();
          mbar_arrive(sb + SM_BAR + B_SEMPTY + wg * 8);
          if (n == 9 && wg == 0) TSP(21);
          bulk_wait0();
          if (n == 9 && wg == 0) TSP(22);
          fence_async_all();
          red_release(flag, 1);
          if (n == 9 && wg == 0) TSP(23);
        }
        mbar_arrive(sb + SM_BAR + B_DONE);
      }
    } else {
      if (lane == 0) {
        const unsigned long long t0 = gtime();
        while (!mbar_try(sb + SM_BAR + B_DONE, 0)) {
          if (gtime() - t0 > 2000000000ull) __trap();
        }
      }
    }
    __syncwarp();
    cluster_arrive();
    cluster_wait();
  } else {
    const int wg = warp >> 2;
    TS(0);
    if (!spare) {
      const int r = row0 + j * 16 + warp * 2;
      uint32_t v[2][16];
#pragma unroll
      for (int a = 0; a < 2; a++)
#pragma unroll
        for (int i = 0; i < 4; i++)
          *(uint4*)&v[a][4 * i] = __ldg((const uint4*)(P.x + (size_t)(r + a) * DM + i * 256 + lane * 8));
      if (lane == 0) init_barriers(sb, warp);
      __syncwarp();
      cluster_arrive();
      float s[2], q[2];
#pragma unroll
      for (int a = 0; a < 2; a++) {
        float t0 = 0.f, t1 = 0.f;
#pragma unroll
        for (int i = 0; i < 16; i++) { t0 += bf_lo(v[a][i]); t1 += bf_hi(v[a][i]); }
        s[a] = t0 + t1;
      }
#pragma unroll
      for (int o = 16; o; o >>= 1) { s[0] += __shfl_xor_sync(~0u, s[0], o); s[1] += __shfl_xor_sync(~0u, s[1], o); }
#pragma unroll
      for (int a = 0; a < 2; a++) {
        s[a] *= 1.0f / DM;
        float t0 = 0.f, t1 = 0.f;
#pragma unroll
        for (int i = 0; i < 16; i++) {
          const float d0 = bf_lo(v[a][i]) - s[a], d1 = bf_hi(v[a][i]) - s[a];
          t0 = fmaf(d0, d0, t0); t1 = fmaf(d1, d1, t1);
        }
        q[a] = t0 + t1;
      }
#pragma unroll
      for (int o = 16; o; o >>= 1) { q[0] += __shfl_xor_sync(~0u, q[0], o); q[1] += __shfl_xor_sync(~0u, q[1], o); }
#pragma unroll
      for (int a = 0; a < 2; a++) {
        const uint32_t mb2 = pack_bf16(s[a], s[a]);
        const float inv = 1.0f / bf_round(sqrtf(bf_round(bf_round(q[a] * (1.0f / DM)) + 1e-5f)));
#pragma unroll
        for (int i = 0; i < 16; i++) {
          const __nv_bfloat162 d = __hsub2_rn(*(const __nv_bfloat162*)&v[a][i], *(const __nv_bfloat162*)&mb2);
          const uint32_t du = *(const uint32_t*)&d;
          v[a][i] = pack_bf16(bf_lo(du) * inv, bf_hi(du) * inv);
        }
#pragma unroll
        for (int i = 0; i < 4; i++)
          *(uint4*)(P.act + (size_t)(r + a) * ACT_W + C_XN + i * 256 + lane * 8) = *(const uint4*)&v[a][4 * i];
      }
      TS(11);
      fence_async_all();
      TS(12);
      __syncwarp();
      if (lane == 0) red_release(&fl->ln[rb][0], 1);
      TS(13);
    } else {
      if (lane == 0) init_barriers(sb, warp);
      __syncwarp();
      cluster_arrive();
    }
    cluster_wait();
    asm volatile("setmaxnreg.inc.sync.aligned.u32 240;");
    Cons c;
    c.zero = blockIdx.y; c.sb = sb; c.g = 0; c.pos = 0; c.nstg = 0; c.wg = wg; c.lane = lane;
    c.rel = mapa(sb + SM_BAR + B_EMPTY, lane & 1);
    float acc[128];
    TS(1);
    if (spare) {
      uint32_t pend[32];
#pragma unroll
      for (int i = 0; i < 32; i++) pend[i] = 0;
#pragma unroll 1
      for (int t = 0; t < 8; t++) {
        gemm_loop_flush<256, 2>(acc, c, pend, t > 0);
        h_epilogue<2>(acc, c, pend);
      }
      c.stg_acquire();
      stage_boxes<2>(pend, 0, c);
      TS(6);
    } else {
      if (wg == 1) bar_arrive(1, 256);
      {
        uint32_t pend[16];
#pragma unroll
        for (int i = 0; i < 16; i++) pend[i] = 0;
#pragma unroll 1
        for (int t = 0; t < 2; t++) {
          gemm_loop_flush<192, 1>(acc, c, pend, t > 0);
          h_epilogue<1>(acc, c, pend);
          TS(2 + t);
        }
        gemm_loop_flush<256, 1>(acc, c, pend, true);
      }
#pragma unroll 1
      for (int t = 0; t < 2; t++) {
        TS(8 + t);
        attn_tile(acc, c, t);
        TS(4 + t);
        gemm_loop<256>(acc, c, t == 0 ? 16 : is_s ? 64 : 56);
      }
      TS(6);
      const uint32_t x0 = c.pos;
      const uint32_t woff = ((tid_x() >> 5) & 3) * 2048 + lane * 16;
#pragma unroll 1
      for (int hh = 0; hh < 2; hh++) {
        if (is_s) { if (hh == 0) c.stg_acquire(); } else c.stg_acquire();
        {
          uint32_t rowoff, xr;
          frag_addr(rowoff, xr);
          const uint32_t stg = sb + SM_STG + wg * 16384 + rowoff;
          if (hh == 0) {
#pragma unroll
            for (int kb = 0; kb < 8; kb++)
              stsm4(stg + (kb >> 2) * 8192 + ((32 * (kb & 3)) ^ xr), pack_bf16(acc[8 * kb], acc[8 * kb + 1]), pack_bf16(acc[8 * kb + 2], acc[8 * kb + 3]),
                    pack_bf16(acc[8 * kb + 4], acc[8 * kb + 5]), pack_bf16(acc[8 * kb + 6], acc[8 * kb + 7]));
          } else {
#pragma unroll
            for (int kb = 8; kb < 16; kb++)
              stsm4(stg + ((kb >> 2) & 1) * 8192 + ((32 * (kb & 3)) ^ xr), pack_bf16(acc[8 * kb], acc[8 * kb + 1]), pack_bf16(acc[8 * kb + 2], acc[8 * kb + 3]),
                    pack_bf16(acc[8 * kb + 4], acc[8 * kb + 5]), pack_bf16(acc[8 * kb + 6], acc[8 * kb + 7]));
          }
        }
        __syncwarp();
        const uint32_t sa = sb + SM_STG + wg * 16384 + woff;
        if (is_s) {
          c.wait_full(c.g + hh);
          c.wait_full(c.g + 2 + hh);
          if (hh == 0) TS(22); else TS(23);
#pragma unroll 1
          for (int bx = 0; bx < 2; bx++) {
            const uint32_t xa = sb + wrap12(x0 + 2 * hh + bx) * SLOT + wg * 8192 + woff;
            const uint32_t ga = sb + wrap12(wrap12(x0 + 4) + 2 * hh + bx) * SLOT + wg * 8192 + woff;
            uint32_t sv[16], xv[16], gv[16];
#pragma unroll
            for (int i = 0; i < 4; i++) {
              lds128(sa + bx * 8192 + i * 512, sv[4 * i], sv[4 * i + 1], sv[4 * i + 2], sv[4 * i + 3]);
              lds128(ga + i * 512, gv[4 * i], gv[4 * i + 1], gv[4 * i + 2], gv[4 * i + 3]);
              lds128(xa + i * 512, xv[4 * i], xv[4 * i + 1], xv[4 * i + 2], xv[4 * i + 3]);
            }
#pragma unroll
            for (int i = 0; i < 16; i++) {
              const __nv_bfloat162 pr = __hmul2_rn(*(const __nv_bfloat162*)&sv[i], *(const __nv_bfloat162*)&gv[i]);
              const __nv_bfloat162 o = __hadd2_rn(*(const __nv_bfloat162*)&xv[i], pr);
              xv[i] = *(const uint32_t*)&o;
            }
#pragma unroll
            for (int i = 0; i < 4; i++) sts128(xa + i * 512, xv[4 * i], xv[4 * i + 1], xv[4 * i + 2], xv[4 * i + 3]);
          }
          fence_async_smem();
          bar_sync(3 + wg, 128);
          if ((threadIdx.x & 127) == 0) {
            tma_st2(&P.out_st, sb + wrap12(x0 + 2 * hh) * SLOT + wg * 8192, (j & 3) * 256 + hh * 128, row0 + wg * 64);
            tma_st2(&P.out_st, sb + wrap12(x0 + 2 * hh + 1) * SLOT + wg * 8192, (j & 3) * 256 + hh * 128 + 64, row0 + wg * 64);
            bulk_commit();
          }
        } else {
#pragma unroll 1
          for (int i = 0; i < 8; i++) {
            const uint32_t a = sa + (i >> 2) * 8192 + (i & 3) * 512;
            uint32_t v0, v1, v2, v3;
            lds128(a, v0, v1, v2, v3);
            sts128(a, silu2(v0), silu2(v1), silu2(v2), silu2(v3));
          }
          c.stg_publish();
          if (hh == 0) TS(22);
        }
      }
      TS(24);
      if (is_s && (threadIdx.x & 127) == 0) bulk_wait_read0();
    }
    TS(7);
    __syncwarp();
    if (lane == 0) mbar_arrive(sb + SM_BAR + B_DONE);
    cluster_arrive();
    cluster_wait();
  }
}

typedef CUresult (*EncodeFn)(CUtensorMap*, CUtensorMapDataType, cuuint32_t, void*, const cuuint64_t*, const cuuint64_t*,
                             const cuuint32_t*, const cuuint32_t*, CUtensorMapInterleave, CUtensorMapSwizzle,
                             CUtensorMapL2promotion, CUtensorMapFloatOOBfill);

void map2d(EncodeFn enc, CUtensorMap* m, const void* base, uint64_t cols, uint64_t rows, uint32_t box_rows) {
  cuuint64_t dims[2] = {cols, rows};
  cuuint64_t strides[1] = {cols * 2};
  cuuint32_t box[2] = {64, box_rows};
  cuuint32_t es[2] = {1, 1};
  enc(m, CU_TENSOR_MAP_DATA_TYPE_BFLOAT16, 2, (void*)base, dims, strides, box, es, CU_TENSOR_MAP_INTERLEAVE_NONE,
      CU_TENSOR_MAP_SWIZZLE_128B, CU_TENSOR_MAP_L2_PROMOTION_L2_256B, CU_TENSOR_MAP_FLOAT_OOB_FILL_NONE);
}
void map3d(EncodeFn enc, CUtensorMap* m, const void* base, uint64_t cols, uint64_t rows, uint32_t box_rows, uint32_t box_blks) {
  cuuint64_t dims[3] = {64, rows, cols / 64};
  cuuint64_t strides[2] = {cols * 2, 128};
  cuuint32_t box[3] = {64, box_rows, box_blks};
  cuuint32_t es[3] = {1, 1, 1};
  enc(m, CU_TENSOR_MAP_DATA_TYPE_BFLOAT16, 3, (void*)base, dims, strides, box, es, CU_TENSOR_MAP_INTERLEAVE_NONE,
      CU_TENSOR_MAP_SWIZZLE_128B, CU_TENSOR_MAP_L2_PROMOTION_L2_256B, CU_TENSOR_MAP_FLOAT_OOB_FILL_NONE);
}

}

extern "C" void kernel_launch(void* const* d_in, const int* in_sizes, int n_in, void* d_out, int out_size) {
  (void)in_sizes; (void)n_in; (void)out_size;
  static EncodeFn enc = nullptr;
  static void* act = nullptr;
  static void* flags = nullptr;
  if (!enc) {
    void* fn = nullptr;
    cudaDriverEntryPointQueryResult qr;
    cudaGetDriverEntryPoint("cuTensorMapEncodeTiled", &fn, cudaEnableDefault, &qr);
    enc = (EncodeFn)fn;
    cudaGetSymbolAddress(&act, g_act);
    cudaGetSymbolAddress(&flags, g_flags);
    cudaFuncSetAttribute(fused_kernel, cudaFuncAttributeMaxDynamicSharedMemorySize, SMEM_BYTES);
  }
  Params P;
  map2d(enc, &P.act_ld, act, ACT_W, SEQ, 128);
  map2d(enc, &P.act_st, act, ACT_W, SEQ, 64);
  map2d(enc, &P.x_ld, d_in[0], DM, SEQ, 128);
  map2d(enc, &P.out_st, d_out, DM, SEQ, 64);
  map2d(enc, &P.k_ld, d_in[1], 128, 4 * SK, 128);
  map3d(enc, &P.v_ld, d_in[2], 128, 4 * SK, 64, 2);
  map3d(enc, &P.wq, d_in[3], NQ, DM, 32, 4);
  map3d(enc, &P.w1b4, d_in[6], DFF, DM, 32, 4);
  map3d(enc, &P.w1b3, d_in[6], DFF, DM, 32, 3);
  map3d(enc, &P.wo, d_in[4], DM, NQ, 32, 4);
  map3d(enc, &P.w2, d_in[7], DM, DFF, 32, 4);
  P.x = (const __nv_bfloat16*)d_in[0];
  P.act = (__nv_bfloat16*)act;
  P.flags = (Flags*)flags;
  fused_kernel<<<NCLUSTER * 2, 384, SMEM_BYTES>>>(P);
}
```

```cpp
#include <cuda_runtime.h>
#include <cuda_bf16.h>
#include <cuda.h>
#include <stdint.h>

namespace {

constexpr int SEQ    = 2048;
constexpr int DM     = 1024;
constexpr int NQ     = 4096;
constexpr int DFF    = 3584;
constexpr int SK     = 2048;
constexpr int WIN    = 512;
constexpr int KV0    = SK - WIN;
constexpr int C_XN = 0, C_O = 1024, C_H = 5120, C_G = 8704, ACT_W = 9728;

constexpr int H_REG = 384, H_SPARE0 = 8 * H_REG;
static_assert(H_SPARE0 + 512 == DFF, "H split");

constexpr int NSLOT = 12, SLOT = 16384, NBAR = 8;
constexpr int SM_STG = NSLOT * SLOT;
constexpr int SM_BAR = SM_STG + 2 * 16384;
constexpr int SMEM_BYTES = SM_BAR + 256 + 1024;
constexpr int B_FULL = 0, B_EMPTY = 64, B_SFULL = 128, B_SEMPTY = 144, B_DONE = 160;

constexpr int NCLUSTER = 66;

struct Flags {
  unsigned ln[16][32];
  unsigned h[16][32];
  unsigned o[16][32];
  unsigned g[16][32];
  unsigned epoch[160];
};
__device__ __nv_bfloat16 g_act[(size_t)SEQ * ACT_W];
__device__ Flags g_flags;

struct Params {
  CUtensorMap act_ld, act_st, x_ld, out_st, k_ld, v_ld, wq, w1b4, w1b3, wo, w2;
  const __nv_bfloat16* x;
  __nv_bfloat16* act;
  Flags* flags;
};

__device__ __forceinline__ uint32_t smem_u32(const void* p) { return (uint32_t)__cvta_generic_to_shared(p); }
__device__ __forceinline__ void mbar_init(uint32_t bar, uint32_t cnt) {
  asm volatile("mbarrier.init.shared::cta.b64 [%0], %1;" ::"r"(bar), "r"(cnt) : "memory");
}
__device__ __forceinline__ bool mbar_try(uint32_t bar, uint32_t parity) {
  uint32_t ok;
  asm volatile("{\n.reg .pred p;\nmbarrier.try_wait.parity.shared::cta.b64 p, [%1], %2;\nselp.u32 %0, 1, 0, p;\n}\n"
               : "=r"(ok) : "r"(bar), "r"(parity) : "memory");
  return ok;
}
__device__ __forceinline__ void mbar_wait(uint32_t bar, uint32_t parity) {
  asm volatile("{\n.reg .pred p;\nWAIT_%=:\nmbarrier.try_wait.parity.shared::cta.b64 p, [%0], %1;\n@p bra DONE_%=;\nbra WAIT_%=;\nDONE_%=:\n}\n"
               ::"r"(bar), "r"(parity) : "memory");
}
__device__ __forceinline__ void mbar_arrive(uint32_t bar) {
  asm volatile("mbarrier.arrive.shared::cta.b64 _, [%0];" ::"r"(bar) : "memory");
}
__device__ __forceinline__ void mbar_arrive_cluster(uint32_t cluster_addr) {
  asm volatile("mbarrier.arrive.shared::cluster.b64 _, [%0];" ::"r"(cluster_addr) : "memory");
}
__device__ __forceinline__ void mbar_expect_tx(uint32_t bar, uint32_t bytes) {
  asm volatile("mbarrier.arrive.expect_tx.shared::cta.b64 _, [%0], %1;" ::"r"(bar), "r"(bytes) : "memory");
}
__device__ __forceinline__ uint32_t mapa(uint32_t addr, uint32_t rank) {
  uint32_t r;
  asm("mapa.shared::cluster.u32 %0, %1, %2;" : "=r"(r) : "r"(addr), "r"(rank));
  return r;
}
__device__ __forceinline__ void cluster_arrive() { asm volatile("barrier.cluster.arrive.relaxed.aligned;" ::: "memory"); }
__device__ __forceinline__ void cluster_wait() { asm volatile("barrier.cluster.wait.acquire.aligned;" ::: "memory"); }
__device__ __forceinline__ void bar_sync(int id, int n) { asm volatile("bar.sync %0, %1;" ::"r"(id), "r"(n) : "memory"); }
__device__ __forceinline__ void bar_arrive(int id, int n) { asm volatile("bar.arrive %0, %1;" ::"r"(id), "r"(n) : "memory"); }
__device__ __forceinline__ void fence_async_smem() { asm volatile("fence.proxy.async.shared::cta;" ::: "memory"); }
__device__ __forceinline__ void fence_async_all() { asm volatile("fence.proxy.async.global;" ::: "memory"); }

__device__ __forceinline__ void tma_ld2(uint32_t dst, const CUtensorMap* m, uint32_t bar, int c0, int c1) {
  asm volatile("cp.async.bulk.tensor.2d.shared::cluster.global.mbarrier::complete_tx::bytes [%0], [%1, {%3, %4}], [%2];"
               ::"r"(dst), "l"(m), "r"(bar), "r"(c0), "r"(c1) : "memory");
}
__device__ __forceinline__ void tma_ld2_mc(uint32_t dst, const CUtensorMap* m, uint32_t bar, int c0, int c1) {
  asm volatile("cp.async.bulk.tensor.2d.shared::cluster.global.mbarrier::complete_tx::bytes.multicast::cluster [%0], [%1, {%3, %4}], [%2], %5;"
               ::"r"(dst), "l"(m), "r"(bar), "r"(c0), "r"(c1), "h"((uint16_t)3) : "memory");
}
__device__ __forceinline__ void tma_ld3_mc(uint32_t dst, const CUtensorMap* m, uint32_t bar, int c0, int c1, int c2) {
  asm volatile("cp.async.bulk.tensor.3d.shared::cluster.global.mbarrier::complete_tx::bytes.multicast::cluster [%0], [%1, {%3, %4, %5}], [%2], %6;"
               ::"r"(dst), "l"(m), "r"(bar), "r"(c0), "r"(c1), "r"(c2), "h"((uint16_t)3) : "memory");
}
__device__ __forceinline__ void tma_ld3_mc_hint(uint32_t dst, const CUtensorMap* m, uint32_t bar, int c0, int c1, int c2, uint64_t pol) {
  asm volatile("cp.async.bulk.tensor.3d.shared::cluster.global.mbarrier::complete_tx::bytes.multicast::cluster.L2::cache_hint [%0], [%1, {%3, %4, %5}], [%2], %6, %7;"
               ::"r"(dst), "l"(m), "r"(bar), "r"(c0), "r"(c1), "r"(c2), "h"((uint16_t)3), "l"(pol) : "memory");
}
__device__ __forceinline__ void tma_ld2_hint(uint32_t dst, const CUtensorMap* m, uint32_t bar, int c0, int c1, uint64_t pol) {
  asm volatile("cp.async.bulk.tensor.2d.shared::cluster.global.mbarrier::complete_tx::bytes.L2::cache_hint [%0], [%1, {%3, %4}], [%2], %5;"
               ::"r"(dst), "l"(m), "r"(bar), "r"(c0), "r"(c1), "l"(pol) : "memory");
}
__device__ __forceinline__ void tma_st2_hint(const CUtensorMap* m, uint32_t src, int c0, int c1, uint64_t pol) {
  asm volatile("cp.async.bulk.tensor.2d.global.shared::cta.bulk_group.L2::cache_hint [%0, {%2, %3}], [%1], %4;"
               ::"l"(m), "r"(src), "r"(c0), "r"(c1), "l"(pol) : "memory");
}
#define POL_FIRST 0x12F0000000000000ull
__device__ __forceinline__ uint64_t policy_evict_first() {
  uint64_t p;
  asm volatile("createpolicy.fractional.L2::evict_first.b64 %0, 1.0;" : "=l"(p));
  return p;
}
__device__ __forceinline__ void tma_st2(const CUtensorMap* m, uint32_t src, int c0, int c1) {
  asm volatile("cp.async.bulk.tensor.2d.global.shared::cta.bulk_group [%0, {%2, %3}], [%1];"
               ::"l"(m), "r"(src), "r"(c0), "r"(c1) : "memory");
}
__device__ __forceinline__ void tma_pf2(const CUtensorMap* m, int c0, int c1) {
  asm volatile("cp.async.bulk.prefetch.tensor.2d.L2.global [%0, {%1, %2}];" ::"l"(m), "r"(c0), "r"(c1) : "memory");
}
__device__ __forceinline__ void bulk_commit() { asm volatile("cp.async.bulk.commit_group;" ::: "memory"); }
__device__ __forceinline__ void bulk_wait_read0() { asm volatile("cp.async.bulk.wait_group.read 0;" ::: "memory"); }
__device__ __forceinline__ void bulk_wait0() { asm volatile("cp.async.bulk.wait_group 0;" ::: "memory"); }
__device__ __forceinline__ void prefetch_map(const CUtensorMap* m) {
  asm volatile("prefetch.tensormap [%0];" ::"l"(m) : "memory");
}
__device__ __forceinline__ unsigned ld_acquire(const unsigned* p) {
  unsigned v;
  asm volatile("ld.acquire.gpu.global.u32 %0, [%1];" : "=r"(v) : "l"(p) : "memory");
  return v;
}
__device__ __forceinline__ void red_release(unsigned* p, unsigned v) {
  asm volatile("red.release.gpu.global.add.u32 [%0], %1;" ::"l"(p), "r"(v) : "memory");
}
__device__ __forceinline__ void wg_fence() { asm volatile("wgmma.fence.sync.aligned;" ::: "memory"); }
__device__ __forceinline__ void wg_commit() { asm volatile("wgmma.commit_group.sync.aligned;" ::: "memory"); }
template <int N> __device__ __forceinline__ void wg_wait() { asm volatile("wgmma.wait_group.sync.aligned %0;" ::"n"(N) : "memory"); }
template <int N> __device__ __forceinline__ void fence_regs(float (&d)[N]) {
#pragma unroll
  for (int i = 0; i < N; i++) asm volatile("" : "+f"(d[i])::"memory");
}
template <int N> __device__ __forceinline__ void fence_regs(uint32_t (&d)[N]) {
#pragma unroll
  for (int i = 0; i < N; i++) asm volatile("" : "+r"(d[i])::"memory");
}
__device__ __forceinline__ uint64_t mkdesc(uint32_t addr, uint32_t lbo, uint32_t sbo) {
  return (uint64_t)((addr & 0x3FFFF) >> 4) | ((uint64_t)(lbo >> 4) << 16) | ((uint64_t)(sbo >> 4) << 32) | (1ull << 62);
}
__device__ __forceinline__ uint32_t pack_bf16(float lo, float hi) {
  uint32_t r;
  asm("cvt.rn.bf16x2.f32 %0, %1, %2;" : "=r"(r) : "f"(hi), "f"(lo));
  return r;
}
__device__ __forceinline__ uint32_t pack_bf16_relu(float lo, float hi) {
  uint32_t r;
  asm("cvt.rn.relu.bf16x2.f32 %0, %1, %2;" : "=r"(r) : "f"(hi), "f"(lo));
  return r;
}
__device__ __forceinline__ float bf_lo(uint32_t v) { return __uint_as_float(v << 16); }
__device__ __forceinline__ float bf_hi(uint32_t v) { return __uint_as_float(v & 0xFFFF0000u); }
__device__ __forceinline__ float bf_round(float v) { return __bfloat162float(__float2bfloat16_rn(v)); }
__device__ __forceinline__ float ex2(float x) {
  float r;
  asm("ex2.approx.ftz.f32 %0, %1;" : "=f"(r) : "f"(x));
  return r;
}
__device__ __forceinline__ float rcp(float x) {
  float r;
  asm("rcp.approx.ftz.f32 %0, %1;" : "=f"(r) : "f"(x));
  return r;
}
__device__ __forceinline__ uint32_t tid_x() {
  uint32_t t;
  asm volatile("mov.u32 %0, %%tid.x;" : "=r"(t));
  return t;
}
__device__ __forceinline__ void stsm4(uint32_t addr, uint32_t r0, uint32_t r1, uint32_t r2, uint32_t r3) {
  asm volatile("stmatrix.sync.aligned.m8n8.x4.shared.b16 [%0], {%1, %2, %3, %4};" ::"r"(addr), "r"(r0), "r"(r1), "r"(r2), "r"(r3) : "memory");
}
__device__ __forceinline__ void ldsm4(uint32_t addr, uint32_t& r0, uint32_t& r1, uint32_t& r2, uint32_t& r3) {
  asm volatile("ldmatrix.sync.aligned.m8n8.x4.shared.b16 {%0, %1, %2, %3}, [%4];" : "=r"(r0), "=r"(r1), "=r"(r2), "=r"(r3) : "r"(addr) : "memory");
}
__device__ __forceinline__ void sts128(uint32_t addr, uint32_t r0, uint32_t r1, uint32_t r2, uint32_t r3) {
  asm volatile("st.shared.v4.b32 [%0], {%1, %2, %3, %4};" ::"r"(addr), "r"(r0), "r"(r1), "r"(r2), "r"(r3) : "memory");
}
__device__ __forceinline__ void lds128(uint32_t addr, uint32_t& r0, uint32_t& r1, uint32_t& r2, uint32_t& r3) {
  asm volatile("ld.shared.v4.b32 {%0, %1, %2, %3}, [%4];" : "=r"(r0), "=r"(r1), "=r"(r2), "=r"(r3) : "r"(addr) : "memory");
}
__device__ __forceinline__ unsigned long long gtime() {
  unsigned long long t;
  asm volatile("mov.u64 %0, %globaltimer;" : "=l"(t));
  return t;
}

__device__ __forceinline__ void wgmma_ss_n256_tb(float (&d)[128], uint64_t da, uint64_t db, uint32_t sc) {
  asm volatile("{\n.reg .pred p;\nsetp.ne.b32 p, %130, 0;\n"
    "wgmma.mma_async.sync.aligned.m64n256k16.f32.bf16.bf16 "
    "{%0, %1, %2, %3, %4, %5, %6, %7, %8, %9, %10, %11, %12, %13, %14, %15, %16, %17, %18, %19, %20, %21, %22, %23, %24, %25, %26, %27, %28, %29, %30, %31, %32, %33, %34, %35, %36, %37, %38, %39, %40, %41, %42, %43, %44, %45, %46, %47, %48, %49, %50, %51, %52, %53, %54, %55, %56, %57, %58, %59, %60, %61, %62, %63, %64, %65, %66, %67, %68, %69, %70, %71, %72, %73, %74, %75, %76, %77, %78, %79, %80, %81, %82, %83, %84, %85, %86, %87, %88, %89, %90, %91, %92, %93, %94, %95, %96, %97, %98, %99, %100, %101, %102, %103, %104, %105, %106, %107, %108, %109, %110, %111, %112, %113, %114, %115, %116, %117, %118, %119, %120, %121, %122, %123, %124, %125, %126, %127}, %128, %129, p, 1, 1, 0, 1;\n}\n"
    : "+f"(d[0]), "+f"(d[1]), "+f"(d[2]), "+f"(d[3]), "+f"(d[4]), "+f"(d[5]), "+f"(d[6]), "+f"(d[7]), "+f"(d[8]), "+f"(d[9]), "+f"(d[10]), "+f"(d[11]), "+f"(d[12]), "+f"(d[13]), "+f"(d[14]), "+f"(d[15]), "+f"(d[16]), "+f"(d[17]), "+f"(d[18]), "+f"(d[19]), "+f"(d[20]), "+f"(d[21]), "+f"(d[22]), "+f"(d[23]), "+f"(d[24]), "+f"(d[25]), "+f"(d[26]), "+f"(d[27]), "+f"(d[28]), "+f"(d[29]), "+f"(d[30]), "+f"(d[31]), "+f"(d[32]), "+f"(d[33]), "+f"(d[34]), "+f"(d[35]), "+f"(d[36]), "+f"(d[37]), "+f"(d[38]), "+f"(d[39]), "+f"(d[40]), "+f"(d[41]), "+f"(d[42]), "+f"(d[43]), "+f"(d[44]), "+f"(d[45]), "+f"(d[46]), "+f"(d[47]), "+f"(d[48]), "+f"(d[49]), "+f"(d[50]), "+f"(d[51]), "+f"(d[52]), "+f"(d[53]), "+f"(d[54]), "+f"(d[55]), "+f"(d[56]), "+f"(d[57]), "+f"(d[58]), "+f"(d[59]), "+f"(d[60]), "+f"(d[61]), "+f"(d[62]), "+f"(d[63]), "+f"(d[64]), "+f"(d[65]), "+f"(d[66]), "+f"(d[67]), "+f"(d[68]), "+f"(d[69]), "+f"(d[70]), "+f"(d[71]), "+f"(d[72]), "+f"(d[73]), "+f"(d[74]), "+f"(d[75]), "+f"(d[76]), "+f"(d[77]), "+f"(d[78]), "+f"(d[79]), "+f"(d[80]), "+f"(d[81]), "+f"(d[82]), "+f"(d[83]), "+f"(d[84]), "+f"(d[85]), "+f"(d[86]), "+f"(d[87]), "+f"(d[88]), "+f"(d[89]), "+f"(d[90]), "+f"(d[91]), "+f"(d[92]), "+f"(d[93]), "+f"(d[94]), "+f"(d[95]), "+f"(d[96]), "+f"(d[97]), "+f"(d[98]), "+f"(d[99]), "+f"(d[100]), "+f"(d[101]), "+f"(d[102]), "+f"(d[103]), "+f"(d[104]), "+f"(d[105]), "+f"(d[106]), "+f"(d[107]), "+f"(d[108]), "+f"(d[109]), "+f"(d[110]), "+f"(d[111]), "+f"(d[112]), "+f"(d[113]), "+f"(d[114]), "+f"(d[115]), "+f"(d[116]), "+f"(d[117]), "+f"(d[118]), "+f"(d[119]), "+f"(d[120]), "+f"(d[121]), "+f"(d[122]), "+f"(d[123]), "+f"(d[124]), "+f"(d[125]), "+f"(d[126]), "+f"(d[127])
    : "l"(da), "l"(db), "r"(sc));
}
__device__ __forceinline__ void wgmma_ss_n192_tb(float (&d)[128], uint64_t da, uint64_t db, uint32_t sc) {
  asm volatile("{\n.reg .pred p;\nsetp.ne.b32 p, %98, 0;\n"
    "wgmma.mma_async.sync.aligned.m64n192k16.f32.bf16.bf16 "
    "{%0, %1, %2, %3, %4, %5, %6, %7, %8, %9, %10, %11, %12, %13, %14, %15, %16, %17, %18, %19, %20, %21, %22, %23, %24, %25, %26, %27, %28, %29, %30, %31, %32, %33, %34, %35, %36, %37, %38, %39, %40, %41, %42, %43, %44, %45, %46, %47, %48, %49, %50, %51, %52, %53, %54, %55, %56, %57, %58, %59, %60, %61, %62, %63, %64, %65, %66, %67, %68, %69, %70, %71, %72, %73, %74, %75, %76, %77, %78, %79, %80, %81, %82, %83, %84, %85, %86, %87, %88, %89, %90, %91, %92, %93, %94, %95}, %96, %97, p, 1, 1, 0, 1;\n}\n"
    : "+f"(d[0]), "+f"(d[1]), "+f"(d[2]), "+f"(d[3]), "+f"(d[4]), "+f"(d[5]), "+f"(d[6]), "+f"(d[7]), "+f"(d[8]), "+f"(d[9]), "+f"(d[10]), "+f"(d[11]), "+f"(d[12]), "+f"(d[13]), "+f"(d[14]), "+f"(d[15]), "+f"(d[16]), "+f"(d[17]), "+f"(d[18]), "+f"(d[19]), "+f"(d[20]), "+f"(d[21]), "+f"(d[22]), "+f"(d[23]), "+f"(d[24]), "+f"(d[25]), "+f"(d[26]), "+f"(d[27]), "+f"(d[28]), "+f"(d[29]), "+f"(d[30]), "+f"(d[31]), "+f"(d[32]), "+f"(d[33]), "+f"(d[34]), "+f"(d[35]), "+f"(d[36]), "+f"(d[37]), "+f"(d[38]), "+f"(d[39]), "+f"(d[40]), "+f"(d[41]), "+f"(d[42]), "+f"(d[43]), "+f"(d[44]), "+f"(d[45]), "+f"(d[46]), "+f"(d[47]), "+f"(d[48]), "+f"(d[49]), "+f"(d[50]), "+f"(d[51]), "+f"(d[52]), "+f"(d[53]), "+f"(d[54]), "+f"(d[55]), "+f"(d[56]), "+f"(d[57]), "+f"(d[58]), "+f"(d[59]), "+f"(d[60]), "+f"(d[61]), "+f"(d[62]), "+f"(d[63]), "+f"(d[64]), "+f"(d[65]), "+f"(d[66]), "+f"(d[67]), "+f"(d[68]), "+f"(d[69]), "+f"(d[70]), "+f"(d[71]), "+f"(d[72]), "+f"(d[73]), "+f"(d[74]), "+f"(d[75]), "+f"(d[76]), "+f"(d[77]), "+f"(d[78]), "+f"(d[79]), "+f"(d[80]), "+f"(d[81]), "+f"(d[82]), "+f"(d[83]), "+f"(d[84]), "+f"(d[85]), "+f"(d[86]), "+f"(d[87]), "+f"(d[88]), "+f"(d[89]), "+f"(d[90]), "+f"(d[91]), "+f"(d[92]), "+f"(d[93]), "+f"(d[94]), "+f"(d[95])
    : "l"(da), "l"(db), "r"(sc));
}
__device__ __forceinline__ void wgmma_rs_n128(float (&d)[64], uint32_t a0, uint32_t a1, uint32_t a2, uint32_t a3, uint64_t db, uint32_t sc) {
  asm volatile("{\n.reg .pred p;\nsetp.ne.b32 p, %69, 0;\n"
    "wgmma.mma_async.sync.aligned.m64n128k16.f32.bf16.bf16 "
    "{%0, %1, %2, %3, %4, %5, %6, %7, %8, %9, %10, %11, %12, %13, %14, %15, %16, %17, %18, %19, %20, %21, %22, %23, %24, %25, %26, %27, %28, %29, %30, %31, %32, %33, %34, %35, %36, %37, %38, %39, %40, %41, %42, %43, %44, %45, %46, %47, %48, %49, %50, %51, %52, %53, %54, %55, %56, %57, %58, %59, %60, %61, %62, %63}, {%64, %65, %66, %67}, %68, p, 1, 1, 0;\n}\n"
    : "+f"(d[0]), "+f"(d[1]), "+f"(d[2]), "+f"(d[3]), "+f"(d[4]), "+f"(d[5]), "+f"(d[6]), "+f"(d[7]), "+f"(d[8]), "+f"(d[9]), "+f"(d[10]), "+f"(d[11]), "+f"(d[12]), "+f"(d[13]), "+f"(d[14]), "+f"(d[15]), "+f"(d[16]), "+f"(d[17]), "+f"(d[18]), "+f"(d[19]), "+f"(d[20]), "+f"(d[21]), "+f"(d[22]), "+f"(d[23]), "+f"(d[24]), "+f"(d[25]), "+f"(d[26]), "+f"(d[27]), "+f"(d[28]), "+f"(d[29]), "+f"(d[30]), "+f"(d[31]), "+f"(d[32]), "+f"(d[33]), "+f"(d[34]), "+f"(d[35]), "+f"(d[36]), "+f"(d[37]), "+f"(d[38]), "+f"(d[39]), "+f"(d[40]), "+f"(d[41]), "+f"(d[42]), "+f"(d[43]), "+f"(d[44]), "+f"(d[45]), "+f"(d[46]), "+f"(d[47]), "+f"(d[48]), "+f"(d[49]), "+f"(d[50]), "+f"(d[51]), "+f"(d[52]), "+f"(d[53]), "+f"(d[54]), "+f"(d[55]), "+f"(d[56]), "+f"(d[57]), "+f"(d[58]), "+f"(d[59]), "+f"(d[60]), "+f"(d[61]), "+f"(d[62]), "+f"(d[63])
    : "r"(a0), "r"(a1), "r"(a2), "r"(a3), "l"(db), "r"(sc));
}
__device__ __forceinline__ void wgmma_rs_n128_tb(float (&d)[64], uint32_t a0, uint32_t a1, uint32_t a2, uint32_t a3, uint64_t db, uint32_t sc) {
  asm volatile("{\n.reg .pred p;\nsetp.ne.b32 p, %69, 0;\n"
    "wgmma.mma_async.sync.aligned.m64n128k16.f32.bf16.bf16 "
    "{%0, %1, %2, %3, %4, %5, %6, %7, %8, %9, %10, %11, %12, %13, %14, %15, %16, %17, %18, %19, %20, %21, %22, %23, %24, %25, %26, %27, %28, %29, %30, %31, %32, %33, %34, %35, %36, %37, %38, %39, %40, %41, %42, %43, %44, %45, %46, %47, %48, %49, %50, %51, %52, %53, %54, %55, %56, %57, %58, %59, %60, %61, %62, %63}, {%64, %65, %66, %67}, %68, p, 1, 1, 1;\n}\n"
    : "+f"(d[0]), "+f"(d[1]), "+f"(d[2]), "+f"(d[3]), "+f"(d[4]), "+f"(d[5]), "+f"(d[6]), "+f"(d[7]), "+f"(d[8]), "+f"(d[9]), "+f"(d[10]), "+f"(d[11]), "+f"(d[12]), "+f"(d[13]), "+f"(d[14]), "+f"(d[15]), "+f"(d[16]), "+f"(d[17]), "+f"(d[18]), "+f"(d[19]), "+f"(d[20]), "+f"(d[21]), "+f"(d[22]), "+f"(d[23]), "+f"(d[24]), "+f"(d[25]), "+f"(d[26]), "+f"(d[27]), "+f"(d[28]), "+f"(d[29]), "+f"(d[30]), "+f"(d[31]), "+f"(d[32]), "+f"(d[33]), "+f"(d[34]), "+f"(d[35]), "+f"(d[36]), "+f"(d[37]), "+f"(d[38]), "+f"(d[39]), "+f"(d[40]), "+f"(d[41]), "+f"(d[42]), "+f"(d[43]), "+f"(d[44]), "+f"(d[45]), "+f"(d[46]), "+f"(d[47]), "+f"(d[48]), "+f"(d[49]), "+f"(d[50]), "+f"(d[51]), "+f"(d[52]), "+f"(d[53]), "+f"(d[54]), "+f"(d[55]), "+f"(d[56]), "+f"(d[57]), "+f"(d[58]), "+f"(d[59]), "+f"(d[60]), "+f"(d[61]), "+f"(d[62]), "+f"(d[63])
    : "r"(a0), "r"(a1), "r"(a2), "r"(a3), "l"(db), "r"(sc));
}

#define TS(i) do {} while (0)
#define TR(j, i) do {} while (0)
#define TSS(i, c) do {} while (0)

__device__ __forceinline__ uint32_t wrap12(uint32_t p) { return p >= NSLOT ? p - NSLOT : p; }

struct Cons {
  uint32_t sb;
  uint32_t g, pos;
  uint32_t rel;
  uint32_t nstg;
  uint32_t zero;
  int wg, lane;
  __device__ __forceinline__ void wait_full(uint32_t gg) const { mbar_wait(sb + SM_BAR + B_FULL + (gg & 7) * 8, (gg >> 3) & 1); }
  __device__ __forceinline__ void release(uint32_t gg) const { if (lane < 2) mbar_arrive_cluster(rel + (gg & 7) * 8); }
  __device__ __forceinline__ void stg_acquire() { mbar_wait(sb + SM_BAR + B_SEMPTY + wg * 8, (nstg & 1) ^ 1); nstg++; }
  __device__ __forceinline__ void stg_publish() const {
    fence_async_smem();
    __syncwarp();
    if (lane == 0) mbar_arrive(sb + SM_BAR + B_SFULL + wg * 8);
  }
};

__device__ __forceinline__ void frag_addr(uint32_t& rowoff, uint32_t& xr) {
  const uint32_t t = tid_x();
  rowoff = ((t >> 5) & 3) * 2048 + (t & 15) * 128;
  xr = (((t >> 4) & 1) ^ (t & 7)) << 4;
}
template <int NB, int NR>
__device__ __forceinline__ void stage_boxes(const uint32_t (&r)[NR], int r0, const Cons& c) {
  uint32_t rowoff, xr;
  frag_addr(rowoff, xr);
  const uint32_t stg = c.sb + SM_STG + c.wg * 16384 + rowoff;
#pragma unroll
  for (int b = 0; b < NB; b++)
#pragma unroll
    for (int kb = 0; kb < 4; kb++)
      stsm4(stg + b * 8192 + ((32 * kb) ^ xr), r[r0 + b * 16 + kb * 4], r[r0 + b * 16 + kb * 4 + 1], r[r0 + b * 16 + kb * 4 + 2], r[r0 + b * 16 + kb * 4 + 3]);
  c.stg_publish();
}

template <int N, bool FIRST>
__device__ __forceinline__ void gemm_step(float (&acc)[128], Cons& c) {
  const uint32_t p1 = wrap12(c.pos + 1), p2 = wrap12(c.pos + 2);
  const uint64_t da = mkdesc(c.sb + c.wg * 8192 + c.pos * SLOT, 16, 1024);
  const uint64_t b0 = mkdesc(c.sb + p1 * SLOT, 4096, 1024);
  const uint64_t b1 = mkdesc(c.sb + p2 * SLOT, 4096, 1024);
  c.wait_full(c.g);
  wg_fence();
  if (N == 256) {
    wgmma_ss_n256_tb(acc, da, b0, FIRST ? 0 : 1);
    wgmma_ss_n256_tb(acc, da + 2, b0 + 128, 1);
    wgmma_ss_n256_tb(acc, da + 4, b1, 1);
    wgmma_ss_n256_tb(acc, da + 6, b1 + 128, 1);
  } else {
    wgmma_ss_n192_tb(acc, da, b0, FIRST ? 0 : 1);
    wgmma_ss_n192_tb(acc, da + 2, b0 + 128, 1);
    wgmma_ss_n192_tb(acc, da + 4, b1, 1);
    wgmma_ss_n192_tb(acc, da + 6, b1 + 128, 1);
  }
  wg_commit();
  if (!FIRST) {
    wg_wait<1>();
    c.release(c.g - 1);
  }
  c.g++;
  c.pos = wrap12(p2 + 1);
}

template <int N>
__device__ __forceinline__ void gemm_loop(float (&acc)[128], Cons& c, int nk) {
  gemm_step<N, true>(acc, c);
#pragma unroll 1
  for (int k = 1; k < nk; k++) gemm_step<N, false>(acc, c);
  wg_wait<0>();
  c.release(c.g - 1);
  fence_regs(acc);
}
template <int N, int NB>
__device__ __forceinline__ void gemm_loop_flush(float (&acc)[128], Cons& c, const uint32_t (&pend)[NB * 16], bool flush) {
  gemm_step<N, true>(acc, c);
#pragma unroll 1
  for (int k = 1; k < 16; k++) {
    gemm_step<N, false>(acc, c);
    if (k == 3 && flush) {
      c.stg_acquire();
      stage_boxes<NB>(pend, 0, c);
    }
  }
  wg_wait<0>();
  c.release(c.g - 1);
  fence_regs(acc);
}
template <int NB>
__device__ __forceinline__ void h_epilogue(const float (&acc)[128], Cons& c, uint32_t (&pend)[NB * 16]) {
  uint32_t r[32];
#pragma unroll
  for (int i = 0; i < 32; i++) r[i] = pack_bf16_relu(acc[2 * i], acc[2 * i + 1]);
  c.stg_acquire();
  stage_boxes<2>(r, 0, c);
#pragma unroll
  for (int i = 0; i < NB * 16; i++) pend[i] = pack_bf16_relu(acc[64 + 2 * i], acc[65 + 2 * i]);
}

__device__ __forceinline__ uint32_t silu2(uint32_t f2) {
  const float a = bf_lo(f2), b = bf_hi(f2);
  const float ta = ex2(-1.4426950408889634f * fabsf(a)), tb = ex2(-1.4426950408889634f * fabsf(b));
  const float da = 1.0f + ta, db = 1.0f + tb;
  const float r = rcp(da * db);
  return pack_bf16((a >= 0.f ? a : a * ta) * (r * db), (b >= 0.f ? b : b * tb) * (r * da));
}

constexpr float SM_C = 0.08838834764831845f * 1.4426950408889634f;

#define ONCE(c) _Pragma("unroll 1") for (uint32_t once_ = 0; once_ <= (c).zero; once_++)
__device__ __forceinline__ void row_max2(const float (&S)[64], float& n0, float& n1) {
  float x[4], y[4];
#pragma unroll
  for (int i = 0; i < 4; i++) { x[i] = fmaxf(S[4 * i], S[4 * i + 1]); y[i] = fmaxf(S[4 * i + 2], S[4 * i + 3]); }
#pragma unroll
  for (int i = 4; i < 16; i++) {
    x[i & 3] = fmaxf(x[i & 3], fmaxf(S[4 * i], S[4 * i + 1]));
    y[i & 3] = fmaxf(y[i & 3], fmaxf(S[4 * i + 2], S[4 * i + 3]));
  }
  n0 = fmaxf(fmaxf(x[0], x[1]), fmaxf(x[2], x[3]));
  n1 = fmaxf(fmaxf(y[0], y[1]), fmaxf(y[2], y[3]));
  n0 = fmaxf(n0, __shfl_xor_sync(~0u, n0, 1));
  n1 = fmaxf(n1, __shfl_xor_sync(~0u, n1, 1));
  n0 = fmaxf(n0, __shfl_xor_sync(~0u, n0, 2));
  n1 = fmaxf(n1, __shfl_xor_sync(~0u, n1, 2));
}
__device__ __forceinline__ void to_exponent(float (&S)[64], float cc0, float cc1) {
#pragma unroll
  for (int i = 0; i < 16; i++) {
    S[4 * i] = fmaf(S[4 * i], SM_C, cc0); S[4 * i + 1] = fmaf(S[4 * i + 1], SM_C, cc0);
    S[4 * i + 2] = fmaf(S[4 * i + 2], SM_C, cc1); S[4 * i + 3] = fmaf(S[4 * i + 3], SM_C, cc1);
  }
}
__device__ __forceinline__ void scale_o(float (&O)[64], float f0, float f1) {
#pragma unroll
  for (int i = 0; i < 16; i++) { O[4 * i] *= f0; O[4 * i + 1] *= f0; O[4 * i + 2] *= f1; O[4 * i + 3] *= f1; }
}
template <int G0>
__device__ __forceinline__ void exp_pack(const float (&S)[64], uint32_t (&p)[32], float (&a)[4]) {
#pragma unroll
  for (int i = G0; i < 16; i++) {
    const float e0 = ex2(S[4 * i]), e1 = ex2(S[4 * i + 1]), e2 = ex2(S[4 * i + 2]), e3 = ex2(S[4 * i + 3]);
    a[0] += e0; a[1] += e1; a[2] += e2; a[3] += e3;
    p[2 * i] = pack_bf16(e0, e1);
    p[2 * i + 1] = pack_bf16(e2, e3);
  }
}
#define EARLY 4
__device__ __forceinline__ void softmax_early(float (&S)[64], float cc0, float cc1, float (&a)[4], uint32_t (&pe)[2 * EARLY + 1], const Cons& c) {
  a[0] = a[1] = a[2] = a[3] = 0.f;
  ONCE(c) {
    to_exponent(S, cc0, cc1);
#pragma unroll
    for (int i = 0; i < EARLY; i++) {
      const float e0 = ex2(S[4 * i]), e1 = ex2(S[4 * i + 1]), e2 = ex2(S[4 * i + 2]), e3 = ex2(S[4 * i + 3]);
      a[0] += e0; a[1] += e1; a[2] += e2; a[3] += e3;
      pe[2 * i] = pack_bf16(e0, e1);
      pe[2 * i + 1] = pack_bf16(e2, e3);
    }
  }
}
__device__ __forceinline__ void softmax_late(float (&S)[64], uint32_t (&p)[32], float (&O)[64], float& cc0, float& cc1, float& l0, float& l1,
                                             float (&a)[4], const uint32_t (&pe)[2 * EARLY + 1], uint32_t zero) {
#pragma unroll
  for (int i = 0; i < 2 * EARLY; i++) p[i] = pe[i] ^ zero;
  exp_pack<EARLY>(S, p, a);
  if (__any_sync(~0u, !(fmaxf(a[0] + a[1], a[2] + a[3]) <= 65536.f))) {
    float d0, d1;
    row_max2(S, d0, d1);
    d0 = fmaxf(d0, 0.f); d1 = fmaxf(d1, 0.f);
#pragma unroll
    for (int i = 0; i < 16; i++) { S[4 * i] -= d0; S[4 * i + 1] -= d0; S[4 * i + 2] -= d1; S[4 * i + 3] -= d1; }
    cc0 -= d0; cc1 -= d1;
    const float f0 = ex2(-d0), f1 = ex2(-d1);
    scale_o(O, f0, f1);
    l0 *= f0; l1 *= f1;
    a[0] = a[1] = a[2] = a[3] = 0.f;
    exp_pack<0>(S, p, a);
  }
  l0 += a[0] + a[1];
  l1 += a[2] + a[3];
}

__device__ __forceinline__ void inv_rowsum(float l0, float l1, float& i0, float& i1) {
  l0 += __shfl_xor_sync(~0u, l0, 1); l1 += __shfl_xor_sync(~0u, l1, 1);
  l0 += __shfl_xor_sync(~0u, l0, 2); l1 += __shfl_xor_sync(~0u, l1, 2);
  i0 = rcp(l0); i1 = rcp(l1);
}
__device__ __forceinline__ void write_o(const float (&O)[64], const Cons& c) {
  uint32_t rowoff, xr;
  frag_addr(rowoff, xr);
  const uint32_t stg = c.sb + SM_STG + c.wg * 16384 + rowoff;
#pragma unroll
  for (int kb = 0; kb < 8; kb++)
    stsm4(stg + (kb >> 2) * 8192 + ((32 * (kb & 3)) ^ xr),
          pack_bf16(O[8 * kb], O[8 * kb + 1]), pack_bf16(O[8 * kb + 2], O[8 * kb + 3]),
          pack_bf16(O[8 * kb + 4], O[8 * kb + 5]), pack_bf16(O[8 * kb + 6], O[8 * kb + 7]));
  c.stg_publish();
}

__device__ __forceinline__ void issue_qk(float (&S)[64], const uint32_t (&q)[32], uint32_t s0, uint32_t s1, uint32_t zero) {
  const uint64_t d0 = mkdesc(s0, 16, 1024), d1 = mkdesc(s1, 16, 1024);
#pragma unroll
  for (int kk = 0; kk < 8; kk++)
    wgmma_rs_n128(S, q[4 * kk], q[4 * kk + 1], q[4 * kk + 2], q[4 * kk + 3], (kk < 4 ? d0 : d1) + (kk & 3) * 2, kk > 0 ? 1u : zero);
}
__device__ __forceinline__ void issue_pv(float (&O)[64], const uint32_t (&p)[32], uint32_t s0, uint32_t s1, uint32_t accum) {
  const uint64_t d0 = mkdesc(s0, 8192, 1024), d1 = mkdesc(s1, 8192, 1024);
#pragma unroll
  for (int kk = 0; kk < 8; kk++)
    wgmma_rs_n128_tb(O, p[4 * kk], p[4 * kk + 1], p[4 * kk + 2], p[4 * kk + 3], (kk < 4 ? d0 : d1) + (kk & 3) * 128, kk > 0 ? 1u : accum);
}

#define TURN_SYNC()   bar_sync(1 + c.wg, 256)
#define TURN_PASS()   bar_arrive(2 - c.wg, 256)

__device__ __forceinline__ void attn_tile(const float (&acc)[128], Cons& c, int t) {
  uint32_t q[32], p[32];
  float S[64], O[64];
  const uint32_t stash = c.sb + SM_STG + c.wg * 16384 + ((threadIdx.x >> 5) & 3) * 2048 + c.lane * 16;
#pragma unroll
  for (int i = 0; i < 32; i++) q[i] = pack_bf16(acc[2 * i], acc[2 * i + 1]);
  c.stg_acquire();
#pragma unroll
  for (int i = 0; i < 8; i++)
    sts128(stash + (i >> 2) * 8192 + (i & 3) * 512, pack_bf16(acc[64 + 8 * i], acc[65 + 8 * i]), pack_bf16(acc[66 + 8 * i], acc[67 + 8 * i]),
           pack_bf16(acc[68 + 8 * i], acc[69 + 8 * i]), pack_bf16(acc[70 + 8 * i], acc[71 + 8 * i]));
  fence_regs(q);
  TR(0, 0);
  TURN_SYNC();
  TR(0, 1);
  c.wait_full(c.g);
  wg_fence();
  issue_qk(O, q, c.sb + c.pos * SLOT, c.sb + wrap12(c.pos + 1) * SLOT, 0);
  wg_commit();
  c.wait_full(c.g + 1);
  wg_fence();
  issue_qk(S, q, c.sb + wrap12(c.pos + 2) * SLOT, c.sb + wrap12(c.pos + 3) * SLOT, 0);
  wg_commit();
  TURN_PASS();
  TR(0, 2);
  wg_wait<1>();
  TR(0, 3);
  fence_regs(O);
  c.release(c.g);
  float cc0, cc1, l0, l1, f0 = 0.f, f1 = 0.f;
  float a[4] = {0.f, 0.f, 0.f, 0.f};
  uint32_t pe[2 * EARLY + 1];
  row_max2(O, cc0, cc1);
  cc0 *= -SM_C; cc1 *= -SM_C;
  ONCE(c) { to_exponent(O, cc0, cc1); }
  wg_wait<0>();
  fence_regs(S);
  fence_regs(q);
  c.release(c.g + 1);
  exp_pack<0>(O, p, a);
  l0 = a[0] + a[1];
  l1 = a[2] + a[3];
  c.pos = wrap12(c.pos + 4);
  TR(1, 0);
  TURN_SYNC();
  TR(1, 1);
  c.wait_full(c.g + 2);
  wg_fence();
  issue_pv(O, p, c.sb + c.pos * SLOT, c.sb + wrap12(c.pos + 1) * SLOT, 0);
  wg_commit();
  TURN_PASS();
  TR(1, 2);
  softmax_early(S, cc0, cc1, a, pe, c);
  TR(1, 4);
  wg_wait<0>();
  TR(1, 5);
  fence_regs(O);
  fence_regs(p);
  c.release(c.g + 2);
  c.g += 3;
  c.pos = wrap12(c.pos + 2);
  softmax_late(S, p, O, cc0, cc1, l0, l1, a, pe, c.zero);
#pragma unroll 1
  for (int j = 1; j < 7 + (int)c.zero; j++) {
    const uint32_t k0 = c.pos, k1 = wrap12(k0 + 1), v0 = wrap12(k0 + 2), v1 = wrap12(k0 + 3);
    TR(j + 1, 0);
    TURN_SYNC();
    TR(j + 1, 1);
    c.wait_full(c.g);
    wg_fence();
    issue_qk(S, q, c.sb + k0 * SLOT, c.sb + k1 * SLOT, 0);
    wg_commit();
    if (j == 4) {
      scale_o(O, f0, f1);
      write_o(O, c);
    }
    c.wait_full(c.g + 1);
    wg_fence();
    issue_pv(O, p, c.sb + v0 * SLOT, c.sb + v1 * SLOT, j != 4);
    wg_commit();
    TURN_PASS();
    TR(j + 1, 2);
    wg_wait<1>();
    TR(j + 1, 3);
    fence_regs(S);
    fence_regs(q);
    c.release(c.g);
    if (j == 3) {
      row_max2(S, cc0, cc1);
      cc0 *= -SM_C; cc1 *= -SM_C;
      inv_rowsum(l0, l1, f0, f1);
      l0 = 0.f; l1 = 0.f;
    }
    softmax_early(S, cc0, cc1, a, pe, c);
    if (j == 2) {
#pragma unroll
      for (int i = 0; i < 8; i++) lds128(stash + (i >> 2) * 8192 + (i & 3) * 512, q[4 * i], q[4 * i + 1], q[4 * i + 2], q[4 * i + 3]);
      __syncwarp();
    }
    TR(j + 1, 4);
    wg_wait<0>();
    TR(j + 1, 5);
    fence_regs(O);
    fence_regs(p);
    c.release(c.g + 1);
    c.g += 2;
    c.pos = wrap12(v1 + 1);
    softmax_late(S, p, O, cc0, cc1, l0, l1, a, pe, c.zero);
  }
  TR(8, 0);
  TURN_SYNC();
  TR(8, 1);
  c.wait_full(c.g);
  wg_fence();
  issue_pv(O, p, c.sb + c.pos * SLOT, c.sb + wrap12(c.pos + 1) * SLOT, 1);
  wg_commit();
  TURN_PASS();
  TR(8, 2);
  c.stg_acquire();
  float a0, a1;
  inv_rowsum(l0, l1, a0, a1);
  wg_wait<0>();
  TR(8, 5);
  fence_regs(O);
  fence_regs(p);
  c.release(c.g);
  c.g++;
  c.pos = wrap12(c.pos + 2);
  scale_o(O, a0, a1);
  write_o(O, c);
  TR(9, 0);
}

struct Prod {
  uint32_t sb, g, pos, head, tail_g, tail_pos, hist;
  __device__ __forceinline__ uint32_t full() const { return sb + SM_BAR + B_FULL + (g & 7) * 8; }
  __device__ __forceinline__ uint32_t slot(uint32_t i) const { return sb + wrap12(pos + i) * SLOT; }
  __device__ __forceinline__ void acquire(uint32_t size) {
#pragma unroll 1
    while (head + size - tail_pos > NSLOT) {
      mbar_wait(sb + SM_BAR + B_EMPTY + (tail_g & 7) * 8, (tail_g >> 3) & 1);
      tail_pos += 2 + ((hist >> (tail_g & 31)) & 1);
      tail_g++;
    }
    hist = (hist & ~(1u << (g & 31))) | ((size - 2) << (g & 31));
  }
  __device__ __forceinline__ void advance(uint32_t size) { g++; head += size; pos = wrap12(pos + size); }
};

__device__ __forceinline__ void wait_flag(const unsigned* p, unsigned target) {
  while ((int)(ld_acquire(p) - target) < 0) {}
  fence_async_all();
}

__device__ __forceinline__ void init_barriers(uint32_t sb, int warp) {
  const uint32_t cnt = warp < 4 ? 1 : warp < 8 ? 16 : warp == 8 ? 4 : warp == 9 ? 1 : 11;
  if (warp < 11) mbar_init(sb + SM_BAR + warp * 16, cnt);
  if (warp < 10) mbar_init(sb + SM_BAR + warp * 16 + 8, cnt);
  asm volatile("fence.mbarrier_init.release.cluster;" ::: "memory");
}

#define TSP(i) do {} while (0)

__global__ void __cluster_dims__(2, 1, 1) __launch_bounds__(384, 1) fused_kernel(const __grid_constant__ Params P) {
  extern __shared__ uint8_t smem_raw[];
  const uint32_t sb = (smem_u32(smem_raw) + 1023u) & ~1023u;
  const int warp = __shfl_sync(~0u, (int)(threadIdx.x >> 5), 0);
  const int lane = threadIdx.x & 31;
  const int rank = blockIdx.x & 1;
  const int cl = blockIdx.x >> 1;
  const int j = cl >> 3;
  const int rb = (cl & 7) * 2 + rank;
  const bool is_s = j < 4, spare = j == 8;
  const int row0 = rb * 128;
  Flags* fl = P.flags;

  if (warp >= 8) {
    unsigned ep0 = 0;
    if (warp == 8) asm volatile("ld.volatile.global.u32 %0, [%1];" : "=r"(ep0) : "l"(&fl->epoch[blockIdx.x]));
    if (lane == 0) {
      if (warp == 8) prefetch_map(spare ? &P.w1b4 : &P.w1b3);
      if (warp == 9) prefetch_map(&P.act_ld);
      init_barriers(sb, warp);
    }
    __syncwarp();
    cluster_arrive();
    if (warp == 10 && lane == 0) {
      prefetch_map(&P.act_st); prefetch_map(&P.wq); prefetch_map(&P.k_ld); prefetch_map(&P.v_ld);
      prefetch_map(is_s ? &P.wo : &P.w2); prefetch_map(&P.x_ld); prefetch_map(&P.out_st);
    }
    __syncwarp();
    cluster_wait();
    asm volatile("setmaxnreg.dec.sync.aligned.u32 24;");
    if (warp == 8) {
      TSP(17);
#define ep1 (ep0 + 1)
      Prod p{sb, 0, 0, 0, 0, 0, 0};
#define LDA(dst, m, bar, c0, c1) tma_ld2(dst, m, bar, c0, c1)
#define LDW1(dst, m, bar, c0, c1, c2) tma_ld3_mc(dst, m, bar, c0, c1, c2)
#define LDW(dst, m, bar, c0, c1, c2) tma_ld3_mc(dst, m, bar, c0, c1, c2)
      {
        const CUtensorMap* mb = spare ? &P.w1b4 : &P.w1b3;
        const uint32_t bytes = spare ? 49152 : 40960;
        const int nt = spare ? 8 : 2;
#pragma unroll 1
        for (int t = 0; t < nt; t++) {
          const int r = spare ? ((cl & 1) * 4 + (t >> 1)) * 2 + rank : rb;
          const int nb0 = spare ? (H_SPARE0 >> 6) + (t & 1) * 4 : j * 6 + t * 3;
          int k = 0;
          if (t == 0) {
#pragma unroll 1
            for (; k < 4; k++) {
              p.acquire(3);
              if (lane == 0) { mbar_expect_tx(p.full(), bytes); LDW1(p.slot(1 + rank), mb, p.full(), 0, k * 64 + rank * 32, nb0); }
              p.advance(3);
            }
            TSP(14);
            asm volatile("" : "+r"(ep0));
            wait_flag(&fl->ln[r][0], ep1 * 64);
            TSP(15);
            if (lane == 0)
              for (int i = 0; i < 4; i++) tma_ld2(sb + i * 3 * SLOT, &P.act_ld, sb + SM_BAR + B_FULL + i * 8, C_XN + i * 64, r * 128);
          } else if (spare && !(t & 1)) {
            wait_flag(&fl->ln[r][0], ep1 * 64);
          }
#pragma unroll 1
          for (; k < 16; k++) {
            p.acquire(3);
            if (lane == 0) {
              mbar_expect_tx(p.full(), bytes);
              LDW1(p.slot(1 + rank), mb, p.full(), 0, k * 64 + rank * 32, nb0);
              tma_ld2(p.slot(0), &P.act_ld, p.full(), C_XN + k * 64, r * 128);
            }
            p.advance(3);
          }
        }
      }
      if (!spare) {
        const int kvrow = (j >> 1) * SK + KV0;
#pragma unroll 1
        for (int t = 0; t < 2; t++) {
          const int nb0 = (4 * j + 2 * t) * 2;
#pragma unroll 1
          for (int k = 0; k < 16; k++) {
            p.acquire(3);
            if (lane == 0) {
              mbar_expect_tx(p.full(), 49152);
              LDW1(p.slot(1 + rank), &P.wq, p.full(), 0, k * 64 + rank * 32, nb0);
              tma_ld2(p.slot(0), &P.act_ld, p.full(), C_XN + k * 64, row0);
            }
            p.advance(3);
          }
#pragma unroll 1
          for (int i = 0; i < 16; i++) {
            const bool is_k = i == 0 || (i < 15 && (i & 1));
            const int ch = (is_k ? ((i + 1) >> 1) : (i == 15 ? 7 : (i >> 1) - 1)) & 3;
            p.acquire(2);
            if (lane == 0) {
              mbar_expect_tx(p.full(), 32768);
              if (is_k) tma_ld2_mc(p.slot(rank), &P.k_ld, p.full(), rank * 64, kvrow + ch * 128);
              else      tma_ld3_mc(p.slot(rank), &P.v_ld, p.full(), 0, kvrow + ch * 128 + rank * 64, 0);
            }
            p.advance(2);
            if (t == 1 && i == 4) {
              if (!is_s) wait_flag(&fl->h[rb][0], ep1 * 64);
              else if (lane < 4) tma_pf2(&P.x_ld, (j & 3) * 256 + lane * 64, row0);
            }
          }
        }
        const int jn = j & 3;
        if (is_s) {
#pragma unroll 1
          for (int i = 0; i < 2; i++) {
            p.acquire(2);
            if (lane == 0) {
              mbar_expect_tx(p.full(), 32768);
              tma_ld2(p.slot(0), &P.x_ld, p.full(), jn * 256 + i * 128, row0);
              tma_ld2(p.slot(1), &P.x_ld, p.full(), jn * 256 + i * 128 + 64, row0);
            }
            p.advance(2);
          }
          unsigned ready = 0;
#pragma unroll 1
          for (int i = 0; i < 64; i++) {
            const int hi = i >> 1;
            const int head = 4 * ((hi & 15) >> 1) + (hi & 1) + ((hi >> 4) << 1);
            const int kc = head * 128 + (i & 1) * 64;
            p.acquire(3);
            if (lane == 0) { mbar_expect_tx(p.full(), 49152); LDW(p.slot(1 + rank), &P.wo, p.full(), 0, kc + rank * 32, jn * 4); }
            if (!((ready >> head) & 1)) {
              do { ready = __ballot_sync(~0u, (int)(ld_acquire(&fl->o[rb][lane]) - ep1 * 2) >= 0); } while (!((ready >> head) & 1));
              __syncwarp();
              fence_async_all();
            }
            if (lane == 0) LDA(p.slot(0), &P.act_ld, p.full(), C_O + kc, row0);
            if (i == 56 && lane == 0) prefetch_map(&P.out_st);
            p.advance(3);
          }
          TSP(20);
          wait_flag(&fl->g[rb][jn], ep1 * 4);
          TSP(21);
#pragma unroll 1
          for (int i = 0; i < 2; i++) {
            p.acquire(2);
            if (lane == 0) {
              mbar_expect_tx(p.full(), 32768);
              tma_ld2(p.slot(0), &P.act_ld, p.full(), C_G + jn * 256 + i * 128, row0);
              tma_ld2(p.slot(1), &P.act_ld, p.full(), C_G + jn * 256 + i * 128 + 64, row0);
            }
            p.advance(2);
          }
        } else {
#pragma unroll 1
          for (int k = 0; k < 56; k++) {
            p.acquire(3);
            if (lane == 0) { mbar_expect_tx(p.full(), 49152); LDW(p.slot(1 + rank), &P.w2, p.full(), 0, k * 64 + rank * 32, jn * 4); }
            if (k == H_SPARE0 / 64) wait_flag(&fl->h[rb][16], ep1 * 8);
            if (lane == 0) LDA(p.slot(0), &P.act_ld, p.full(), C_H + k * 64, row0);
            p.advance(3);
          }
        }
      }
      if (lane == 0) { *(volatile unsigned*)&fl->epoch[blockIdx.x] = ep1; mbar_arrive(sb + SM_BAR + B_DONE); }
    } else if (warp < 11) {
      const int wg = warp - 9;
      if (lane == 0) {
        const uint32_t stg = sb + SM_STG + wg * 16384;
        const int nev = spare ? 16 : is_s ? 8 : 10;
#pragma unroll 1
        for (int n = 0; n < nev; n++) {
          int col, row = row0, nbox = 2;
          unsigned* flag;
          if (spare) {
            const int r = ((cl & 1) * 4 + (n >> 2)) * 2 + rank;
            row = r * 128;
            col = C_H + H_SPARE0 + (n & 3) * 128;
            flag = &fl->h[r][16];
          } else if (n < 4) {
            col = C_H + j * H_REG + (n >> 1) * 192 + (n & 1) * 128;
            nbox = 2 - (n & 1);
            flag = &fl->h[rb][0];
          } else if (n < 8) {
            col = C_O + (4 * j + n - 4) * 128;
            flag = &fl->o[rb][4 * j + n - 4];
          } else {
            col = C_G + (j & 3) * 256 + (n - 8) * 128;
            flag = &fl->g[rb][j & 3];
          }
          mbar_wait(sb + SM_BAR + B_SFULL + wg * 8, n & 1);
          if (n == 9 && wg == 0) TSP(20);
          tma_st2(&P.act_st, stg, col, row + wg * 64);
          if (nbox == 2) tma_st2(&P.act_st, stg + 8192, col + 64, row + wg * 64);
          bulk_commit();
          bulk_wait_read0();
          mbar_arrive(sb + SM_BAR + B_SEMPTY + wg * 8);
          if (n == 9 && wg == 0) TSP(21);
          bulk_wait0();
          if (n == 9 && wg == 0) TSP(22);
          fence_async_all();
          red_release(flag, 1);
          if (n == 9 && wg == 0) TSP(23);
        }
        mbar_arrive(sb + SM_BAR + B_DONE);
      }
    } else {
      if (lane == 0) {
        const unsigned long long t0 = gtime();
        while (!mbar_try(sb + SM_BAR + B_DONE, 0)) {
          if (gtime() - t0 > 2000000000ull) __trap();
        }
      }
    }
    __syncwarp();
    cluster_arrive();
    cluster_wait();
  } else {
    const int wg = warp >> 2;
    TS(0);
    if (!spare) {
      const int r = row0 + j * 16 + warp * 2;
      uint32_t v[2][16];
#pragma unroll
      for (int a = 0; a < 2; a++)
#pragma unroll
        for (int i = 0; i < 4; i++)
          *(uint4*)&v[a][4 * i] = __ldg((const uint4*)(P.x + (size_t)(r + a) * DM + i * 256 + lane * 8));
      if (lane == 0) init_barriers(sb, warp);
      __syncwarp();
      cluster_arrive();
      float s[2], q[2];
#pragma unroll
      for (int a = 0; a < 2; a++) {
        float t0 = 0.f, t1 = 0.f;
#pragma unroll
        for (int i = 0; i < 16; i++) { t0 += bf_lo(v[a][i]); t1 += bf_hi(v[a][i]); }
        s[a] = t0 + t1;
      }
#pragma unroll
      for (int o = 16; o; o >>= 1) { s[0] += __shfl_xor_sync(~0u, s[0], o); s[1] += __shfl_xor_sync(~0u, s[1], o); }
#pragma unroll
      for (int a = 0; a < 2; a++) {
        s[a] *= 1.0f / DM;
        float t0 = 0.f, t1 = 0.f;
#pragma unroll
        for (int i = 0; i < 16; i++) {
          const float d0 = bf_lo(v[a][i]) - s[a], d1 = bf_hi(v[a][i]) - s[a];
          t0 = fmaf(d0, d0, t0); t1 = fmaf(d1, d1, t1);
        }
        q[a] = t0 + t1;
      }
#pragma unroll
      for (int o = 16; o; o >>= 1) { q[0] += __shfl_xor_sync(~0u, q[0], o); q[1] += __shfl_xor_sync(~0u, q[1], o); }
#pragma unroll
      for (int a = 0; a < 2; a++) {
        const uint32_t mb2 = pack_bf16(s[a], s[a]);
        const float inv = 1.0f / bf_round(sqrtf(bf_round(bf_round(q[a] * (1.0f / DM)) + 1e-5f)));
#pragma unroll
        for (int i = 0; i < 16; i++) {
          const __nv_bfloat162 d = __hsub2_rn(*(const __nv_bfloat162*)&v[a][i], *(const __nv_bfloat162*)&mb2);
          const uint32_t du = *(const uint32_t*)&d;
          v[a][i] = pack_bf16(bf_lo(du) * inv, bf_hi(du) * inv);
        }
#pragma unroll
        for (int i = 0; i < 4; i++)
          *(uint4*)(P.act + (size_t)(r + a) * ACT_W + C_XN + i * 256 + lane * 8) = *(const uint4*)&v[a][4 * i];
      }
      TS(11);
      fence_async_all();
      TS(12);
      __syncwarp();
      if (lane == 0) red_release(&fl->ln[rb][0], 1);
      TS(13);
    } else {
      if (lane == 0) init_barriers(sb, warp);
      __syncwarp();
      cluster_arrive();
    }
    cluster_wait();
    asm volatile("setmaxnreg.inc.sync.aligned.u32 240;");
    Cons c;
    c.zero = blockIdx.y; c.sb = sb; c.g = 0; c.pos = 0; c.nstg = 0; c.wg = wg; c.lane = lane;
    c.rel = mapa(sb + SM_BAR + B_EMPTY, lane & 1);
    float acc[128];
    TS(1);
    if (spare) {
      uint32_t pend[32];
#pragma unroll
      for (int i = 0; i < 32; i++) pend[i] = 0;
#pragma unroll 1
      for (int t = 0; t < 8; t++) {
        gemm_loop_flush<256, 2>(acc, c, pend, t > 0);
        h_epilogue<2>(acc, c, pend);
      }
      c.stg_acquire();
      stage_boxes<2>(pend, 0, c);
      TS(6);
    } else {
      if (wg == 1) bar_arrive(1, 256);
      {
        uint32_t pend[16];
#pragma unroll
        for (int i = 0; i < 16; i++) pend[i] = 0;
#pragma unroll 1
        for (int t = 0; t < 2; t++) {
          gemm_loop_flush<192, 1>(acc, c, pend, t > 0);
          h_epilogue<1>(acc, c, pend);
          TS(2 + t);
        }
        gemm_loop_flush<256, 1>(acc, c, pend, true);
      }
#pragma unroll 1
      for (int t = 0;; t++) {
        TS(8 + t);
        attn_tile(acc, c, t);
        TS(4 + t);
        if (t == 1) break;
        gemm_loop<256>(acc, c, 16);
      }
      uint32_t rowoff, xr;
      if (is_s) {
        uint32_t xv[64];
        frag_addr(rowoff, xr);
#pragma unroll
        for (int b = 0; b < 4; b++) {
          if ((b & 1) == 0) c.wait_full(c.g + (b >> 1));
          const uint32_t sx = sb + wrap12(c.pos + b) * SLOT + wg * 8192 + rowoff;
#pragma unroll
          for (int kb = 0; kb < 4; kb++)
            ldsm4(sx + ((32 * kb) ^ xr), xv[16 * b + 4 * kb], xv[16 * b + 4 * kb + 1], xv[16 * b + 4 * kb + 2], xv[16 * b + 4 * kb + 3]);
        }
        fence_regs(xv);
        __syncwarp();
        c.release(c.g);
        c.release(c.g + 1);
        c.g += 2;
        c.pos = wrap12(c.pos + 4);
        gemm_loop<256>(acc, c, 64);
        TS(6);
        frag_addr(rowoff, xr);
#pragma unroll
        for (int b = 0; b < 4; b++) {
          if ((b & 1) == 0) c.wait_full(c.g + (b >> 1));
          if (b == 0) TS(22);
          if (b == 2) TS(23);
          const uint32_t gs = sb + wrap12(c.pos + b) * SLOT + wg * 8192;
          uint32_t gv[16];
#pragma unroll
          for (int kb = 0; kb < 4; kb++) ldsm4(gs + rowoff + ((32 * kb) ^ xr), gv[4 * kb], gv[4 * kb + 1], gv[4 * kb + 2], gv[4 * kb + 3]);
#pragma unroll
          for (int i = 0; i < 16; i++) {
            const uint32_t s2 = pack_bf16(acc[32 * b + 2 * i], acc[32 * b + 2 * i + 1]);
            const __nv_bfloat162 pr = __hmul2_rn(*(const __nv_bfloat162*)&s2, *(const __nv_bfloat162*)&gv[i]);
            const __nv_bfloat162 o = __hadd2_rn(*(const __nv_bfloat162*)&xv[16 * b + i], pr);
            gv[i] = *(const uint32_t*)&o;
          }
#pragma unroll
          for (int kb = 0; kb < 4; kb++) stsm4(gs + rowoff + ((32 * kb) ^ xr), gv[4 * kb], gv[4 * kb + 1], gv[4 * kb + 2], gv[4 * kb + 3]);
          if (b & 1) {
            fence_async_smem();
            bar_sync(3 + wg, 128);
            if ((threadIdx.x & 127) == 0) {
              tma_st2(&P.out_st, sb + wrap12(c.pos + b - 1) * SLOT + wg * 8192, (j & 3) * 256 + b * 64 - 64, row0 + wg * 64);
              tma_st2(&P.out_st, gs, (j & 3) * 256 + b * 64, row0 + wg * 64);
              bulk_commit();
            }
          }
        }
        TS(24);
        if ((threadIdx.x & 127) == 0) bulk_wait_read0();
      } else {
        gemm_loop<256>(acc, c, 56);
        TS(6);
        frag_addr(rowoff, xr);
        const uint32_t stg = sb + SM_STG + wg * 16384 + rowoff;
#pragma unroll
        for (int hh = 0; hh < 2; hh++) {
          c.stg_acquire();
#pragma unroll
          for (int kb = 0; kb < 8; kb++)
            stsm4(stg + (kb >> 2) * 8192 + ((32 * (kb & 3)) ^ xr),
                  silu2(pack_bf16(acc[64 * hh + 8 * kb], acc[64 * hh + 8 * kb + 1])), silu2(pack_bf16(acc[64 * hh + 8 * kb + 2], acc[64 * hh + 8 * kb + 3])),
                  silu2(pack_bf16(acc[64 * hh + 8 * kb + 4], acc[64 * hh + 8 * kb + 5])), silu2(pack_bf16(acc[64 * hh + 8 * kb + 6], acc[64 * hh + 8 * kb + 7])));
          c.stg_publish();
          if (hh == 0) TS(22);
        }
      }
    }
    TS(7);
    __syncwarp();
    if (lane == 0) mbar_arrive(sb + SM_BAR + B_DONE);
    cluster_arrive();
    cluster_wait();
  }
}

typedef CUresult (*EncodeFn)(CUtensorMap*, CUtensorMapDataType, cuuint32_t, void*, const cuuint64_t*, const cuuint64_t*,
                             const cuuint32_t*, const cuuint32_t*, CUtensorMapInterleave, CUtensorMapSwizzle,
                             CUtensorMapL2promotion, CUtensorMapFloatOOBfill);

void map2d(EncodeFn enc, CUtensorMap* m, const void* base, uint64_t cols, uint64_t rows, uint32_t box_rows) {
  cuuint64_t dims[2] = {cols, rows};
  cuuint64_t strides[1] = {cols * 2};
  cuuint32_t box[2] = {64, box_rows};
  cuuint32_t es[2] = {1, 1};
  enc(m, CU_TENSOR_MAP_DATA_TYPE_BFLOAT16, 2, (void*)base, dims, strides, box, es, CU_TENSOR_MAP_INTERLEAVE_NONE,
      CU_TENSOR_MAP_SWIZZLE_128B, CU_TENSOR_MAP_L2_PROMOTION_L2_256B, CU_TENSOR_MAP_FLOAT_OOB_FILL_NONE);
}
void map3d(EncodeFn enc, CUtensorMap* m, const void* base, uint64_t cols, uint64_t rows, uint32_t box_rows, uint32_t box_blks) {
  cuuint64_t dims[3] = {64, rows, cols / 64};
  cuuint64_t strides[2] = {cols * 2, 128};
  cuuint32_t box[3] = {64, box_rows, box_blks};
  cuuint32_t es[3] = {1, 1, 1};
  enc(m, CU_TENSOR_MAP_DATA_TYPE_BFLOAT16, 3, (void*)base, dims, strides, box, es, CU_TENSOR_MAP_INTERLEAVE_NONE,
      CU_TENSOR_MAP_SWIZZLE_128B, CU_TENSOR_MAP_L2_PROMOTION_L2_256B, CU_TENSOR_MAP_FLOAT_OOB_FILL_NONE);
}

}

extern "C" void kernel_launch(void* const* d_in, const int* in_sizes, int n_in, void* d_out, int out_size) {
  (void)in_sizes; (void)n_in; (void)out_size;
  static EncodeFn enc = nullptr;
  static void* act = nullptr;
  static void* flags = nullptr;
  if (!enc) {
    void* fn = nullptr;
    cudaDriverEntryPointQueryResult qr;
    cudaGetDriverEntryPoint("cuTensorMapEncodeTiled", &fn, cudaEnableDefault, &qr);
    enc = (EncodeFn)fn;
    cudaGetSymbolAddress(&act, g_act);
    cudaGetSymbolAddress(&flags, g_flags);
    cudaFuncSetAttribute(fused_kernel, cudaFuncAttributeMaxDynamicSharedMemorySize, SMEM_BYTES);
  }
  Params P;
  map2d(enc, &P.act_ld, act, ACT_W, SEQ, 128);
  map2d(enc, &P.act_st, act, ACT_W, SEQ, 64);
  map2d(enc, &P.x_ld, d_in[0], DM, SEQ, 128);
  map2d(enc, &P.out_st, d_out, DM, SEQ, 64);
  map2d(enc, &P.k_ld, d_in[1], 128, 4 * SK, 128);
  map3d(enc, &P.v_ld, d_in[2], 128, 4 * SK, 64, 2);
  map3d(enc, &P.wq, d_in[3], NQ, DM, 32, 4);
  map3d(enc, &P.w1b4, d_in[6], DFF, DM, 32, 4);
  map3d(enc, &P.w1b3, d_in[6], DFF, DM, 32, 3);
  map3d(enc, &P.wo, d_in[4], DM, NQ, 32, 4);
  map3d(enc, &P.w2, d_in[7], DM, DFF, 32, 4);
  P.x = (const __nv_bfloat16*)d_in[0];
  P.act = (__nv_bfloat16*)act;
  P.flags = (Flags*)flags;
  fused_kernel<<<NCLUSTER * 2, 384, SMEM_BYTES>>>(P);
}
```

```cpp
#include <cuda_runtime.h>
#include <cuda_bf16.h>
#include <cuda.h>
#include <stdint.h>

namespace {

constexpr int SEQ    = 2048;
constexpr int DM     = 1024;
constexpr int NQ     = 4096;
constexpr int DFF    = 3584;
constexpr int SK     = 2048;
constexpr int WIN    = 512;
constexpr int KV0    = SK - WIN;
constexpr int C_XN = 0, C_O = 1024, C_H = 5120, C_G = 8704, ACT_W = 9728;

constexpr int H_REG = 384, H_SPARE0 = 8 * H_REG;
static_assert(H_SPARE0 + 512 == DFF, "H split");

constexpr int NSLOT = 12, SLOT = 16384, NBAR = 8;
constexpr int SM_STG = NSLOT * SLOT;
constexpr int SM_BAR = SM_STG + 2 * 16384;
constexpr int SMEM_BYTES = SM_BAR + 256 + 1024;
constexpr int B_FULL = 0, B_EMPTY = 64, B_SFULL = 128, B_SEMPTY = 144, B_DONE = 160;

constexpr int NCLUSTER = 66;

struct Flags {
  unsigned ln[16][32];
  unsigned h[16][32];
  unsigned o[16][32];
  unsigned g[16][32];
  unsigned epoch[160];
};
__device__ __nv_bfloat16 g_act[(size_t)SEQ * ACT_W];
__device__ Flags g_flags;

struct Params {
  CUtensorMap act_ld, act_st, x_ld, out_st, k_ld, v_ld, wq, w1b4, w1b3, wo, w2;
  const __nv_bfloat16* x;
  __nv_bfloat16* act;
  Flags* flags;
};

__device__ __forceinline__ uint32_t smem_u32(const void* p) { return (uint32_t)__cvta_generic_to_shared(p); }
__device__ __forceinline__ void mbar_init(uint32_t bar, uint32_t cnt) {
  asm volatile("mbarrier.init.shared::cta.b64 [%0], %1;" ::"r"(bar), "r"(cnt) : "memory");
}
__device__ __forceinline__ bool mbar_try(uint32_t bar, uint32_t parity) {
  uint32_t ok;
  asm volatile("{\n.reg .pred p;\nmbarrier.try_wait.parity.shared::cta.b64 p, [%1], %2;\nselp.u32 %0, 1, 0, p;\n}\n"
               : "=r"(ok) : "r"(bar), "r"(parity) : "memory");
  return ok;
}
__device__ __forceinline__ void mbar_wait(uint32_t bar, uint32_t parity) {
  asm volatile("{\n.reg .pred p;\nWAIT_%=:\nmbarrier.try_wait.parity.shared::cta.b64 p, [%0], %1;\n@p bra DONE_%=;\nbra WAIT_%=;\nDONE_%=:\n}\n"
               ::"r"(bar), "r"(parity) : "memory");
}
__device__ __forceinline__ void mbar_arrive(uint32_t bar) {
  asm volatile("mbarrier.arrive.shared::cta.b64 _, [%0];" ::"r"(bar) : "memory");
}
__device__ __forceinline__ void mbar_arrive_cluster(uint32_t cluster_addr) {
  asm volatile("mbarrier.arrive.shared::cluster.b64 _, [%0];" ::"r"(cluster_addr) : "memory");
}
__device__ __forceinline__ void mbar_expect_tx(uint32_t bar, uint32_t bytes) {
  asm volatile("mbarrier.arrive.expect_tx.shared::cta.b64 _, [%0], %1;" ::"r"(bar), "r"(bytes) : "memory");
}
__device__ __forceinline__ uint32_t mapa(uint32_t addr, uint32_t rank) {
  uint32_t r;
  asm("mapa.shared::cluster.u32 %0, %1, %2;" : "=r"(r) : "r"(addr), "r"(rank));
  return r;
}
__device__ __forceinline__ void cluster_arrive() { asm volatile("barrier.cluster.arrive.relaxed.aligned;" ::: "memory"); }
__device__ __forceinline__ void cluster_wait() { asm volatile("barrier.cluster.wait.acquire.aligned;" ::: "memory"); }
__device__ __forceinline__ void bar_sync(int id, int n) { asm volatile("bar.sync %0, %1;" ::"r"(id), "r"(n) : "memory"); }
__device__ __forceinline__ void bar_arrive(int id, int n) { asm volatile("bar.arrive %0, %1;" ::"r"(id), "r"(n) : "memory"); }
__device__ __forceinline__ void fence_async_smem() { asm volatile("fence.proxy.async.shared::cta;" ::: "memory"); }
__device__ __forceinline__ void fence_async_all() { asm volatile("fence.proxy.async.global;" ::: "memory"); }

__device__ __forceinline__ void tma_ld2(uint32_t dst, const CUtensorMap* m, uint32_t bar, int c0, int c1) {
  asm volatile("cp.async.bulk.tensor.2d.shared::cluster.global.mbarrier::complete_tx::bytes [%0], [%1, {%3, %4}], [%2];"
               ::"r"(dst), "l"(m), "r"(bar), "r"(c0), "r"(c1) : "memory");
}
__device__ __forceinline__ void tma_ld2_mc(uint32_t dst, const CUtensorMap* m, uint32_t bar, int c0, int c1) {
  asm volatile("cp.async.bulk.tensor.2d.shared::cluster.global.mbarrier::complete_tx::bytes.multicast::cluster [%0], [%1, {%3, %4}], [%2], %5;"
               ::"r"(dst), "l"(m), "r"(bar), "r"(c0), "r"(c1), "h"((uint16_t)3) : "memory");
}
__device__ __forceinline__ void tma_ld3_mc(uint32_t dst, const CUtensorMap* m, uint32_t bar, int c0, int c1, int c2) {
  asm volatile("cp.async.bulk.tensor.3d.shared::cluster.global.mbarrier::complete_tx::bytes.multicast::cluster [%0], [%1, {%3, %4, %5}], [%2], %6;"
               ::"r"(dst), "l"(m), "r"(bar), "r"(c0), "r"(c1), "r"(c2), "h"((uint16_t)3) : "memory");
}
__device__ __forceinline__ void tma_ld3_mc_hint(uint32_t dst, const CUtensorMap* m, uint32_t bar, int c0, int c1, int c2, uint64_t pol) {
  asm volatile("cp.async.bulk.tensor.3d.shared::cluster.global.mbarrier::complete_tx::bytes.multicast::cluster.L2::cache_hint [%0], [%1, {%3, %4, %5}], [%2], %6, %7;"
               ::"r"(dst), "l"(m), "r"(bar), "r"(c0), "r"(c1), "r"(c2), "h"((uint16_t)3), "l"(pol) : "memory");
}
__device__ __forceinline__ void tma_ld2_hint(uint32_t dst, const CUtensorMap* m, uint32_t bar, int c0, int c1, uint64_t pol) {
  asm volatile("cp.async.bulk.tensor.2d.shared::cluster.global.mbarrier::complete_tx::bytes.L2::cache_hint [%0], [%1, {%3, %4}], [%2], %5;"
               ::"r"(dst), "l"(m), "r"(bar), "r"(c0), "r"(c1), "l"(pol) : "memory");
}
__device__ __forceinline__ void tma_st2_hint(const CUtensorMap* m, uint32_t src, int c0, int c1, uint64_t pol) {
  asm volatile("cp.async.bulk.tensor.2d.global.shared::cta.bulk_group.L2::cache_hint [%0, {%2, %3}], [%1], %4;"
               ::"l"(m), "r"(src), "r"(c0), "r"(c1), "l"(pol) : "memory");
}
#define POL_FIRST 0x12F0000000000000ull
__device__ __forceinline__ uint64_t policy_evict_first() {
  uint64_t p;
  asm volatile("createpolicy.fractional.L2::evict_first.b64 %0, 1.0;" : "=l"(p));
  return p;
}
__device__ __forceinline__ void tma_st2(const CUtensorMap* m, uint32_t src, int c0, int c1) {
  asm volatile("cp.async.bulk.tensor.2d.global.shared::cta.bulk_group [%0, {%2, %3}], [%1];"
               ::"l"(m), "r"(src), "r"(c0), "r"(c1) : "memory");
}
__device__ __forceinline__ void tma_pf2(const CUtensorMap* m, int c0, int c1) {
  asm volatile("cp.async.bulk.prefetch.tensor.2d.L2.global [%0, {%1, %2}];" ::"l"(m), "r"(c0), "r"(c1) : "memory");
}
__device__ __forceinline__ void bulk_commit() { asm volatile("cp.async.bulk.commit_group;" ::: "memory"); }
__device__ __forceinline__ void bulk_wait_read0() { asm volatile("cp.async.bulk.wait_group.read 0;" ::: "memory"); }
__device__ __forceinline__ void bulk_wait0() { asm volatile("cp.async.bulk.wait_group 0;" ::: "memory"); }
__device__ __forceinline__ void prefetch_map(const CUtensorMap* m) {
  asm volatile("prefetch.tensormap [%0];" ::"l"(m) : "memory");
}
__device__ __forceinline__ unsigned ld_acquire(const unsigned* p) {
  unsigned v;
  asm volatile("ld.acquire.gpu.global.u32 %0, [%1];" : "=r"(v) : "l"(p) : "memory");
  return v;
}
__device__ __forceinline__ void red_release(unsigned* p, unsigned v) {
  asm volatile("red.release.gpu.global.add.u32 [%0], %1;" ::"l"(p), "r"(v) : "memory");
}
__device__ __forceinline__ void wg_fence() { asm volatile("wgmma.fence.sync.aligned;" ::: "memory"); }
__device__ __forceinline__ void wg_commit() { asm volatile("wgmma.commit_group.sync.aligned;" ::: "memory"); }
template <int N> __device__ __forceinline__ void wg_wait() { asm volatile("wgmma.wait_group.sync.aligned %0;" ::"n"(N) : "memory"); }
template <int N> __device__ __forceinline__ void fence_regs(float (&d)[N]) {
#pragma unroll
  for (int i = 0; i < N; i++) asm volatile("" : "+f"(d[i])::"memory");
}
template <int N> __device__ __forceinline__ void fence_regs(uint32_t (&d)[N]) {
#pragma unroll
  for (int i = 0; i < N; i++) asm volatile("" : "+r"(d[i])::"memory");
}
__device__ __forceinline__ uint64_t mkdesc(uint32_t addr, uint32_t lbo, uint32_t sbo) {
  return (uint64_t)((addr & 0x3FFFF) >> 4) | ((uint64_t)(lbo >> 4) << 16) | ((uint64_t)(sbo >> 4) << 32) | (1ull << 62);
}
__device__ __forceinline__ uint32_t pack_bf16(float lo, float hi) {
  uint32_t r;
  asm("cvt.rn.bf16x2.f32 %0, %1, %2;" : "=r"(r) : "f"(hi), "f"(lo));
  return r;
}
__device__ __forceinline__ uint32_t pack_bf16_relu(float lo, float hi) {
  uint32_t r;
  asm("cvt.rn.relu.bf16x2.f32 %0, %1, %2;" : "=r"(r) : "f"(hi), "f"(lo));
  return r;
}
__device__ __forceinline__ float bf_lo(uint32_t v) { return __uint_as_float(v << 16); }
__device__ __forceinline__ float bf_hi(uint32_t v) { return __uint_as_float(v & 0xFFFF0000u); }
__device__ __forceinline__ float bf_round(float v) { return __bfloat162float(__float2bfloat16_rn(v)); }
__device__ __forceinline__ float ex2(float x) {
  float r;
  asm("ex2.approx.ftz.f32 %0, %1;" : "=f"(r) : "f"(x));
  return r;
}
__device__ __forceinline__ float rcp(float x) {
  float r;
  asm("rcp.approx.ftz.f32 %0, %1;" : "=f"(r) : "f"(x));
  return r;
}
__device__ __forceinline__ uint32_t tid_x() {
  uint32_t t;
  asm volatile("mov.u32 %0, %%tid.x;" : "=r"(t));
  return t;
}
__device__ __forceinline__ void stsm4(uint32_t addr, uint32_t r0, uint32_t r1, uint32_t r2, uint32_t r3) {
  asm volatile("stmatrix.sync.aligned.m8n8.x4.shared.b16 [%0], {%1, %2, %3, %4};" ::"r"(addr), "r"(r0), "r"(r1), "r"(r2), "r"(r3) : "memory");
}
__device__ __forceinline__ void ldsm4(uint32_t addr, uint32_t& r0, uint32_t& r1, uint32_t& r2, uint32_t& r3) {
  asm volatile("ldmatrix.sync.aligned.m8n8.x4.shared.b16 {%0, %1, %2, %3}, [%4];" : "=r"(r0), "=r"(r1), "=r"(r2), "=r"(r3) : "r"(addr) : "memory");
}
__device__ __forceinline__ void sts128(uint32_t addr, uint32_t r0, uint32_t r1, uint32_t r2, uint32_t r3) {
  asm volatile("st.shared.v4.b32 [%0], {%1, %2, %3, %4};" ::"r"(addr), "r"(r0), "r"(r1), "r"(r2), "r"(r3) : "memory");
}
__device__ __forceinline__ void lds128(uint32_t addr, uint32_t& r0, uint32_t& r1, uint32_t& r2, uint32_t& r3) {
  asm volatile("ld.shared.v4.b32 {%0, %1, %2, %3}, [%4];" : "=r"(r0), "=r"(r1), "=r"(r2), "=r"(r3) : "r"(addr) : "memory");
}
__device__ __forceinline__ unsigned long long gtime() {
  unsigned long long t;
  asm volatile("mov.u64 %0, %globaltimer;" : "=l"(t));
  return t;
}

__device__ __forceinline__ void wgmma_ss_n256_tb(float (&d)[128], uint64_t da, uint64_t db, uint32_t sc) {
  asm volatile("{\n.reg .pred p;\nsetp.ne.b32 p, %130, 0;\n"
    "wgmma.mma_async.sync.aligned.m64n256k16.f32.bf16.bf16 "
    "{%0, %1, %2, %3, %4, %5, %6, %7, %8, %9, %10, %11, %12, %13, %14, %15, %16, %17, %18, %19, %20, %21, %22, %23, %24, %25, %26, %27, %28, %29, %30, %31, %32, %33, %34, %35, %36, %37, %38, %39, %40, %41, %42, %43, %44, %45, %46, %47, %48, %49, %50, %51, %52, %53, %54, %55, %56, %57, %58, %59, %60, %61, %62, %63, %64, %65, %66, %67, %68, %69, %70, %71, %72, %73, %74, %75, %76, %77, %78, %79, %80, %81, %82, %83, %84, %85, %86, %87, %88, %89, %90, %91, %92, %93, %94, %95, %96, %97, %98, %99, %100, %101, %102, %103, %104, %105, %106, %107, %108, %109, %110, %111, %112, %113, %114, %115, %116, %117, %118, %119, %120, %121, %122, %123, %124, %125, %126, %127}, %128, %129, p, 1, 1, 0, 1;\n}\n"
    : "+f"(d[0]), "+f"(d[1]), "+f"(d[2]), "+f"(d[3]), "+f"(d[4]), "+f"(d[5]), "+f"(d[6]), "+f"(d[7]), "+f"(d[8]), "+f"(d[9]), "+f"(d[10]), "+f"(d[11]), "+f"(d[12]), "+f"(d[13]), "+f"(d[14]), "+f"(d[15]), "+f"(d[16]), "+f"(d[17]), "+f"(d[18]), "+f"(d[19]), "+f"(d[20]), "+f"(d[21]), "+f"(d[22]), "+f"(d[23]), "+f"(d[24]), "+f"(d[25]), "+f"(d[26]), "+f"(d[27]), "+f"(d[28]), "+f"(d[29]), "+f"(d[30]), "+f"(d[31]), "+f"(d[32]), "+f"(d[33]), "+f"(d[34]), "+f"(d[35]), "+f"(d[36]), "+f"(d[37]), "+f"(d[38]), "+f"(d[39]), "+f"(d[40]), "+f"(d[41]), "+f"(d[42]), "+f"(d[43]), "+f"(d[44]), "+f"(d[45]), "+f"(d[46]), "+f"(d[47]), "+f"(d[48]), "+f"(d[49]), "+f"(d[50]), "+f"(d[51]), "+f"(d[52]), "+f"(d[53]), "+f"(d[54]), "+f"(d[55]), "+f"(d[56]), "+f"(d[57]), "+f"(d[58]), "+f"(d[59]), "+f"(d[60]), "+f"(d[61]), "+f"(d[62]), "+f"(d[63]), "+f"(d[64]), "+f"(d[65]), "+f"(d[66]), "+f"(d[67]), "+f"(d[68]), "+f"(d[69]), "+f"(d[70]), "+f"(d[71]), "+f"(d[72]), "+f"(d[73]), "+f"(d[74]), "+f"(d[75]), "+f"(d[76]), "+f"(d[77]), "+f"(d[78]), "+f"(d[79]), "+f"(d[80]), "+f"(d[81]), "+f"(d[82]), "+f"(d[83]), "+f"(d[84]), "+f"(d[85]), "+f"(d[86]), "+f"(d[87]), "+f"(d[88]), "+f"(d[89]), "+f"(d[90]), "+f"(d[91]), "+f"(d[92]), "+f"(d[93]), "+f"(d[94]), "+f"(d[95]), "+f"(d[96]), "+f"(d[97]), "+f"(d[98]), "+f"(d[99]), "+f"(d[100]), "+f"(d[101]), "+f"(d[102]), "+f"(d[103]), "+f"(d[104]), "+f"(d[105]), "+f"(d[106]), "+f"(d[107]), "+f"(d[108]), "+f"(d[109]), "+f"(d[110]), "+f"(d[111]), "+f"(d[112]), "+f"(d[113]), "+f"(d[114]), "+f"(d[115]), "+f"(d[116]), "+f"(d[117]), "+f"(d[118]), "+f"(d[119]), "+f"(d[120]), "+f"(d[121]), "+f"(d[122]), "+f"(d[123]), "+f"(d[124]), "+f"(d[125]), "+f"(d[126]), "+f"(d[127])
    : "l"(da), "l"(db), "r"(sc));
}
__device__ __forceinline__ void wgmma_ss_n192_tb(float (&d)[128], uint64_t da, uint64_t db, uint32_t sc) {
  asm volatile("{\n.reg .pred p;\nsetp.ne.b32 p, %98, 0;\n"
    "wgmma.mma_async.sync.aligned.m64n192k16.f32.bf16.bf16 "
    "{%0, %1, %2, %3, %4, %5, %6, %7, %8, %9, %10, %11, %12, %13, %14, %15, %16, %17, %18, %19, %20, %21, %22, %23, %24, %25, %26, %27, %28, %29, %30, %31, %32, %33, %34, %35, %36, %37, %38, %39, %40, %41, %42, %43, %44, %45, %46, %47, %48, %49, %50, %51, %52, %53, %54, %55, %56, %57, %58, %59, %60, %61, %62, %63, %64, %65, %66, %67, %68, %69, %70, %71, %72, %73, %74, %75, %76, %77, %78, %79, %80, %81, %82, %83, %84, %85, %86, %87, %88, %89, %90, %91, %92, %93, %94, %95}, %96, %97, p, 1, 1, 0, 1;\n}\n"
    : "+f"(d[0]), "+f"(d[1]), "+f"(d[2]), "+f"(d[3]), "+f"(d[4]), "+f"(d[5]), "+f"(d[6]), "+f"(d[7]), "+f"(d[8]), "+f"(d[9]), "+f"(d[10]), "+f"(d[11]), "+f"(d[12]), "+f"(d[13]), "+f"(d[14]), "+f"(d[15]), "+f"(d[16]), "+f"(d[17]), "+f"(d[18]), "+f"(d[19]), "+f"(d[20]), "+f"(d[21]), "+f"(d[22]), "+f"(d[23]), "+f"(d[24]), "+f"(d[25]), "+f"(d[26]), "+f"(d[27]), "+f"(d[28]), "+f"(d[29]), "+f"(d[30]), "+f"(d[31]), "+f"(d[32]), "+f"(d[33]), "+f"(d[34]), "+f"(d[35]), "+f"(d[36]), "+f"(d[37]), "+f"(d[38]), "+f"(d[39]), "+f"(d[40]), "+f"(d[41]), "+f"(d[42]), "+f"(d[43]), "+f"(d[44]), "+f"(d[45]), "+f"(d[46]), "+f"(d[47]), "+f"(d[48]), "+f"(d[49]), "+f"(d[50]), "+f"(d[51]), "+f"(d[52]), "+f"(d[53]), "+f"(d[54]), "+f"(d[55]), "+f"(d[56]), "+f"(d[57]), "+f"(d[58]), "+f"(d[59]), "+f"(d[60]), "+f"(d[61]), "+f"(d[62]), "+f"(d[63]), "+f"(d[64]), "+f"(d[65]), "+f"(d[66]), "+f"(d[67]), "+f"(d[68]), "+f"(d[69]), "+f"(d[70]), "+f"(d[71]), "+f"(d[72]), "+f"(d[73]), "+f"(d[74]), "+f"(d[75]), "+f"(d[76]), "+f"(d[77]), "+f"(d[78]), "+f"(d[79]), "+f"(d[80]), "+f"(d[81]), "+f"(d[82]), "+f"(d[83]), "+f"(d[84]), "+f"(d[85]), "+f"(d[86]), "+f"(d[87]), "+f"(d[88]), "+f"(d[89]), "+f"(d[90]), "+f"(d[91]), "+f"(d[92]), "+f"(d[93]), "+f"(d[94]), "+f"(d[95])
    : "l"(da), "l"(db), "r"(sc));
}
__device__ __forceinline__ void wgmma_rs_n128(float (&d)[64], uint32_t a0, uint32_t a1, uint32_t a2, uint32_t a3, uint64_t db, uint32_t sc) {
  asm volatile("{\n.reg .pred p;\nsetp.ne.b32 p, %69, 0;\n"
    "wgmma.mma_async.sync.aligned.m64n128k16.f32.bf16.bf16 "
    "{%0, %1, %2, %3, %4, %5, %6, %7, %8, %9, %10, %11, %12, %13, %14, %15, %16, %17, %18, %19, %20, %21, %22, %23, %24, %25, %26, %27, %28, %29, %30, %31, %32, %33, %34, %35, %36, %37, %38, %39, %40, %41, %42, %43, %44, %45, %46, %47, %48, %49, %50, %51, %52, %53, %54, %55, %56, %57, %58, %59, %60, %61, %62, %63}, {%64, %65, %66, %67}, %68, p, 1, 1, 0;\n}\n"
    : "+f"(d[0]), "+f"(d[1]), "+f"(d[2]), "+f"(d[3]), "+f"(d[4]), "+f"(d[5]), "+f"(d[6]), "+f"(d[7]), "+f"(d[8]), "+f"(d[9]), "+f"(d[10]), "+f"(d[11]), "+f"(d[12]), "+f"(d[13]), "+f"(d[14]), "+f"(d[15]), "+f"(d[16]), "+f"(d[17]), "+f"(d[18]), "+f"(d[19]), "+f"(d[20]), "+f"(d[21]), "+f"(d[22]), "+f"(d[23]), "+f"(d[24]), "+f"(d[25]), "+f"(d[26]), "+f"(d[27]), "+f"(d[28]), "+f"(d[29]), "+f"(d[30]), "+f"(d[31]), "+f"(d[32]), "+f"(d[33]), "+f"(d[34]), "+f"(d[35]), "+f"(d[36]), "+f"(d[37]), "+f"(d[38]), "+f"(d[39]), "+f"(d[40]), "+f"(d[41]), "+f"(d[42]), "+f"(d[43]), "+f"(d[44]), "+f"(d[45]), "+f"(d[46]), "+f"(d[47]), "+f"(d[48]), "+f"(d[49]), "+f"(d[50]), "+f"(d[51]), "+f"(d[52]), "+f"(d[53]), "+f"(d[54]), "+f"(d[55]), "+f"(d[56]), "+f"(d[57]), "+f"(d[58]), "+f"(d[59]), "+f"(d[60]), "+f"(d[61]), "+f"(d[62]), "+f"(d[63])
    : "r"(a0), "r"(a1), "r"(a2), "r"(a3), "l"(db), "r"(sc));
}
__device__ __forceinline__ void wgmma_rs_n128_tb(float (&d)[64], uint32_t a0, uint32_t a1, uint32_t a2, uint32_t a3, uint64_t db, uint32_t sc) {
  asm volatile("{\n.reg .pred p;\nsetp.ne.b32 p, %69, 0;\n"
    "wgmma.mma_async.sync.aligned.m64n128k16.f32.bf16.bf16 "
    "{%0, %1, %2, %3, %4, %5, %6, %7, %8, %9, %10, %11, %12, %13, %14, %15, %16, %17, %18, %19, %20, %21, %22, %23, %24, %25, %26, %27, %28, %29, %30, %31, %32, %33, %34, %35, %36, %37, %38, %39, %40, %41, %42, %43, %44, %45, %46, %47, %48, %49, %50, %51, %52, %53, %54, %55, %56, %57, %58, %59, %60, %61, %62, %63}, {%64, %65, %66, %67}, %68, p, 1, 1, 1;\n}\n"
    : "+f"(d[0]), "+f"(d[1]), "+f"(d[2]), "+f"(d[3]), "+f"(d[4]), "+f"(d[5]), "+f"(d[6]), "+f"(d[7]), "+f"(d[8]), "+f"(d[9]), "+f"(d[10]), "+f"(d[11]), "+f"(d[12]), "+f"(d[13]), "+f"(d[14]), "+f"(d[15]), "+f"(d[16]), "+f"(d[17]), "+f"(d[18]), "+f"(d[19]), "+f"(d[20]), "+f"(d[21]), "+f"(d[22]), "+f"(d[23]), "+f"(d[24]), "+f"(d[25]), "+f"(d[26]), "+f"(d[27]), "+f"(d[28]), "+f"(d[29]), "+f"(d[30]), "+f"(d[31]), "+f"(d[32]), "+f"(d[33]), "+f"(d[34]), "+f"(d[35]), "+f"(d[36]), "+f"(d[37]), "+f"(d[38]), "+f"(d[39]), "+f"(d[40]), "+f"(d[41]), "+f"(d[42]), "+f"(d[43]), "+f"(d[44]), "+f"(d[45]), "+f"(d[46]), "+f"(d[47]), "+f"(d[48]), "+f"(d[49]), "+f"(d[50]), "+f"(d[51]), "+f"(d[52]), "+f"(d[53]), "+f"(d[54]), "+f"(d[55]), "+f"(d[56]), "+f"(d[57]), "+f"(d[58]), "+f"(d[59]), "+f"(d[60]), "+f"(d[61]), "+f"(d[62]), "+f"(d[63])
    : "r"(a0), "r"(a1), "r"(a2), "r"(a3), "l"(db), "r"(sc));
}

#define TS(i) do {} while (0)
#define TR(j, i) do {} while (0)
#define TSS(i, c) do {} while (0)

__device__ __forceinline__ uint32_t wrap12(uint32_t p) { return p >= NSLOT ? p - NSLOT : p; }

struct Cons {
  uint32_t sb;
  uint32_t g, pos;
  uint32_t rel;
  uint32_t nstg;
  uint32_t zero;
  int wg, lane;
  __device__ __forceinline__ void wait_full(uint32_t gg) const { mbar_wait(sb + SM_BAR + B_FULL + (gg & 7) * 8, (gg >> 3) & 1); }
  __device__ __forceinline__ void release(uint32_t gg) const { if (lane < 2) mbar_arrive_cluster(rel + (gg & 7) * 8); }
  __device__ __forceinline__ void stg_acquire() { mbar_wait(sb + SM_BAR + B_SEMPTY + wg * 8, (nstg & 1) ^ 1); nstg++; }
  __device__ __forceinline__ void stg_publish() const {
    fence_async_smem();
    __syncwarp();
    if (lane == 0) mbar_arrive(sb + SM_BAR + B_SFULL + wg * 8);
  }
};

__device__ __forceinline__ void frag_addr(uint32_t& rowoff, uint32_t& xr) {
  const uint32_t t = tid_x();
  rowoff = ((t >> 5) & 3) * 2048 + (t & 15) * 128;
  xr = (((t >> 4) & 1) ^ (t & 7)) << 4;
}
template <int NB, int NR>
__device__ __forceinline__ void stage_boxes(const uint32_t (&r)[NR], int r0, const Cons& c) {
  uint32_t rowoff, xr;
  frag_addr(rowoff, xr);
  const uint32_t stg = c.sb + SM_STG + c.wg * 16384 + rowoff;
#pragma unroll
  for (int b = 0; b < NB; b++)
#pragma unroll
    for (int kb = 0; kb < 4; kb++)
      stsm4(stg + b * 8192 + ((32 * kb) ^ xr), r[r0 + b * 16 + kb * 4], r[r0 + b * 16 + kb * 4 + 1], r[r0 + b * 16 + kb * 4 + 2], r[r0 + b * 16 + kb * 4 + 3]);
  c.stg_publish();
}

template <int N, bool FIRST>
__device__ __forceinline__ void gemm_step(float (&acc)[128], Cons& c, uint32_t prev = 1) {
  const uint32_t p1 = wrap12(c.pos + 1), p2 = wrap12(c.pos + 2);
  const uint64_t da = mkdesc(c.sb + c.wg * 8192 + c.pos * SLOT, 16, 1024);
  const uint64_t b0 = mkdesc(c.sb + p1 * SLOT, 4096, 1024);
  const uint64_t b1 = mkdesc(c.sb + p2 * SLOT, 4096, 1024);
  c.wait_full(c.g);
  wg_fence();
  if (N == 256) {
    wgmma_ss_n256_tb(acc, da, b0, FIRST ? 0 : 1);
    wgmma_ss_n256_tb(acc, da + 2, b0 + 128, 1);
    wgmma_ss_n256_tb(acc, da + 4, b1, 1);
    wgmma_ss_n256_tb(acc, da + 6, b1 + 128, 1);
  } else {
    wgmma_ss_n192_tb(acc, da, b0, FIRST ? 0 : 1);
    wgmma_ss_n192_tb(acc, da + 2, b0 + 128, 1);
    wgmma_ss_n192_tb(acc, da + 4, b1, 1);
    wgmma_ss_n192_tb(acc, da + 6, b1 + 128, 1);
  }
  wg_commit();
  if (!FIRST) {
    wg_wait<1>();
    c.release(c.g - prev);
  }
  c.g++;
  c.pos = wrap12(p2 + 1);
}

template <int N>
__device__ __forceinline__ void gemm_loop(float (&acc)[128], Cons& c, int nk) {
  gemm_step<N, true>(acc, c);
#pragma unroll 1
  for (int k = 1; k < nk; k++) gemm_step<N, false>(acc, c);
  wg_wait<0>();
  c.release(c.g - 1);
  fence_regs(acc);
}
template <int N, int NB>
__device__ __forceinline__ void gemm_loop_flush(float (&acc)[128], Cons& c, const uint32_t (&pend)[NB * 16], bool flush) {
  gemm_step<N, true>(acc, c);
#pragma unroll 1
  for (int k = 1; k < 16; k++) {
    gemm_step<N, false>(acc, c);
    if (k == 3 && flush) {
      c.stg_acquire();
      stage_boxes<NB>(pend, 0, c);
    }
  }
  wg_wait<0>();
  c.release(c.g - 1);
  fence_regs(acc);
}
template <int NB>
__device__ __forceinline__ void h_epilogue(const float (&acc)[128], Cons& c, uint32_t (&pend)[NB * 16]) {
  uint32_t r[32];
#pragma unroll
  for (int i = 0; i < 32; i++) r[i] = pack_bf16_relu(acc[2 * i], acc[2 * i + 1]);
  c.stg_acquire();
  stage_boxes<2>(r, 0, c);
#pragma unroll
  for (int i = 0; i < NB * 16; i++) pend[i] = pack_bf16_relu(acc[64 + 2 * i], acc[65 + 2 * i]);
}

template <int R0>
__device__ __forceinline__ void load_x(uint32_t (&xv)[64], Cons& c) {
  uint32_t rowoff, xr;
  frag_addr(rowoff, xr);
  c.wait_full(c.g);
#pragma unroll
  for (int b = 0; b < 2; b++)
#pragma unroll
    for (int kb = 0; kb < 4; kb++)
      ldsm4(c.sb + wrap12(c.pos + b) * SLOT + c.wg * 8192 + rowoff + ((32 * kb) ^ xr), xv[R0 + 16 * b + 4 * kb], xv[R0 + 16 * b + 4 * kb + 1],
            xv[R0 + 16 * b + 4 * kb + 2], xv[R0 + 16 * b + 4 * kb + 3]);
#pragma unroll
  for (int i = 0; i < 32; i++) asm volatile("" : "+r"(xv[R0 + i])::"memory");
  __syncwarp();
  c.release(c.g);
  c.g++;
  c.pos = wrap12(c.pos + 2);
}

__device__ __forceinline__ uint32_t silu2(uint32_t f2) {
  const float a = bf_lo(f2), b = bf_hi(f2);
  const float ta = ex2(-1.4426950408889634f * fabsf(a)), tb = ex2(-1.4426950408889634f * fabsf(b));
  const float da = 1.0f + ta, db = 1.0f + tb;
  const float r = rcp(da * db);
  return pack_bf16((a >= 0.f ? a : a * ta) * (r * db), (b >= 0.f ? b : b * tb) * (r * da));
}

constexpr float SM_C = 0.08838834764831845f * 1.4426950408889634f;

#define ONCE(c) _Pragma("unroll 1") for (uint32_t once_ = 0; once_ <= (c).zero; once_++)
__device__ __forceinline__ void row_max2(const float (&S)[64], float& n0, float& n1) {
  float x[4], y[4];
#pragma unroll
  for (int i = 0; i < 4; i++) { x[i] = fmaxf(S[4 * i], S[4 * i + 1]); y[i] = fmaxf(S[4 * i + 2], S[4 * i + 3]); }
#pragma unroll
  for (int i = 4; i < 16; i++) {
    x[i & 3] = fmaxf(x[i & 3], fmaxf(S[4 * i], S[4 * i + 1]));
    y[i & 3] = fmaxf(y[i & 3], fmaxf(S[4 * i + 2], S[4 * i + 3]));
  }
  n0 = fmaxf(fmaxf(x[0], x[1]), fmaxf(x[2], x[3]));
  n1 = fmaxf(fmaxf(y[0], y[1]), fmaxf(y[2], y[3]));
  n0 = fmaxf(n0, __shfl_xor_sync(~0u, n0, 1));
  n1 = fmaxf(n1, __shfl_xor_sync(~0u, n1, 1));
  n0 = fmaxf(n0, __shfl_xor_sync(~0u, n0, 2));
  n1 = fmaxf(n1, __shfl_xor_sync(~0u, n1, 2));
}
__device__ __forceinline__ void to_exponent(float (&S)[64], float cc0, float cc1) {
#pragma unroll
  for (int i = 0; i < 16; i++) {
    S[4 * i] = fmaf(S[4 * i], SM_C, cc0); S[4 * i + 1] = fmaf(S[4 * i + 1], SM_C, cc0);
    S[4 * i + 2] = fmaf(S[4 * i + 2], SM_C, cc1); S[4 * i + 3] = fmaf(S[4 * i + 3], SM_C, cc1);
  }
}
__device__ __forceinline__ void scale_o(float (&O)[64], float f0, float f1) {
#pragma unroll
  for (int i = 0; i < 16; i++) { O[4 * i] *= f0; O[4 * i + 1] *= f0; O[4 * i + 2] *= f1; O[4 * i + 3] *= f1; }
}
template <int G0>
__device__ __forceinline__ void exp_pack(const float (&S)[64], uint32_t (&p)[32], float (&a)[4]) {
#pragma unroll
  for (int i = G0; i < 16; i++) {
    const float e0 = ex2(S[4 * i]), e1 = ex2(S[4 * i + 1]), e2 = ex2(S[4 * i + 2]), e3 = ex2(S[4 * i + 3]);
    a[0] += e0; a[1] += e1; a[2] += e2; a[3] += e3;
    p[2 * i] = pack_bf16(e0, e1);
    p[2 * i + 1] = pack_bf16(e2, e3);
  }
}
#define EARLY 4
__device__ __forceinline__ void softmax_early(float (&S)[64], float cc0, float cc1, float (&a)[4], uint32_t (&pe)[2 * EARLY + 1], const Cons& c) {
  a[0] = a[1] = a[2] = a[3] = 0.f;
  ONCE(c) {
    to_exponent(S, cc0, cc1);
#pragma unroll
    for (int i = 0; i < EARLY; i++) {
      const float e0 = ex2(S[4 * i]), e1 = ex2(S[4 * i + 1]), e2 = ex2(S[4 * i + 2]), e3 = ex2(S[4 * i + 3]);
      a[0] += e0; a[1] += e1; a[2] += e2; a[3] += e3;
      pe[2 * i] = pack_bf16(e0, e1);
      pe[2 * i + 1] = pack_bf16(e2, e3);
    }
  }
}
__device__ __forceinline__ void softmax_late(float (&S)[64], uint32_t (&p)[32], float (&O)[64], float& cc0, float& cc1, float& l0, float& l1,
                                             float (&a)[4], const uint32_t (&pe)[2 * EARLY + 1], uint32_t zero) {
#pragma unroll
  for (int i = 0; i < 2 * EARLY; i++) p[i] = pe[i] ^ zero;
  exp_pack<EARLY>(S, p, a);
  if (__any_sync(~0u, !(fmaxf(a[0] + a[1], a[2] + a[3]) <= 65536.f))) {
    float d0, d1;
    row_max2(S, d0, d1);
    d0 = fmaxf(d0, 0.f); d1 = fmaxf(d1, 0.f);
#pragma unroll
    for (int i = 0; i < 16; i++) { S[4 * i] -= d0; S[4 * i + 1] -= d0; S[4 * i + 2] -= d1; S[4 * i + 3] -= d1; }
    cc0 -= d0; cc1 -= d1;
    const float f0 = ex2(-d0), f1 = ex2(-d1);
    scale_o(O, f0, f1);
    l0 *= f0; l1 *= f1;
    a[0] = a[1] = a[2] = a[3] = 0.f;
    exp_pack<0>(S, p, a);
  }
  l0 += a[0] + a[1];
  l1 += a[2] + a[3];
}

__device__ __forceinline__ void inv_rowsum(float l0, float l1, float& i0, float& i1) {
  l0 += __shfl_xor_sync(~0u, l0, 1); l1 += __shfl_xor_sync(~0u, l1, 1);
  l0 += __shfl_xor_sync(~0u, l0, 2); l1 += __shfl_xor_sync(~0u, l1, 2);
  i0 = rcp(l0); i1 = rcp(l1);
}
__device__ __forceinline__ void write_o(const float (&O)[64], const Cons& c) {
  uint32_t rowoff, xr;
  frag_addr(rowoff, xr);
  const uint32_t stg = c.sb + SM_STG + c.wg * 16384 + rowoff;
#pragma unroll
  for (int kb = 0; kb < 8; kb++)
    stsm4(stg + (kb >> 2) * 8192 + ((32 * (kb & 3)) ^ xr),
          pack_bf16(O[8 * kb], O[8 * kb + 1]), pack_bf16(O[8 * kb + 2], O[8 * kb + 3]),
          pack_bf16(O[8 * kb + 4], O[8 * kb + 5]), pack_bf16(O[8 * kb + 6], O[8 * kb + 7]));
  c.stg_publish();
}

__device__ __forceinline__ void issue_qk(float (&S)[64], const uint32_t (&q)[32], uint32_t s0, uint32_t s1, uint32_t zero) {
  const uint64_t d0 = mkdesc(s0, 16, 1024), d1 = mkdesc(s1, 16, 1024);
#pragma unroll
  for (int kk = 0; kk < 8; kk++)
    wgmma_rs_n128(S, q[4 * kk], q[4 * kk + 1], q[4 * kk + 2], q[4 * kk + 3], (kk < 4 ? d0 : d1) + (kk & 3) * 2, kk > 0 ? 1u : zero);
}
__device__ __forceinline__ void issue_pv(float (&O)[64], const uint32_t (&p)[32], uint32_t s0, uint32_t s1, uint32_t accum) {
  const uint64_t d0 = mkdesc(s0, 8192, 1024), d1 = mkdesc(s1, 8192, 1024);
#pragma unroll
  for (int kk = 0; kk < 8; kk++)
    wgmma_rs_n128_tb(O, p[4 * kk], p[4 * kk + 1], p[4 * kk + 2], p[4 * kk + 3], (kk < 4 ? d0 : d1) + (kk & 3) * 128, kk > 0 ? 1u : accum);
}

#define TURN_SYNC()   bar_sync(1 + c.wg, 256)
#define TURN_PASS()   bar_arrive(2 - c.wg, 256)

__device__ __forceinline__ void attn_tile(const float (&acc)[128], Cons& c, int t) {
  uint32_t q[32], p[32];
  float S[64], O[64];
  const uint32_t stash = c.sb + SM_STG + c.wg * 16384 + ((threadIdx.x >> 5) & 3) * 2048 + c.lane * 16;
#pragma unroll
  for (int i = 0; i < 32; i++) q[i] = pack_bf16(acc[2 * i], acc[2 * i + 1]);
  c.stg_acquire();
#pragma unroll
  for (int i = 0; i < 8; i++)
    sts128(stash + (i >> 2) * 8192 + (i & 3) * 512, pack_bf16(acc[64 + 8 * i], acc[65 + 8 * i]), pack_bf16(acc[66 + 8 * i], acc[67 + 8 * i]),
           pack_bf16(acc[68 + 8 * i], acc[69 + 8 * i]), pack_bf16(acc[70 + 8 * i], acc[71 + 8 * i]));
  fence_regs(q);
  TR(0, 0);
  TURN_SYNC();
  TR(0, 1);
  c.wait_full(c.g);
  wg_fence();
  issue_qk(O, q, c.sb + c.pos * SLOT, c.sb + wrap12(c.pos + 1) * SLOT, 0);
  wg_commit();
  c.wait_full(c.g + 1);
  wg_fence();
  issue_qk(S, q, c.sb + wrap12(c.pos + 2) * SLOT, c.sb + wrap12(c.pos + 3) * SLOT, 0);
  wg_commit();
  TURN_PASS();
  TR(0, 2);
  wg_wait<1>();
  TR(0, 3);
  fence_regs(O);
  c.release(c.g);
  float cc0, cc1, l0, l1, f0 = 0.f, f1 = 0.f;
  float a[4] = {0.f, 0.f, 0.f, 0.f};
  uint32_t pe[2 * EARLY + 1];
  row_max2(O, cc0, cc1);
  cc0 *= -SM_C; cc1 *= -SM_C;
  ONCE(c) { to_exponent(O, cc0, cc1); }
  wg_wait<0>();
  fence_regs(S);
  fence_regs(q);
  c.release(c.g + 1);
  exp_pack<0>(O, p, a);
  l0 = a[0] + a[1];
  l1 = a[2] + a[3];
  c.pos = wrap12(c.pos + 4);
  TR(1, 0);
  TURN_SYNC();
  TR(1, 1);
  c.wait_full(c.g + 2);
  wg_fence();
  issue_pv(O, p, c.sb + c.pos * SLOT, c.sb + wrap12(c.pos + 1) * SLOT, 0);
  wg_commit();
  TURN_PASS();
  TR(1, 2);
  softmax_early(S, cc0, cc1, a, pe, c);
  TR(1, 4);
  wg_wait<0>();
  TR(1, 5);
  fence_regs(O);
  fence_regs(p);
  c.release(c.g + 2);
  c.g += 3;
  c.pos = wrap12(c.pos + 2);
  softmax_late(S, p, O, cc0, cc1, l0, l1, a, pe, c.zero);
#pragma unroll 1
  for (int j = 1; j < 7 + (int)c.zero; j++) {
    const uint32_t k0 = c.pos, k1 = wrap12(k0 + 1), v0 = wrap12(k0 + 2), v1 = wrap12(k0 + 3);
    TR(j + 1, 0);
    TURN_SYNC();
    TR(j + 1, 1);
    c.wait_full(c.g);
    wg_fence();
    issue_qk(S, q, c.sb + k0 * SLOT, c.sb + k1 * SLOT, 0);
    wg_commit();
    if (j == 4) {
      scale_o(O, f0, f1);
      write_o(O, c);
    }
    c.wait_full(c.g + 1);
    wg_fence();
    issue_pv(O, p, c.sb + v0 * SLOT, c.sb + v1 * SLOT, j != 4);
    wg_commit();
    TURN_PASS();
    TR(j + 1, 2);
    wg_wait<1>();
    TR(j + 1, 3);
    fence_regs(S);
    fence_regs(q);
    c.release(c.g);
    if (j == 3) {
      row_max2(S, cc0, cc1);
      cc0 *= -SM_C; cc1 *= -SM_C;
      inv_rowsum(l0, l1, f0, f1);
      l0 = 0.f; l1 = 0.f;
    }
    softmax_early(S, cc0, cc1, a, pe, c);
    if (j == 2) {
#pragma unroll
      for (int i = 0; i < 8; i++) lds128(stash + (i >> 2) * 8192 + (i & 3) * 512, q[4 * i], q[4 * i + 1], q[4 * i + 2], q[4 * i + 3]);
      __syncwarp();
    }
    TR(j + 1, 4);
    wg_wait<0>();
    TR(j + 1, 5);
    fence_regs(O);
    fence_regs(p);
    c.release(c.g + 1);
    c.g += 2;
    c.pos = wrap12(v1 + 1);
    softmax_late(S, p, O, cc0, cc1, l0, l1, a, pe, c.zero);
  }
  TR(8, 0);
  TURN_SYNC();
  TR(8, 1);
  c.wait_full(c.g);
  wg_fence();
  issue_pv(O, p, c.sb + c.pos * SLOT, c.sb + wrap12(c.pos + 1) * SLOT, 1);
  wg_commit();
  TURN_PASS();
  TR(8, 2);
  c.stg_acquire();
  float a0, a1;
  inv_rowsum(l0, l1, a0, a1);
  wg_wait<0>();
  TR(8, 5);
  fence_regs(O);
  fence_regs(p);
  c.release(c.g);
  c.g++;
  c.pos = wrap12(c.pos + 2);
  scale_o(O, a0, a1);
  write_o(O, c);
  TR(9, 0);
}

struct Prod {
  uint32_t sb, g, pos, head, tail_g, tail_pos, hist;
  __device__ __forceinline__ uint32_t full() const { return sb + SM_BAR + B_FULL + (g & 7) * 8; }
  __device__ __forceinline__ uint32_t slot(uint32_t i) const { return sb + wrap12(pos + i) * SLOT; }
  __device__ __forceinline__ void acquire(uint32_t size) {
#pragma unroll 1
    while (head + size - tail_pos > NSLOT) {
      mbar_wait(sb + SM_BAR + B_EMPTY + (tail_g & 7) * 8, (tail_g >> 3) & 1);
      tail_pos += 2 + ((hist >> (tail_g & 31)) & 1);
      tail_g++;
    }
    hist = (hist & ~(1u << (g & 31))) | ((size - 2) << (g & 31));
  }
  __device__ __forceinline__ void advance(uint32_t size) { g++; head += size; pos = wrap12(pos + size); }
};

__device__ __forceinline__ void wait_flag(const unsigned* p, unsigned target) {
  while ((int)(ld_acquire(p) - target) < 0) {}
  fence_async_all();
}

__device__ __forceinline__ void init_barriers(uint32_t sb, int warp) {
  const uint32_t cnt = warp < 4 ? 1 : warp < 8 ? 16 : warp == 8 ? 4 : warp == 9 ? 1 : 11;
  if (warp < 11) mbar_init(sb + SM_BAR + warp * 16, cnt);
  if (warp < 10) mbar_init(sb + SM_BAR + warp * 16 + 8, cnt);
  asm volatile("fence.mbarrier_init.release.cluster;" ::: "memory");
}

#define TSP(i) do {} while (0)

__global__ void __cluster_dims__(2, 1, 1) __launch_bounds__(384, 1) fused_kernel(const __grid_constant__ Params P) {
  extern __shared__ uint8_t smem_raw[];
  const uint32_t sb = (smem_u32(smem_raw) + 1023u) & ~1023u;
  const int warp = __shfl_sync(~0u, (int)(threadIdx.x >> 5), 0);
  const int lane = threadIdx.x & 31;
  const int rank = blockIdx.x & 1;
  const int cl = blockIdx.x >> 1;
  const int j = cl >> 3;
  const int rb = (cl & 7) * 2 + rank;
  const bool is_s = j < 4, spare = j == 8;
  const int row0 = rb * 128;
  Flags* fl = P.flags;

  if (warp >= 8) {
    unsigned ep0 = 0;
    if (warp == 8) asm volatile("ld.volatile.global.u32 %0, [%1];" : "=r"(ep0) : "l"(&fl->epoch[blockIdx.x]));
    if (lane == 0) {
      if (warp == 8) prefetch_map(spare ? &P.w1b4 : &P.w1b3);
      if (warp == 9) prefetch_map(&P.act_ld);
      init_barriers(sb, warp);
    }
    __syncwarp();
    cluster_arrive();
    if (warp == 10 && lane == 0) {
      prefetch_map(&P.act_st); prefetch_map(&P.wq); prefetch_map(&P.k_ld); prefetch_map(&P.v_ld);
      prefetch_map(is_s ? &P.wo : &P.w2); prefetch_map(&P.x_ld); prefetch_map(&P.out_st);
    }
    __syncwarp();
    cluster_wait();
    asm volatile("setmaxnreg.dec.sync.aligned.u32 24;");
    if (warp == 8) {
      TSP(17);
#define ep1 (ep0 + 1)
      Prod p{sb, 0, 0, 0, 0, 0, 0};
#define LDA(dst, m, bar, c0, c1) tma_ld2(dst, m, bar, c0, c1)
#define LDW1(dst, m, bar, c0, c1, c2) tma_ld3_mc(dst, m, bar, c0, c1, c2)
#define LDW(dst, m, bar, c0, c1, c2) tma_ld3_mc(dst, m, bar, c0, c1, c2)
      {
        const CUtensorMap* mb = spare ? &P.w1b4 : &P.w1b3;
        const uint32_t bytes = spare ? 49152 : 40960;
        const int nt = spare ? 8 : 2;
#pragma unroll 1
        for (int t = 0; t < nt; t++) {
          const int r = spare ? ((cl & 1) * 4 + (t >> 1)) * 2 + rank : rb;
          const int nb0 = spare ? (H_SPARE0 >> 6) + (t & 1) * 4 : j * 6 + t * 3;
          int k = 0;
          if (t == 0) {
#pragma unroll 1
            for (; k < 4; k++) {
              p.acquire(3);
              if (lane == 0) { mbar_expect_tx(p.full(), bytes); LDW1(p.slot(1 + rank), mb, p.full(), 0, k * 64 + rank * 32, nb0); }
              p.advance(3);
            }
            TSP(14);
            asm volatile("" : "+r"(ep0));
            wait_flag(&fl->ln[r][0], ep1 * 64);
            TSP(15);
            if (lane == 0)
              for (int i = 0; i < 4; i++) tma_ld2(sb + i * 3 * SLOT, &P.act_ld, sb + SM_BAR + B_FULL + i * 8, C_XN + i * 64, r * 128);
          } else if (spare && !(t & 1)) {
            wait_flag(&fl->ln[r][0], ep1 * 64);
          }
#pragma unroll 1
          for (; k < 16; k++) {
            p.acquire(3);
            if (lane == 0) {
              mbar_expect_tx(p.full(), bytes);
              LDW1(p.slot(1 + rank), mb, p.full(), 0, k * 64 + rank * 32, nb0);
              tma_ld2(p.slot(0), &P.act_ld, p.full(), C_XN + k * 64, r * 128);
            }
            p.advance(3);
          }
        }
      }
      if (!spare) {
        const int kvrow = (j >> 1) * SK + KV0;
#pragma unroll 1
        for (int t = 0; t < 2; t++) {
          const int nb0 = (4 * j + 2 * t) * 2;
#pragma unroll 1
          for (int k = 0; k < 16; k++) {
            p.acquire(3);
            if (lane == 0) {
              mbar_expect_tx(p.full(), 49152);
              LDW1(p.slot(1 + rank), &P.wq, p.full(), 0, k * 64 + rank * 32, nb0);
              tma_ld2(p.slot(0), &P.act_ld, p.full(), C_XN + k * 64, row0);
            }
            p.advance(3);
          }
#pragma unroll 1
          for (int i = 0; i < 16; i++) {
            const bool is_k = i == 0 || (i < 15 && (i & 1));
            const int ch = (is_k ? ((i + 1) >> 1) : (i == 15 ? 7 : (i >> 1) - 1)) & 3;
            p.acquire(2);
            if (lane == 0) {
              mbar_expect_tx(p.full(), 32768);
              if (is_k) tma_ld2_mc(p.slot(rank), &P.k_ld, p.full(), rank * 64, kvrow + ch * 128);
              else      tma_ld3_mc(p.slot(rank), &P.v_ld, p.full(), 0, kvrow + ch * 128 + rank * 64, 0);
            }
            p.advance(2);
            if (t == 1 && i == 4) {
              if (!is_s) wait_flag(&fl->h[rb][0], ep1 * 64);
              else if (lane < 4) tma_pf2(&P.x_ld, (j & 3) * 256 + lane * 64, row0);
            }
          }
        }
        const int jn = j & 3;
        if (is_s) {
          unsigned ready = 0;
#pragma unroll 1
          for (int i = 0; i < 64; i++) {
            const int hi = i >> 1;
            const int head = 4 * ((hi & 15) >> 1) + (hi & 1) + ((hi >> 4) << 1);
            const int kc = head * 128 + (i & 1) * 64;
            p.acquire(3);
            if (lane == 0) { mbar_expect_tx(p.full(), 49152); LDW(p.slot(1 + rank), &P.wo, p.full(), 0, kc + rank * 32, jn * 4); }
            if (!((ready >> head) & 1)) {
              do { ready = __ballot_sync(~0u, (int)(ld_acquire(&fl->o[rb][lane]) - ep1 * 2) >= 0); } while (!((ready >> head) & 1));
              __syncwarp();
              fence_async_all();
            }
            if (lane == 0) LDA(p.slot(0), &P.act_ld, p.full(), C_O + kc, row0);
            if (i == 56 && lane == 0) prefetch_map(&P.out_st);
            p.advance(3);
            if (i == 3 || i == 7) {
              p.acquire(2);
              if (lane == 0) {
                mbar_expect_tx(p.full(), 32768);
                tma_ld2(p.slot(0), &P.x_ld, p.full(), jn * 256 + (i >> 2) * 128, row0);
                tma_ld2(p.slot(1), &P.x_ld, p.full(), jn * 256 + (i >> 2) * 128 + 64, row0);
              }
              p.advance(2);
            }
          }
          TSP(20);
          wait_flag(&fl->g[rb][jn], ep1 * 4);
          TSP(21);
#pragma unroll 1
          for (int i = 0; i < 2; i++) {
            p.acquire(2);
            if (lane == 0) {
              mbar_expect_tx(p.full(), 32768);
              tma_ld2(p.slot(0), &P.act_ld, p.full(), C_G + jn * 256 + i * 128, row0);
              tma_ld2(p.slot(1), &P.act_ld, p.full(), C_G + jn * 256 + i * 128 + 64, row0);
            }
            p.advance(2);
          }
        } else {
#pragma unroll 1
          for (int k = 0; k < 56; k++) {
            p.acquire(3);
            if (lane == 0) { mbar_expect_tx(p.full(), 49152); LDW(p.slot(1 + rank), &P.w2, p.full(), 0, k * 64 + rank * 32, jn * 4); }
            if (k == H_SPARE0 / 64) wait_flag(&fl->h[rb][16], ep1 * 8);
            if (lane == 0) LDA(p.slot(0), &P.act_ld, p.full(), C_H + k * 64, row0);
            p.advance(3);
          }
        }
      }
      if (lane == 0) { *(volatile unsigned*)&fl->epoch[blockIdx.x] = ep1; mbar_arrive(sb + SM_BAR + B_DONE); }
    } else if (warp < 11) {
      const int wg = warp - 9;
      if (lane == 0) {
        const uint32_t stg = sb + SM_STG + wg * 16384;
        const int nev = spare ? 16 : is_s ? 8 : 10;
#pragma unroll 1
        for (int n = 0; n < nev; n++) {
          int col, row = row0, nbox = 2;
          unsigned* flag;
          if (spare) {
            const int r = ((cl & 1) * 4 + (n >> 2)) * 2 + rank;
            row = r * 128;
            col = C_H + H_SPARE0 + (n & 3) * 128;
            flag = &fl->h[r][16];
          } else if (n < 4) {
            col = C_H + j * H_REG + (n >> 1) * 192 + (n & 1) * 128;
            nbox = 2 - (n & 1);
            flag = &fl->h[rb][0];
          } else if (n < 8) {
            col = C_O + (4 * j + n - 4) * 128;
            flag = &fl->o[rb][4 * j + n - 4];
          } else {
            col = C_G + (j & 3) * 256 + (n - 8) * 128;
            flag = &fl->g[rb][j & 3];
          }
          mbar_wait(sb + SM_BAR + B_SFULL + wg * 8, n & 1);
          if (n == 9 && wg == 0) TSP(20);
          tma_st2(&P.act_st, stg, col, row + wg * 64);
          if (nbox == 2) tma_st2(&P.act_st, stg + 8192, col + 64, row + wg * 64);
          bulk_commit();
          bulk_wait_read0();
          mbar_arrive(sb + SM_BAR + B_SEMPTY + wg * 8);
          if (n == 9 && wg == 0) TSP(21);
          bulk_wait0();
          if (n == 9 && wg == 0) TSP(22);
          fence_async_all();
          red_release(flag, 1);
          if (n == 9 && wg == 0) TSP(23);
        }
        mbar_arrive(sb + SM_BAR + B_DONE);
      }
    } else {
      if (lane == 0) {
        const unsigned long long t0 = gtime();
        while (!mbar_try(sb + SM_BAR + B_DONE, 0)) {
          if (gtime() - t0 > 2000000000ull) __trap();
        }
      }
    }
    __syncwarp();
    cluster_arrive();
    cluster_wait();
  } else {
    const int wg = warp >> 2;
    TS(0);
    if (!spare) {
      const int r = row0 + j * 16 + warp * 2;
      uint32_t v[2][16];
#pragma unroll
      for (int a = 0; a < 2; a++)
#pragma unroll
        for (int i = 0; i < 4; i++)
          *(uint4*)&v[a][4 * i] = __ldg((const uint4*)(P.x + (size_t)(r + a) * DM + i * 256 + lane * 8));
      if (lane == 0) init_barriers(sb, warp);
      __syncwarp();
      cluster_arrive();
      float s[2], q[2];
#pragma unroll
      for (int a = 0; a < 2; a++) {
        float t0 = 0.f, t1 = 0.f;
#pragma unroll
        for (int i = 0; i < 16; i++) { t0 += bf_lo(v[a][i]); t1 += bf_hi(v[a][i]); }
        s[a] = t0 + t1;
      }
#pragma unroll
      for (int o = 16; o; o >>= 1) { s[0] += __shfl_xor_sync(~0u, s[0], o); s[1] += __shfl_xor_sync(~0u, s[1], o); }
#pragma unroll
      for (int a = 0; a < 2; a++) {
        s[a] *= 1.0f / DM;
        float t0 = 0.f, t1 = 0.f;
#pragma unroll
        for (int i = 0; i < 16; i++) {
          const float d0 = bf_lo(v[a][i]) - s[a], d1 = bf_hi(v[a][i]) - s[a];
          t0 = fmaf(d0, d0, t0); t1 = fmaf(d1, d1, t1);
        }
        q[a] = t0 + t1;
      }
#pragma unroll
      for (int o = 16; o; o >>= 1) { q[0] += __shfl_xor_sync(~0u, q[0], o); q[1] += __shfl_xor_sync(~0u, q[1], o); }
#pragma unroll
      for (int a = 0; a < 2; a++) {
        const uint32_t mb2 = pack_bf16(s[a], s[a]);
        const float inv = 1.0f / bf_round(sqrtf(bf_round(bf_round(q[a] * (1.0f / DM)) + 1e-5f)));
#pragma unroll
        for (int i = 0; i < 16; i++) {
          const __nv_bfloat162 d = __hsub2_rn(*(const __nv_bfloat162*)&v[a][i], *(const __nv_bfloat162*)&mb2);
          const uint32_t du = *(const uint32_t*)&d;
          v[a][i] = pack_bf16(bf_lo(du) * inv, bf_hi(du) * inv);
        }
#pragma unroll
        for (int i = 0; i < 4; i++)
          *(uint4*)(P.act + (size_t)(r + a) * ACT_W + C_XN + i * 256 + lane * 8) = *(const uint4*)&v[a][4 * i];
      }
      TS(11);
      fence_async_all();
      TS(12);
      __syncwarp();
      if (lane == 0) red_release(&fl->ln[rb][0], 1);
      TS(13);
    } else {
      if (lane == 0) init_barriers(sb, warp);
      __syncwarp();
      cluster_arrive();
    }
    cluster_wait();
    asm volatile("setmaxnreg.inc.sync.aligned.u32 240;");
    Cons c;
    c.zero = blockIdx.y; c.sb = sb; c.g = 0; c.pos = 0; c.nstg = 0; c.wg = wg; c.lane = lane;
    c.rel = mapa(sb + SM_BAR + B_EMPTY, lane & 1);
    float acc[128];
    TS(1);
    if (spare) {
      uint32_t pend[32];
#pragma unroll
      for (int i = 0; i < 32; i++) pend[i] = 0;
#pragma unroll 1
      for (int t = 0; t < 8; t++) {
        gemm_loop_flush<256, 2>(acc, c, pend, t > 0);
        h_epilogue<2>(acc, c, pend);
      }
      c.stg_acquire();
      stage_boxes<2>(pend, 0, c);
      TS(6);
    } else {
      if (wg == 1) bar_arrive(1, 256);
      {
        uint32_t pend[16];
#pragma unroll
        for (int i = 0; i < 16; i++) pend[i] = 0;
#pragma unroll 1
        for (int t = 0; t < 2; t++) {
          gemm_loop_flush<192, 1>(acc, c, pend, t > 0);
          h_epilogue<1>(acc, c, pend);
          TS(2 + t);
        }
        gemm_loop_flush<256, 1>(acc, c, pend, true);
      }
#pragma unroll 1
      for (int t = 0;; t++) {
        TS(8 + t);
        attn_tile(acc, c, t);
        TS(4 + t);
        if (t == 1) break;
        gemm_loop<256>(acc, c, 16);
      }
      uint32_t rowoff, xr;
      if (is_s) {
        uint32_t xv[64];
#pragma unroll
        for (int i = 0; i < 64; i++) xv[i] = 0;
        gemm_step<256, true>(acc, c);
#pragma unroll 1
        for (int k = 1; k < 64; k++) {
          gemm_step<256, false>(acc, c, (k == 4 || k == 8) ? 2 : 1);
          if (k == 3) load_x<0>(xv, c);
          if (k == 7) load_x<32>(xv, c);
        }
        wg_wait<0>();
        c.release(c.g - 1);
        fence_regs(acc);
        TS(6);
        frag_addr(rowoff, xr);
#pragma unroll
        for (int b = 0; b < 4; b++) {
          if ((b & 1) == 0) c.wait_full(c.g + (b >> 1));
          if (b == 0) TS(22);
          if (b == 2) TS(23);
          const uint32_t gs = sb + wrap12(c.pos + b) * SLOT + wg * 8192;
          uint32_t gv[16];
#pragma unroll
          for (int kb = 0; kb < 4; kb++) ldsm4(gs + rowoff + ((32 * kb) ^ xr), gv[4 * kb], gv[4 * kb + 1], gv[4 * kb + 2], gv[4 * kb + 3]);
#pragma unroll
          for (int i = 0; i < 16; i++) {
            const uint32_t s2 = pack_bf16(acc[32 * b + 2 * i], acc[32 * b + 2 * i + 1]);
            const __nv_bfloat162 pr = __hmul2_rn(*(const __nv_bfloat162*)&s2, *(const __nv_bfloat162*)&gv[i]);
            const __nv_bfloat162 o = __hadd2_rn(*(const __nv_bfloat162*)&xv[16 * b + i], pr);
            gv[i] = *(const uint32_t*)&o;
          }
#pragma unroll
          for (int kb = 0; kb < 4; kb++) stsm4(gs + rowoff + ((32 * kb) ^ xr), gv[4 * kb], gv[4 * kb + 1], gv[4 * kb + 2], gv[4 * kb + 3]);
          if (b & 1) {
            fence_async_smem();
            bar_sync(3 + wg, 128);
            if ((threadIdx.x & 127) == 0) {
              tma_st2(&P.out_st, sb + wrap12(c.pos + b - 1) * SLOT + wg * 8192, (j & 3) * 256 + b * 64 - 64, row0 + wg * 64);
              tma_st2(&P.out_st, gs, (j & 3) * 256 + b * 64, row0 + wg * 64);
              bulk_commit();
            }
          }
        }
        TS(24);
        if ((threadIdx.x & 127) == 0) bulk_wait_read0();
      } else {
        gemm_loop<256>(acc, c, 56);
        TS(6);
        frag_addr(rowoff, xr);
        const uint32_t stg = sb + SM_STG + wg * 16384 + rowoff;
#pragma unroll
        for (int hh = 0; hh < 2; hh++) {
          c.stg_acquire();
#pragma unroll
          for (int kb = 0; kb < 8; kb++)
            stsm4(stg + (kb >> 2) * 8192 + ((32 * (kb & 3)) ^ xr),
                  silu2(pack_bf16(acc[64 * hh + 8 * kb], acc[64 * hh + 8 * kb + 1])), silu2(pack_bf16(acc[64 * hh + 8 * kb + 2], acc[64 * hh + 8 * kb + 3])),
                  silu2(pack_bf16(acc[64 * hh + 8 * kb + 4], acc[64 * hh + 8 * kb + 5])), silu2(pack_bf16(acc[64 * hh + 8 * kb + 6], acc[64 * hh + 8 * kb + 7])));
          c.stg_publish();
          if (hh == 0) TS(22);
        }
      }
    }
    TS(7);
    __syncwarp();
    if (lane == 0) mbar_arrive(sb + SM_BAR + B_DONE);
    cluster_arrive();
    cluster_wait();
  }
}

typedef CUresult (*EncodeFn)(CUtensorMap*, CUtensorMapDataType, cuuint32_t, void*, const cuuint64_t*, const cuuint64_t*,
                             const cuuint32_t*, const cuuint32_t*, CUtensorMapInterleave, CUtensorMapSwizzle,
                             CUtensorMapL2promotion, CUtensorMapFloatOOBfill);

void map2d(EncodeFn enc, CUtensorMap* m, const void* base, uint64_t cols, uint64_t rows, uint32_t box_rows) {
  cuuint64_t dims[2] = {cols, rows};
  cuuint64_t strides[1] = {cols * 2};
  cuuint32_t box[2] = {64, box_rows};
  cuuint32_t es[2] = {1, 1};
  enc(m, CU_TENSOR_MAP_DATA_TYPE_BFLOAT16, 2, (void*)base, dims, strides, box, es, CU_TENSOR_MAP_INTERLEAVE_NONE,
      CU_TENSOR_MAP_SWIZZLE_128B, CU_TENSOR_MAP_L2_PROMOTION_L2_256B, CU_TENSOR_MAP_FLOAT_OOB_FILL_NONE);
}
void map3d(EncodeFn enc, CUtensorMap* m, const void* base, uint64_t cols, uint64_t rows, uint32_t box_rows, uint32_t box_blks) {
  cuuint64_t dims[3] = {64, rows, cols / 64};
  cuuint64_t strides[2] = {cols * 2, 128};
  cuuint32_t box[3] = {64, box_rows, box_blks};
  cuuint32_t es[3] = {1, 1, 1};
  enc(m, CU_TENSOR_MAP_DATA_TYPE_BFLOAT16, 3, (void*)base, dims, strides, box, es, CU_TENSOR_MAP_INTERLEAVE_NONE,
      CU_TENSOR_MAP_SWIZZLE_128B, CU_TENSOR_MAP_L2_PROMOTION_L2_256B, CU_TENSOR_MAP_FLOAT_OOB_FILL_NONE);
}

}

extern "C" void kernel_launch(void* const* d_in, const int* in_sizes, int n_in, void* d_out, int out_size) {
  (void)in_sizes; (void)n_in; (void)out_size;
  static EncodeFn enc = nullptr;
  static void* act = nullptr;
  static void* flags = nullptr;
  if (!enc) {
    void* fn = nullptr;
    cudaDriverEntryPointQueryResult qr;
    cudaGetDriverEntryPoint("cuTensorMapEncodeTiled", &fn, cudaEnableDefault, &qr);
    enc = (EncodeFn)fn;
    cudaGetSymbolAddress(&act, g_act);
    cudaGetSymbolAddress(&flags, g_flags);
    cudaFuncSetAttribute(fused_kernel, cudaFuncAttributeMaxDynamicSharedMemorySize, SMEM_BYTES);
  }
  Params P;
  map2d(enc, &P.act_ld, act, ACT_W, SEQ, 128);
  map2d(enc, &P.act_st, act, ACT_W, SEQ, 64);
  map2d(enc, &P.x_ld, d_in[0], DM, SEQ, 128);
  map2d(enc, &P.out_st, d_out, DM, SEQ, 64);
  map2d(enc, &P.k_ld, d_in[1], 128, 4 * SK, 128);
  map3d(enc, &P.v_ld, d_in[2], 128, 4 * SK, 64, 2);
  map3d(enc, &P.wq, d_in[3], NQ, DM, 32, 4);
  map3d(enc, &P.w1b4, d_in[6], DFF, DM, 32, 4);
  map3d(enc, &P.w1b3, d_in[6], DFF, DM, 32, 3);
  map3d(enc, &P.wo, d_in[4], DM, NQ, 32, 4);
  map3d(enc, &P.w2, d_in[7], DM, DFF, 32, 4);
  P.x = (const __nv_bfloat16*)d_in[0];
  P.act = (__nv_bfloat16*)act;
  P.flags = (Flags*)flags;
  fused_kernel<<<NCLUSTER * 2, 384, SMEM_BYTES>>>(P);
}
```

```cpp
#include <cuda_runtime.h>
#include <cuda_bf16.h>
#include <cuda.h>
#include <stdint.h>

namespace {

constexpr int SEQ    = 2048;
constexpr int DM     = 1024;
constexpr int NQ     = 4096;
constexpr int DFF    = 3584;
constexpr int SK     = 2048;
constexpr int WIN    = 512;
constexpr int KV0    = SK - WIN;
constexpr int C_XN = 0, C_O = 1024, C_H = 5120, C_G = 8704, ACT_W = 9728;

constexpr int H_REG = 384, H_SPARE0 = 8 * H_REG;
static_assert(H_SPARE0 + 512 == DFF, "H split");

constexpr int NSLOT = 12, SLOT = 16384, NBAR = 8;
constexpr int SM_STG = NSLOT * SLOT;
constexpr int SM_BAR = SM_STG + 2 * 16384;
constexpr int SMEM_BYTES = SM_BAR + 256 + 1024;
constexpr int B_FULL = 0, B_EMPTY = 64, B_SFULL = 128, B_SEMPTY = 144, B_DONE = 160;

constexpr int NCLUSTER = 66;

struct Flags {
  unsigned ln[16][32];
  unsigned h[16][32];
  unsigned o[16][32];
  unsigned g[16][32];
  unsigned epoch[160];
};
__device__ __nv_bfloat16 g_act[(size_t)SEQ * ACT_W];
__device__ Flags g_flags;

struct Params {
  CUtensorMap act_ld, act_st, x_ld, out_st, k_ld, v_ld, wq, w1b4, w1b3, wo, w2;
  const __nv_bfloat16* x;
  __nv_bfloat16* act;
  Flags* flags;
};

__device__ __forceinline__ uint32_t smem_u32(const void* p) { return (uint32_t)__cvta_generic_to_shared(p); }
__device__ __forceinline__ void mbar_init(uint32_t bar, uint32_t cnt) {
  asm volatile("mbarrier.init.shared::cta.b64 [%0], %1;" ::"r"(bar), "r"(cnt) : "memory");
}
__device__ __forceinline__ bool mbar_try(uint32_t bar, uint32_t parity) {
  uint32_t ok;
  asm volatile("{\n.reg .pred p;\nmbarrier.try_wait.parity.shared::cta.b64 p, [%1], %2;\nselp.u32 %0, 1, 0, p;\n}\n"
               : "=r"(ok) : "r"(bar), "r"(parity) : "memory");
  return ok;
}
__device__ __forceinline__ void mbar_wait(uint32_t bar, uint32_t parity) {
  asm volatile("{\n.reg .pred p;\nWAIT_%=:\nmbarrier.try_wait.parity.shared::cta.b64 p, [%0], %1;\n@p bra DONE_%=;\nbra WAIT_%=;\nDONE_%=:\n}\n"
               ::"r"(bar), "r"(parity) : "memory");
}
__device__ __forceinline__ void mbar_arrive(uint32_t bar) {
  asm volatile("mbarrier.arrive.shared::cta.b64 _, [%0];" ::"r"(bar) : "memory");
}
__device__ __forceinline__ void mbar_arrive_cluster(uint32_t cluster_addr) {
  asm volatile("mbarrier.arrive.shared::cluster.b64 _, [%0];" ::"r"(cluster_addr) : "memory");
}
__device__ __forceinline__ void mbar_expect_tx(uint32_t bar, uint32_t bytes) {
  asm volatile("mbarrier.arrive.expect_tx.shared::cta.b64 _, [%0], %1;" ::"r"(bar), "r"(bytes) : "memory");
}
__device__ __forceinline__ uint32_t mapa(uint32_t addr, uint32_t rank) {
  uint32_t r;
  asm("mapa.shared::cluster.u32 %0, %1, %2;" : "=r"(r) : "r"(addr), "r"(rank));
  return r;
}
__device__ __forceinline__ void cluster_arrive() { asm volatile("barrier.cluster.arrive.relaxed.aligned;" ::: "memory"); }
__device__ __forceinline__ void cluster_wait() { asm volatile("barrier.cluster.wait.acquire.aligned;" ::: "memory"); }
__device__ __forceinline__ void bar_sync(int id, int n) { asm volatile("bar.sync %0, %1;" ::"r"(id), "r"(n) : "memory"); }
__device__ __forceinline__ void bar_arrive(int id, int n) { asm volatile("bar.arrive %0, %1;" ::"r"(id), "r"(n) : "memory"); }
__device__ __forceinline__ void fence_async_smem() { asm volatile("fence.proxy.async.shared::cta;" ::: "memory"); }
__device__ __forceinline__ void fence_async_all() { asm volatile("fence.proxy.async.global;" ::: "memory"); }

__device__ __forceinline__ void tma_ld2(uint32_t dst, const CUtensorMap* m, uint32_t bar, int c0, int c1) {
  asm volatile("cp.async.bulk.tensor.2d.shared::cluster.global.mbarrier::complete_tx::bytes [%0], [%1, {%3, %4}], [%2];"
               ::"r"(dst), "l"(m), "r"(bar), "r"(c0), "r"(c1) : "memory");
}
__device__ __forceinline__ void tma_ld2_mc(uint32_t dst, const CUtensorMap* m, uint32_t bar, int c0, int c1) {
  asm volatile("cp.async.bulk.tensor.2d.shared::cluster.global.mbarrier::complete_tx::bytes.multicast::cluster [%0], [%1, {%3, %4}], [%2], %5;"
               ::"r"(dst), "l"(m), "r"(bar), "r"(c0), "r"(c1), "h"((uint16_t)3) : "memory");
}
__device__ __forceinline__ void tma_ld3_mc(uint32_t dst, const CUtensorMap* m, uint32_t bar, int c0, int c1, int c2) {
  asm volatile("cp.async.bulk.tensor.3d.shared::cluster.global.mbarrier::complete_tx::bytes.multicast::cluster [%0], [%1, {%3, %4, %5}], [%2], %6;"
               ::"r"(dst), "l"(m), "r"(bar), "r"(c0), "r"(c1), "r"(c2), "h"((uint16_t)3) : "memory");
}
__device__ __forceinline__ void tma_ld3_mc_hint(uint32_t dst, const CUtensorMap* m, uint32_t bar, int c0, int c1, int c2, uint64_t pol) {
  asm volatile("cp.async.bulk.tensor.3d.shared::cluster.global.mbarrier::complete_tx::bytes.multicast::cluster.L2::cache_hint [%0], [%1, {%3, %4, %5}], [%2], %6, %7;"
               ::"r"(dst), "l"(m), "r"(bar), "r"(c0), "r"(c1), "r"(c2), "h"((uint16_t)3), "l"(pol) : "memory");
}
__device__ __forceinline__ void tma_ld2_hint(uint32_t dst, const CUtensorMap* m, uint32_t bar, int c0, int c1, uint64_t pol) {
  asm volatile("cp.async.bulk.tensor.2d.shared::cluster.global.mbarrier::complete_tx::bytes.L2::cache_hint [%0], [%1, {%3, %4}], [%2], %5;"
               ::"r"(dst), "l"(m), "r"(bar), "r"(c0), "r"(c1), "l"(pol) : "memory");
}
__device__ __forceinline__ void tma_st2_hint(const CUtensorMap* m, uint32_t src, int c0, int c1, uint64_t pol) {
  asm volatile("cp.async.bulk.tensor.2d.global.shared::cta.bulk_group.L2::cache_hint [%0, {%2, %3}], [%1], %4;"
               ::"l"(m), "r"(src), "r"(c0), "r"(c1), "l"(pol) : "memory");
}
#define POL_FIRST 0x12F0000000000000ull
__device__ __forceinline__ uint64_t policy_evict_first() {
  uint64_t p;
  asm volatile("createpolicy.fractional.L2::evict_first.b64 %0, 1.0;" : "=l"(p));
  return p;
}
__device__ __forceinline__ void tma_st2(const CUtensorMap* m, uint32_t src, int c0, int c1) {
  asm volatile("cp.async.bulk.tensor.2d.global.shared::cta.bulk_group [%0, {%2, %3}], [%1];"
               ::"l"(m), "r"(src), "r"(c0), "r"(c1) : "memory");
}
__device__ __forceinline__ void tma_pf2(const CUtensorMap* m, int c0, int c1) {
  asm volatile("cp.async.bulk.prefetch.tensor.2d.L2.global [%0, {%1, %2}];" ::"l"(m), "r"(c0), "r"(c1) : "memory");
}
__device__ __forceinline__ void bulk_commit() { asm volatile("cp.async.bulk.commit_group;" ::: "memory"); }
__device__ __forceinline__ void bulk_wait_read0() { asm volatile("cp.async.bulk.wait_group.read 0;" ::: "memory"); }
__device__ __forceinline__ void bulk_wait0() { asm volatile("cp.async.bulk.wait_group 0;" ::: "memory"); }
__device__ __forceinline__ void prefetch_map(const CUtensorMap* m) {
  asm volatile("prefetch.tensormap [%0];" ::"l"(m) : "memory");
}
__device__ __forceinline__ unsigned ld_acquire(const unsigned* p) {
  unsigned v;
  asm volatile("ld.acquire.gpu.global.u32 %0, [%1];" : "=r"(v) : "l"(p) : "memory");
  return v;
}
__device__ __forceinline__ void red_release(unsigned* p, unsigned v) {
  asm volatile("red.release.gpu.global.add.u32 [%0], %1;" ::"l"(p), "r"(v) : "memory");
}
__device__ __forceinline__ void wg_fence() { asm volatile("wgmma.fence.sync.aligned;" ::: "memory"); }
__device__ __forceinline__ void wg_commit() { asm volatile("wgmma.commit_group.sync.aligned;" ::: "memory"); }
template <int N> __device__ __forceinline__ void wg_wait() { asm volatile("wgmma.wait_group.sync.aligned %0;" ::"n"(N) : "memory"); }
template <int N> __device__ __forceinline__ void fence_regs(float (&d)[N]) {
#pragma unroll
  for (int i = 0; i < N; i++) asm volatile("" : "+f"(d[i])::"memory");
}
template <int N> __device__ __forceinline__ void fence_regs(uint32_t (&d)[N]) {
#pragma unroll
  for (int i = 0; i < N; i++) asm volatile("" : "+r"(d[i])::"memory");
}
__device__ __forceinline__ uint64_t mkdesc(uint32_t addr, uint32_t lbo, uint32_t sbo) {
  return (uint64_t)((addr & 0x3FFFF) >> 4) | ((uint64_t)(lbo >> 4) << 16) | ((uint64_t)(sbo >> 4) << 32) | (1ull << 62);
}
__device__ __forceinline__ uint32_t pack_bf16(float lo, float hi) {
  uint32_t r;
  asm("cvt.rn.bf16x2.f32 %0, %1, %2;" : "=r"(r) : "f"(hi), "f"(lo));
  return r;
}
__device__ __forceinline__ uint32_t pack_bf16_relu(float lo, float hi) {
  uint32_t r;
  asm("cvt.rn.relu.bf16x2.f32 %0, %1, %2;" : "=r"(r) : "f"(hi), "f"(lo));
  return r;
}
__device__ __forceinline__ float bf_lo(uint32_t v) { return __uint_as_float(v << 16); }
__device__ __forceinline__ float bf_hi(uint32_t v) { return __uint_as_float(v & 0xFFFF0000u); }
__device__ __forceinline__ float bf_round(float v) { return __bfloat162float(__float2bfloat16_rn(v)); }
__device__ __forceinline__ float ex2(float x) {
  float r;
  asm("ex2.approx.ftz.f32 %0, %1;" : "=f"(r) : "f"(x));
  return r;
}
__device__ __forceinline__ float rcp(float x) {
  float r;
  asm("rcp.approx.ftz.f32 %0, %1;" : "=f"(r) : "f"(x));
  return r;
}
__device__ __forceinline__ uint32_t tid_x() {
  uint32_t t;
  asm volatile("mov.u32 %0, %%tid.x;" : "=r"(t));
  return t;
}
__device__ __forceinline__ void stsm4(uint32_t addr, uint32_t r0, uint32_t r1, uint32_t r2, uint32_t r3) {
  asm volatile("stmatrix.sync.aligned.m8n8.x4.shared.b16 [%0], {%1, %2, %3, %4};" ::"r"(addr), "r"(r0), "r"(r1), "r"(r2), "r"(r3) : "memory");
}
__device__ __forceinline__ void ldsm4(uint32_t addr, uint32_t& r0, uint32_t& r1, uint32_t& r2, uint32_t& r3) {
  asm volatile("ldmatrix.sync.aligned.m8n8.x4.shared.b16 {%0, %1, %2, %3}, [%4];" : "=r"(r0), "=r"(r1), "=r"(r2), "=r"(r3) : "r"(addr) : "memory");
}
__device__ __forceinline__ void sts128(uint32_t addr, uint32_t r0, uint32_t r1, uint32_t r2, uint32_t r3) {
  asm volatile("st.shared.v4.b32 [%0], {%1, %2, %3, %4};" ::"r"(addr), "r"(r0), "r"(r1), "r"(r2), "r"(r3) : "memory");
}
__device__ __forceinline__ void lds128(uint32_t addr, uint32_t& r0, uint32_t& r1, uint32_t& r2, uint32_t& r3) {
  asm volatile("ld.shared.v4.b32 {%0, %1, %2, %3}, [%4];" : "=r"(r0), "=r"(r1), "=r"(r2), "=r"(r3) : "r"(addr) : "memory");
}
__device__ __forceinline__ unsigned long long gtime() {
  unsigned long long t;
  asm volatile("mov.u64 %0, %globaltimer;" : "=l"(t));
  return t;
}

__device__ __forceinline__ void wgmma_ss_n256_tb(float (&d)[128], uint64_t da, uint64_t db, uint32_t sc) {
  asm volatile("{\n.reg .pred p;\nsetp.ne.b32 p, %130, 0;\n"
    "wgmma.mma_async.sync.aligned.m64n256k16.f32.bf16.bf16 "
    "{%0, %1, %2, %3, %4, %5, %6, %7, %8, %9, %10, %11, %12, %13, %14, %15, %16, %17, %18, %19, %20, %21, %22, %23, %24, %25, %26, %27, %28, %29, %30, %31, %32, %33, %34, %35, %36, %37, %38, %39, %40, %41, %42, %43, %44, %45, %46, %47, %48, %49, %50, %51, %52, %53, %54, %55, %56, %57, %58, %59, %60, %61, %62, %63, %64, %65, %66, %67, %68, %69, %70, %71, %72, %73, %74, %75, %76, %77, %78, %79, %80, %81, %82, %83, %84, %85, %86, %87, %88, %89, %90, %91, %92, %93, %94, %95, %96, %97, %98, %99, %100, %101, %102, %103, %104, %105, %106, %107, %108, %109, %110, %111, %112, %113, %114, %115, %116, %117, %118, %119, %120, %121, %122, %123, %124, %125, %126, %127}, %128, %129, p, 1, 1, 0, 1;\n}\n"
    : "+f"(d[0]), "+f"(d[1]), "+f"(d[2]), "+f"(d[3]), "+f"(d[4]), "+f"(d[5]), "+f"(d[6]), "+f"(d[7]), "+f"(d[8]), "+f"(d[9]), "+f"(d[10]), "+f"(d[11]), "+f"(d[12]), "+f"(d[13]), "+f"(d[14]), "+f"(d[15]), "+f"(d[16]), "+f"(d[17]), "+f"(d[18]), "+f"(d[19]), "+f"(d[20]), "+f"(d[21]), "+f"(d[22]), "+f"(d[23]), "+f"(d[24]), "+f"(d[25]), "+f"(d[26]), "+f"(d[27]), "+f"(d[28]), "+f"(d[29]), "+f"(d[30]), "+f"(d[31]), "+f"(d[32]), "+f"(d[33]), "+f"(d[34]), "+f"(d[35]), "+f"(d[36]), "+f"(d[37]), "+f"(d[38]), "+f"(d[39]), "+f"(d[40]), "+f"(d[41]), "+f"(d[42]), "+f"(d[43]), "+f"(d[44]), "+f"(d[45]), "+f"(d[46]), "+f"(d[47]), "+f"(d[48]), "+f"(d[49]), "+f"(d[50]), "+f"(d[51]), "+f"(d[52]), "+f"(d[53]), "+f"(d[54]), "+f"(d[55]), "+f"(d[56]), "+f"(d[57]), "+f"(d[58]), "+f"(d[59]), "+f"(d[60]), "+f"(d[61]), "+f"(d[62]), "+f"(d[63]), "+f"(d[64]), "+f"(d[65]), "+f"(d[66]), "+f"(d[67]), "+f"(d[68]), "+f"(d[69]), "+f"(d[70]), "+f"(d[71]), "+f"(d[72]), "+f"(d[73]), "+f"(d[74]), "+f"(d[75]), "+f"(d[76]), "+f"(d[77]), "+f"(d[78]), "+f"(d[79]), "+f"(d[80]), "+f"(d[81]), "+f"(d[82]), "+f"(d[83]), "+f"(d[84]), "+f"(d[85]), "+f"(d[86]), "+f"(d[87]), "+f"(d[88]), "+f"(d[89]), "+f"(d[90]), "+f"(d[91]), "+f"(d[92]), "+f"(d[93]), "+f"(d[94]), "+f"(d[95]), "+f"(d[96]), "+f"(d[97]), "+f"(d[98]), "+f"(d[99]), "+f"(d[100]), "+f"(d[101]), "+f"(d[102]), "+f"(d[103]), "+f"(d[104]), "+f"(d[105]), "+f"(d[106]), "+f"(d[107]), "+f"(d[108]), "+f"(d[109]), "+f"(d[110]), "+f"(d[111]), "+f"(d[112]), "+f"(d[113]), "+f"(d[114]), "+f"(d[115]), "+f"(d[116]), "+f"(d[117]), "+f"(d[118]), "+f"(d[119]), "+f"(d[120]), "+f"(d[121]), "+f"(d[122]), "+f"(d[123]), "+f"(d[124]), "+f"(d[125]), "+f"(d[126]), "+f"(d[127])
    : "l"(da), "l"(db), "r"(sc));
}
__device__ __forceinline__ void wgmma_ss_n192_tb(float (&d)[128], uint64_t da, uint64_t db, uint32_t sc) {
  asm volatile("{\n.reg .pred p;\nsetp.ne.b32 p, %98, 0;\n"
    "wgmma.mma_async.sync.aligned.m64n192k16.f32.bf16.bf16 "
    "{%0, %1, %2, %3, %4, %5, %6, %7, %8, %9, %10, %11, %12, %13, %14, %15, %16, %17, %18, %19, %20, %21, %22, %23, %24, %25, %26, %27, %28, %29, %30, %31, %32, %33, %34, %35, %36, %37, %38, %39, %40, %41, %42, %43, %44, %45, %46, %47, %48, %49, %50, %51, %52, %53, %54, %55, %56, %57, %58, %59, %60, %61, %62, %63, %64, %65, %66, %67, %68, %69, %70, %71, %72, %73, %74, %75, %76, %77, %78, %79, %80, %81, %82, %83, %84, %85, %86, %87, %88, %89, %90, %91, %92, %93, %94, %95}, %96, %97, p, 1, 1, 0, 1;\n}\n"
    : "+f"(d[0]), "+f"(d[1]), "+f"(d[2]), "+f"(d[3]), "+f"(d[4]), "+f"(d[5]), "+f"(d[6]), "+f"(d[7]), "+f"(d[8]), "+f"(d[9]), "+f"(d[10]), "+f"(d[11]), "+f"(d[12]), "+f"(d[13]), "+f"(d[14]), "+f"(d[15]), "+f"(d[16]), "+f"(d[17]), "+f"(d[18]), "+f"(d[19]), "+f"(d[20]), "+f"(d[21]), "+f"(d[22]), "+f"(d[23]), "+f"(d[24]), "+f"(d[25]), "+f"(d[26]), "+f"(d[27]), "+f"(d[28]), "+f"(d[29]), "+f"(d[30]), "+f"(d[31]), "+f"(d[32]), "+f"(d[33]), "+f"(d[34]), "+f"(d[35]), "+f"(d[36]), "+f"(d[37]), "+f"(d[38]), "+f"(d[39]), "+f"(d[40]), "+f"(d[41]), "+f"(d[42]), "+f"(d[43]), "+f"(d[44]), "+f"(d[45]), "+f"(d[46]), "+f"(d[47]), "+f"(d[48]), "+f"(d[49]), "+f"(d[50]), "+f"(d[51]), "+f"(d[52]), "+f"(d[53]), "+f"(d[54]), "+f"(d[55]), "+f"(d[56]), "+f"(d[57]), "+f"(d[58]), "+f"(d[59]), "+f"(d[60]), "+f"(d[61]), "+f"(d[62]), "+f"(d[63]), "+f"(d[64]), "+f"(d[65]), "+f"(d[66]), "+f"(d[67]), "+f"(d[68]), "+f"(d[69]), "+f"(d[70]), "+f"(d[71]), "+f"(d[72]), "+f"(d[73]), "+f"(d[74]), "+f"(d[75]), "+f"(d[76]), "+f"(d[77]), "+f"(d[78]), "+f"(d[79]), "+f"(d[80]), "+f"(d[81]), "+f"(d[82]), "+f"(d[83]), "+f"(d[84]), "+f"(d[85]), "+f"(d[86]), "+f"(d[87]), "+f"(d[88]), "+f"(d[89]), "+f"(d[90]), "+f"(d[91]), "+f"(d[92]), "+f"(d[93]), "+f"(d[94]), "+f"(d[95])
    : "l"(da), "l"(db), "r"(sc));
}
__device__ __forceinline__ void wgmma_rs_n128(float (&d)[64], uint32_t a0, uint32_t a1, uint32_t a2, uint32_t a3, uint64_t db, uint32_t sc) {
  asm volatile("{\n.reg .pred p;\nsetp.ne.b32 p, %69, 0;\n"
    "wgmma.mma_async.sync.aligned.m64n128k16.f32.bf16.bf16 "
    "{%0, %1, %2, %3, %4, %5, %6, %7, %8, %9, %10, %11, %12, %13, %14, %15, %16, %17, %18, %19, %20, %21, %22, %23, %24, %25, %26, %27, %28, %29, %30, %31, %32, %33, %34, %35, %36, %37, %38, %39, %40, %41, %42, %43, %44, %45, %46, %47, %48, %49, %50, %51, %52, %53, %54, %55, %56, %57, %58, %59, %60, %61, %62, %63}, {%64, %65, %66, %67}, %68, p, 1, 1, 0;\n}\n"
    : "+f"(d[0]), "+f"(d[1]), "+f"(d[2]), "+f"(d[3]), "+f"(d[4]), "+f"(d[5]), "+f"(d[6]), "+f"(d[7]), "+f"(d[8]), "+f"(d[9]), "+f"(d[10]), "+f"(d[11]), "+f"(d[12]), "+f"(d[13]), "+f"(d[14]), "+f"(d[15]), "+f"(d[16]), "+f"(d[17]), "+f"(d[18]), "+f"(d[19]), "+f"(d[20]), "+f"(d[21]), "+f"(d[22]), "+f"(d[23]), "+f"(d[24]), "+f"(d[25]), "+f"(d[26]), "+f"(d[27]), "+f"(d[28]), "+f"(d[29]), "+f"(d[30]), "+f"(d[31]), "+f"(d[32]), "+f"(d[33]), "+f"(d[34]), "+f"(d[35]), "+f"(d[36]), "+f"(d[37]), "+f"(d[38]), "+f"(d[39]), "+f"(d[40]), "+f"(d[41]), "+f"(d[42]), "+f"(d[43]), "+f"(d[44]), "+f"(d[45]), "+f"(d[46]), "+f"(d[47]), "+f"(d[48]), "+f"(d[49]), "+f"(d[50]), "+f"(d[51]), "+f"(d[52]), "+f"(d[53]), "+f"(d[54]), "+f"(d[55]), "+f"(d[56]), "+f"(d[57]), "+f"(d[58]), "+f"(d[59]), "+f"(d[60]), "+f"(d[61]), "+f"(d[62]), "+f"(d[63])
    : "r"(a0), "r"(a1), "r"(a2), "r"(a3), "l"(db), "r"(sc));
}
__device__ __forceinline__ void wgmma_rs_n128_tb(float (&d)[64], uint32_t a0, uint32_t a1, uint32_t a2, uint32_t a3, uint64_t db, uint32_t sc) {
  asm volatile("{\n.reg .pred p;\nsetp.ne.b32 p, %69, 0;\n"
    "wgmma.mma_async.sync.aligned.m64n128k16.f32.bf16.bf16 "
    "{%0, %1, %2, %3, %4, %5, %6, %7, %8, %9, %10, %11, %12, %13, %14, %15, %16, %17, %18, %19, %20, %21, %22, %23, %24, %25, %26, %27, %28, %29, %30, %31, %32, %33, %34, %35, %36, %37, %38, %39, %40, %41, %42, %43, %44, %45, %46, %47, %48, %49, %50, %51, %52, %53, %54, %55, %56, %57, %58, %59, %60, %61, %62, %63}, {%64, %65, %66, %67}, %68, p, 1, 1, 1;\n}\n"
    : "+f"(d[0]), "+f"(d[1]), "+f"(d[2]), "+f"(d[3]), "+f"(d[4]), "+f"(d[5]), "+f"(d[6]), "+f"(d[7]), "+f"(d[8]), "+f"(d[9]), "+f"(d[10]), "+f"(d[11]), "+f"(d[12]), "+f"(d[13]), "+f"(d[14]), "+f"(d[15]), "+f"(d[16]), "+f"(d[17]), "+f"(d[18]), "+f"(d[19]), "+f"(d[20]), "+f"(d[21]), "+f"(d[22]), "+f"(d[23]), "+f"(d[24]), "+f"(d[25]), "+f"(d[26]), "+f"(d[27]), "+f"(d[28]), "+f"(d[29]), "+f"(d[30]), "+f"(d[31]), "+f"(d[32]), "+f"(d[33]), "+f"(d[34]), "+f"(d[35]), "+f"(d[36]), "+f"(d[37]), "+f"(d[38]), "+f"(d[39]), "+f"(d[40]), "+f"(d[41]), "+f"(d[42]), "+f"(d[43]), "+f"(d[44]), "+f"(d[45]), "+f"(d[46]), "+f"(d[47]), "+f"(d[48]), "+f"(d[49]), "+f"(d[50]), "+f"(d[51]), "+f"(d[52]), "+f"(d[53]), "+f"(d[54]), "+f"(d[55]), "+f"(d[56]), "+f"(d[57]), "+f"(d[58]), "+f"(d[59]), "+f"(d[60]), "+f"(d[61]), "+f"(d[62]), "+f"(d[63])
    : "r"(a0), "r"(a1), "r"(a2), "r"(a3), "l"(db), "r"(sc));
}

#define TS(i) do {} while (0)
#define TR(j, i) do {} while (0)
#define TSS(i, c) do {} while (0)

__device__ __forceinline__ uint32_t wrap12(uint32_t p) { return p >= NSLOT ? p - NSLOT : p; }

#define ONCE(c) _Pragma("unroll 1") for (uint32_t once_ = 0; once_ <= (c).zero; once_++)
struct Cons {
  uint32_t sb;
  uint32_t g, pos;
  uint32_t rel;
  uint32_t nstg;
  uint32_t zero;
  int wg, lane;
  __device__ __forceinline__ void wait_full(uint32_t gg) const { mbar_wait(sb + SM_BAR + B_FULL + (gg & 7) * 8, (gg >> 3) & 1); }
  __device__ __forceinline__ void release(uint32_t gg) const { if (lane < 2) mbar_arrive_cluster(rel + (gg & 7) * 8); }
  __device__ __forceinline__ void stg_acquire() { mbar_wait(sb + SM_BAR + B_SEMPTY + wg * 8, (nstg & 1) ^ 1); nstg++; }
  __device__ __forceinline__ void stg_publish() const {
    fence_async_smem();
    __syncwarp();
    if (lane == 0) mbar_arrive(sb + SM_BAR + B_SFULL + wg * 8);
  }
};

__device__ __forceinline__ void frag_addr(uint32_t& rowoff, uint32_t& xr) {
  const uint32_t t = tid_x();
  rowoff = ((t >> 5) & 3) * 2048 + (t & 15) * 128;
  xr = (((t >> 4) & 1) ^ (t & 7)) << 4;
}
template <int NB, int NR>
__device__ __forceinline__ void stage_boxes(const uint32_t (&r)[NR], int r0, const Cons& c) {
  uint32_t rowoff, xr;
  frag_addr(rowoff, xr);
  const uint32_t stg = c.sb + SM_STG + c.wg * 16384 + rowoff;
#pragma unroll
  for (int b = 0; b < NB; b++)
#pragma unroll
    for (int kb = 0; kb < 4; kb++)
      stsm4(stg + b * 8192 + ((32 * kb) ^ xr), r[r0 + b * 16 + kb * 4], r[r0 + b * 16 + kb * 4 + 1], r[r0 + b * 16 + kb * 4 + 2], r[r0 + b * 16 + kb * 4 + 3]);
  c.stg_publish();
}

template <int N, bool FIRST>
__device__ __forceinline__ void gemm_step(float (&acc)[128], Cons& c) {
  const uint32_t p1 = wrap12(c.pos + 1), p2 = wrap12(c.pos + 2);
  const uint64_t da = mkdesc(c.sb + c.wg * 8192 + c.pos * SLOT, 16, 1024);
  const uint64_t b0 = mkdesc(c.sb + p1 * SLOT, 4096, 1024);
  const uint64_t b1 = mkdesc(c.sb + p2 * SLOT, 4096, 1024);
  c.wait_full(c.g);
  wg_fence();
  if (N == 256) {
    wgmma_ss_n256_tb(acc, da, b0, FIRST ? 0 : 1);
    wgmma_ss_n256_tb(acc, da + 2, b0 + 128, 1);
    wgmma_ss_n256_tb(acc, da + 4, b1, 1);
    wgmma_ss_n256_tb(acc, da + 6, b1 + 128, 1);
  } else {
    wgmma_ss_n192_tb(acc, da, b0, FIRST ? 0 : 1);
    wgmma_ss_n192_tb(acc, da + 2, b0 + 128, 1);
    wgmma_ss_n192_tb(acc, da + 4, b1, 1);
    wgmma_ss_n192_tb(acc, da + 6, b1 + 128, 1);
  }
  wg_commit();
  if (!FIRST) {
    wg_wait<1>();
    c.release(c.g - 1);
  }
  c.g++;
  c.pos = wrap12(p2 + 1);
}

template <int N>
__device__ __forceinline__ void gemm_loop(float (&acc)[128], Cons& c, int nk) {
  gemm_step<N, true>(acc, c);
#pragma unroll 1
  for (int k = 1; k < nk; k++) gemm_step<N, false>(acc, c);
  wg_wait<0>();
  c.release(c.g - 1);
  fence_regs(acc);
}
template <int N, int NB>
__device__ __forceinline__ void gemm_loop_flush(float (&acc)[128], Cons& c, const uint32_t (&pend)[NB * 16], bool flush) {
  gemm_step<N, true>(acc, c);
#pragma unroll 1
  for (int k = 1; k < 16; k++) {
    gemm_step<N, false>(acc, c);
    if (k == 3 && flush) {
      c.stg_acquire();
      stage_boxes<NB>(pend, 0, c);
    }
  }
  wg_wait<0>();
  c.release(c.g - 1);
  fence_regs(acc);
}
template <int NB>
__device__ __forceinline__ void h_epilogue(const float (&acc)[128], Cons& c, uint32_t (&pend)[NB * 16]) {
  uint32_t r[32];
#pragma unroll
  for (int i = 0; i < 32; i++) r[i] = pack_bf16_relu(acc[2 * i], acc[2 * i + 1]);
  c.stg_acquire();
  stage_boxes<2>(r, 0, c);
#pragma unroll
  for (int i = 0; i < NB * 16; i++) pend[i] = pack_bf16_relu(acc[64 + 2 * i], acc[65 + 2 * i]);
}

__device__ __forceinline__ uint32_t silu2(uint32_t f2) {
  const float a = bf_lo(f2), b = bf_hi(f2);
  const float ta = ex2(-1.4426950408889634f * fabsf(a)), tb = ex2(-1.4426950408889634f * fabsf(b));
  const float da = 1.0f + ta, db = 1.0f + tb;
  const float r = rcp(da * db);
  return pack_bf16((a >= 0.f ? a : a * ta) * (r * db), (b >= 0.f ? b : b * tb) * (r * da));
}

constexpr float SM_C = 0.08838834764831845f * 1.4426950408889634f;

__device__ __forceinline__ void row_max2(const float (&S)[64], float& n0, float& n1) {
  float x[4], y[4];
#pragma unroll
  for (int i = 0; i < 4; i++) { x[i] = fmaxf(S[4 * i], S[4 * i + 1]); y[i] = fmaxf(S[4 * i + 2], S[4 * i + 3]); }
#pragma unroll
  for (int i = 4; i < 16; i++) {
    x[i & 3] = fmaxf(x[i & 3], fmaxf(S[4 * i], S[4 * i + 1]));
    y[i & 3] = fmaxf(y[i & 3], fmaxf(S[4 * i + 2], S[4 * i + 3]));
  }
  n0 = fmaxf(fmaxf(x[0], x[1]), fmaxf(x[2], x[3]));
  n1 = fmaxf(fmaxf(y[0], y[1]), fmaxf(y[2], y[3]));
  n0 = fmaxf(n0, __shfl_xor_sync(~0u, n0, 1));
  n1 = fmaxf(n1, __shfl_xor_sync(~0u, n1, 1));
  n0 = fmaxf(n0, __shfl_xor_sync(~0u, n0, 2));
  n1 = fmaxf(n1, __shfl_xor_sync(~0u, n1, 2));
}
__device__ __forceinline__ void to_exponent(float (&S)[64], float cc0, float cc1) {
#pragma unroll
  for (int i = 0; i < 16; i++) {
    S[4 * i] = fmaf(S[4 * i], SM_C, cc0); S[4 * i + 1] = fmaf(S[4 * i + 1], SM_C, cc0);
    S[4 * i + 2] = fmaf(S[4 * i + 2], SM_C, cc1); S[4 * i + 3] = fmaf(S[4 * i + 3], SM_C, cc1);
  }
}
__device__ __forceinline__ void scale_o(float (&O)[64], float f0, float f1) {
#pragma unroll
  for (int i = 0; i < 16; i++) { O[4 * i] *= f0; O[4 * i + 1] *= f0; O[4 * i + 2] *= f1; O[4 * i + 3] *= f1; }
}
template <int G0>
__device__ __forceinline__ void exp_pack(const float (&S)[64], uint32_t (&p)[32], float (&a)[4]) {
#pragma unroll
  for (int i = G0; i < 16; i++) {
    const float e0 = ex2(S[4 * i]), e1 = ex2(S[4 * i + 1]), e2 = ex2(S[4 * i + 2]), e3 = ex2(S[4 * i + 3]);
    a[0] += e0; a[1] += e1; a[2] += e2; a[3] += e3;
    p[2 * i] = pack_bf16(e0, e1);
    p[2 * i + 1] = pack_bf16(e2, e3);
  }
}
#define EARLY 4
__device__ __forceinline__ void softmax_early(float (&S)[64], float cc0, float cc1, float (&a)[4], uint32_t (&pe)[2 * EARLY + 1], const Cons& c) {
  a[0] = a[1] = a[2] = a[3] = 0.f;
  ONCE(c) {
    to_exponent(S, cc0, cc1);
#pragma unroll
    for (int i = 0; i < EARLY; i++) {
      const float e0 = ex2(S[4 * i]), e1 = ex2(S[4 * i + 1]), e2 = ex2(S[4 * i + 2]), e3 = ex2(S[4 * i + 3]);
      a[0] += e0; a[1] += e1; a[2] += e2; a[3] += e3;
      pe[2 * i] = pack_bf16(e0, e1);
      pe[2 * i + 1] = pack_bf16(e2, e3);
    }
  }
}
__device__ __forceinline__ void softmax_late(float (&S)[64], uint32_t (&p)[32], float (&O)[64], float& cc0, float& cc1, float& l0, float& l1,
                                             float (&a)[4], const uint32_t (&pe)[2 * EARLY + 1], uint32_t zero) {
#pragma unroll
  for (int i = 0; i < 2 * EARLY; i++) p[i] = pe[i] ^ zero;
  exp_pack<EARLY>(S, p, a);
  if (__any_sync(~0u, !(fmaxf(a[0] + a[1], a[2] + a[3]) <= 65536.f))) {
    float d0, d1;
    row_max2(S, d0, d1);
    d0 = fmaxf(d0, 0.f); d1 = fmaxf(d1, 0.f);
#pragma unroll
    for (int i = 0; i < 16; i++) { S[4 * i] -= d0; S[4 * i + 1] -= d0; S[4 * i + 2] -= d1; S[4 * i + 3] -= d1; }
    cc0 -= d0; cc1 -= d1;
    const float f0 = ex2(-d0), f1 = ex2(-d1);
    scale_o(O, f0, f1);
    l0 *= f0; l1 *= f1;
    a[0] = a[1] = a[2] = a[3] = 0.f;
    exp_pack<0>(S, p, a);
  }
  l0 += a[0] + a[1];
  l1 += a[2] + a[3];
}

__device__ __forceinline__ void inv_rowsum(float l0, float l1, float& i0, float& i1) {
  l0 += __shfl_xor_sync(~0u, l0, 1); l1 += __shfl_xor_sync(~0u, l1, 1);
  l0 += __shfl_xor_sync(~0u, l0, 2); l1 += __shfl_xor_sync(~0u, l1, 2);
  i0 = rcp(l0); i1 = rcp(l1);
}
__device__ __forceinline__ void write_o(const float (&O)[64], const Cons& c) {
  uint32_t rowoff, xr;
  frag_addr(rowoff, xr);
  const uint32_t stg = c.sb + SM_STG + c.wg * 16384 + rowoff;
#pragma unroll
  for (int kb = 0; kb < 8; kb++)
    stsm4(stg + (kb >> 2) * 8192 + ((32 * (kb & 3)) ^ xr),
          pack_bf16(O[8 * kb], O[8 * kb + 1]), pack_bf16(O[8 * kb + 2], O[8 * kb + 3]),
          pack_bf16(O[8 * kb + 4], O[8 * kb + 5]), pack_bf16(O[8 * kb + 6], O[8 * kb + 7]));
  c.stg_publish();
}

__device__ __forceinline__ void issue_qk(float (&S)[64], const uint32_t (&q)[32], uint32_t s0, uint32_t s1, uint32_t zero) {
  const uint64_t d0 = mkdesc(s0, 16, 1024), d1 = mkdesc(s1, 16, 1024);
#pragma unroll
  for (int kk = 0; kk < 8; kk++)
    wgmma_rs_n128(S, q[4 * kk], q[4 * kk + 1], q[4 * kk + 2], q[4 * kk + 3], (kk < 4 ? d0 : d1) + (kk & 3) * 2, kk > 0 ? 1u : zero);
}
__device__ __forceinline__ void issue_pv(float (&O)[64], const uint32_t (&p)[32], uint32_t s0, uint32_t s1, uint32_t accum) {
  const uint64_t d0 = mkdesc(s0, 8192, 1024), d1 = mkdesc(s1, 8192, 1024);
#pragma unroll
  for (int kk = 0; kk < 8; kk++)
    wgmma_rs_n128_tb(O, p[4 * kk], p[4 * kk + 1], p[4 * kk + 2], p[4 * kk + 3], (kk < 4 ? d0 : d1) + (kk & 3) * 128, kk > 0 ? 1u : accum);
}

#define TURN_SYNC()   bar_sync(1 + c.wg, 256)
#define TURN_PASS()   bar_arrive(2 - c.wg, 256)

__device__ __forceinline__ void attn_tile(const float (&acc)[128], Cons& c, int t) {
  uint32_t q[32], p[32];
  float S[64], O[64];
  const uint32_t stash = c.sb + SM_STG + c.wg * 16384 + ((threadIdx.x >> 5) & 3) * 2048 + c.lane * 16;
#pragma unroll
  for (int i = 0; i < 32; i++) q[i] = pack_bf16(acc[2 * i], acc[2 * i + 1]);
  c.stg_acquire();
#pragma unroll
  for (int i = 0; i < 8; i++)
    sts128(stash + (i >> 2) * 8192 + (i & 3) * 512, pack_bf16(acc[64 + 8 * i], acc[65 + 8 * i]), pack_bf16(acc[66 + 8 * i], acc[67 + 8 * i]),
           pack_bf16(acc[68 + 8 * i], acc[69 + 8 * i]), pack_bf16(acc[70 + 8 * i], acc[71 + 8 * i]));
  fence_regs(q);
  TR(0, 0);
  TURN_SYNC();
  TR(0, 1);
  c.wait_full(c.g);
  wg_fence();
  issue_qk(O, q, c.sb + c.pos * SLOT, c.sb + wrap12(c.pos + 1) * SLOT, 0);
  wg_commit();
  c.wait_full(c.g + 1);
  wg_fence();
  issue_qk(S, q, c.sb + wrap12(c.pos + 2) * SLOT, c.sb + wrap12(c.pos + 3) * SLOT, 0);
  wg_commit();
  TURN_PASS();
  TR(0, 2);
  wg_wait<1>();
  TR(0, 3);
  fence_regs(O);
  c.release(c.g);
  float cc0, cc1, l0, l1, f0 = 0.f, f1 = 0.f;
  float a[4] = {0.f, 0.f, 0.f, 0.f};
  uint32_t pe[2 * EARLY + 1];
  row_max2(O, cc0, cc1);
  cc0 *= -SM_C; cc1 *= -SM_C;
  ONCE(c) { to_exponent(O, cc0, cc1); }
  wg_wait<0>();
  fence_regs(S);
  fence_regs(q);
  c.release(c.g + 1);
  exp_pack<0>(O, p, a);
  l0 = a[0] + a[1];
  l1 = a[2] + a[3];
  c.pos = wrap12(c.pos + 4);
  TR(1, 0);
  TURN_SYNC();
  TR(1, 1);
  c.wait_full(c.g + 2);
  wg_fence();
  issue_pv(O, p, c.sb + c.pos * SLOT, c.sb + wrap12(c.pos + 1) * SLOT, 0);
  wg_commit();
  TURN_PASS();
  TR(1, 2);
  softmax_early(S, cc0, cc1, a, pe, c);
  TR(1, 4);
  wg_wait<0>();
  TR(1, 5);
  fence_regs(O);
  fence_regs(p);
  c.release(c.g + 2);
  c.g += 3;
  c.pos = wrap12(c.pos + 2);
  softmax_late(S, p, O, cc0, cc1, l0, l1, a, pe, c.zero);
#pragma unroll 1
  for (int j = 1; j < 7 + (int)c.zero; j++) {
    const uint32_t k0 = c.pos, k1 = wrap12(k0 + 1), v0 = wrap12(k0 + 2), v1 = wrap12(k0 + 3);
    TR(j + 1, 0);
    TURN_SYNC();
    TR(j + 1, 1);
    c.wait_full(c.g);
    wg_fence();
    issue_qk(S, q, c.sb + k0 * SLOT, c.sb + k1 * SLOT, 0);
    wg_commit();
    if (j == 4) {
      scale_o(O, f0, f1);
      write_o(O, c);
    }
    c.wait_full(c.g + 1);
    wg_fence();
    issue_pv(O, p, c.sb + v0 * SLOT, c.sb + v1 * SLOT, j != 4);
    wg_commit();
    TURN_PASS();
    TR(j + 1, 2);
    wg_wait<1>();
    TR(j + 1, 3);
    fence_regs(S);
    fence_regs(q);
    c.release(c.g);
    if (j == 3) {
      row_max2(S, cc0, cc1);
      cc0 *= -SM_C; cc1 *= -SM_C;
      inv_rowsum(l0, l1, f0, f1);
      l0 = 0.f; l1 = 0.f;
    }
    softmax_early(S, cc0, cc1, a, pe, c);
    if (j == 2) {
#pragma unroll
      for (int i = 0; i < 8; i++) lds128(stash + (i >> 2) * 8192 + (i & 3) * 512, q[4 * i], q[4 * i + 1], q[4 * i + 2], q[4 * i + 3]);
      __syncwarp();
    }
    TR(j + 1, 4);
    wg_wait<0>();
    TR(j + 1, 5);
    fence_regs(O);
    fence_regs(p);
    c.release(c.g + 1);
    c.g += 2;
    c.pos = wrap12(v1 + 1);
    softmax_late(S, p, O, cc0, cc1, l0, l1, a, pe, c.zero);
  }
  TR(8, 0);
  TURN_SYNC();
  TR(8, 1);
  c.wait_full(c.g);
  wg_fence();
  issue_pv(O, p, c.sb + c.pos * SLOT, c.sb + wrap12(c.pos + 1) * SLOT, 1);
  wg_commit();
  TURN_PASS();
  TR(8, 2);
  c.stg_acquire();
  float a0, a1;
  inv_rowsum(l0, l1, a0, a1);
  wg_wait<0>();
  TR(8, 5);
  fence_regs(O);
  fence_regs(p);
  c.release(c.g);
  c.g++;
  c.pos = wrap12(c.pos + 2);
  scale_o(O, a0, a1);
  write_o(O, c);
  TR(9, 0);
}

struct Prod {
  uint32_t sb, g, pos, head, tail_g, tail_pos, hist;
  __device__ __forceinline__ uint32_t full() const { return sb + SM_BAR + B_FULL + (g & 7) * 8; }
  __device__ __forceinline__ uint32_t slot(uint32_t i) const { return sb + wrap12(pos + i) * SLOT; }
  __device__ __forceinline__ void acquire(uint32_t size) {
#pragma unroll 1
    while (head + size - tail_pos > NSLOT) {
      mbar_wait(sb + SM_BAR + B_EMPTY + (tail_g & 7) * 8, (tail_g >> 3) & 1);
      tail_pos += 2 + ((hist >> (tail_g & 31)) & 1);
      tail_g++;
    }
    hist = (hist & ~(1u << (g & 31))) | ((size - 2) << (g & 31));
  }
  __device__ __forceinline__ void advance(uint32_t size) { g++; head += size; pos = wrap12(pos + size); }
};

__device__ __forceinline__ void wait_flag(const unsigned* p, unsigned target) {
  while ((int)(ld_acquire(p) - target) < 0) {}
  fence_async_all();
}

__device__ __forceinline__ void init_barriers(uint32_t sb, int warp) {
  const uint32_t cnt = warp < 4 ? 1 : warp < 8 ? 16 : warp == 8 ? 4 : warp == 9 ? 1 : 11;
  if (warp < 11) mbar_init(sb + SM_BAR + warp * 16, cnt);
  if (warp < 10) mbar_init(sb + SM_BAR + warp * 16 + 8, cnt);
  asm volatile("fence.mbarrier_init.release.cluster;" ::: "memory");
}

#define TSP(i) do {} while (0)

__global__ void __cluster_dims__(2, 1, 1) __launch_bounds__(384, 1) fused_kernel(const __grid_constant__ Params P) {
  extern __shared__ uint8_t smem_raw[];
  const uint32_t sb = (smem_u32(smem_raw) + 1023u) & ~1023u;
  const int warp = __shfl_sync(~0u, (int)(threadIdx.x >> 5), 0);
  const int lane = threadIdx.x & 31;
  const int rank = blockIdx.x & 1;
  const int cl = blockIdx.x >> 1;
  const int j = cl >> 3;
  const int rb = (cl & 7) * 2 + rank;
  const bool is_s = j < 4, spare = j == 8;
  const int row0 = rb * 128;
  Flags* fl = P.flags;

  if (warp >= 8) {
    unsigned ep0 = 0;
    if (warp == 8) asm volatile("ld.volatile.global.u32 %0, [%1];" : "=r"(ep0) : "l"(&fl->epoch[blockIdx.x]));
    if (lane == 0) {
      if (warp == 8) prefetch_map(spare ? &P.w1b4 : &P.w1b3);
      if (warp == 9) prefetch_map(&P.act_ld);
      init_barriers(sb, warp);
    }
    __syncwarp();
    cluster_arrive();
    if (warp == 10 && lane == 0) {
      prefetch_map(&P.act_st); prefetch_map(&P.wq); prefetch_map(&P.k_ld); prefetch_map(&P.v_ld);
      prefetch_map(is_s ? &P.wo : &P.w2); prefetch_map(&P.x_ld); prefetch_map(&P.out_st);
    }
    __syncwarp();
    cluster_wait();
    asm volatile("setmaxnreg.dec.sync.aligned.u32 24;");
    if (warp == 8) {
      TSP(17);
#define ep1 (ep0 + 1)
      Prod p{sb, 0, 0, 0, 0, 0, 0};
#define LDA(dst, m, bar, c0, c1) tma_ld2(dst, m, bar, c0, c1)
#define LDW1(dst, m, bar, c0, c1, c2) tma_ld3_mc(dst, m, bar, c0, c1, c2)
#define LDW(dst, m, bar, c0, c1, c2) tma_ld3_mc(dst, m, bar, c0, c1, c2)
      {
        const CUtensorMap* mb = spare ? &P.w1b4 : &P.w1b3;
        const uint32_t bytes = spare ? 49152 : 40960;
        const int nt = spare ? 8 : 2;
#pragma unroll 1
        for (int t = 0; t < nt; t++) {
          const int r = spare ? ((cl & 1) * 4 + (t >> 1)) * 2 + rank : rb;
          const int nb0 = spare ? (H_SPARE0 >> 6) + (t & 1) * 4 : j * 6 + t * 3;
          int k = 0;
          if (t == 0) {
#pragma unroll 1
            for (; k < 4; k++) {
              p.acquire(3);
              if (lane == 0) { mbar_expect_tx(p.full(), bytes); LDW1(p.slot(1 + rank), mb, p.full(), 0, k * 64 + rank * 32, nb0); }
              p.advance(3);
            }
            TSP(14);
            asm volatile("" : "+r"(ep0));
            wait_flag(&fl->ln[r][0], ep1 * 64);
            TSP(15);
            if (lane == 0)
              for (int i = 0; i < 4; i++) tma_ld2(sb + i * 3 * SLOT, &P.act_ld, sb + SM_BAR + B_FULL + i * 8, C_XN + i * 64, r * 128);
          } else if (spare && !(t & 1)) {
            wait_flag(&fl->ln[r][0], ep1 * 64);
          }
#pragma unroll 1
          for (; k < 16; k++) {
            p.acquire(3);
            if (lane == 0) {
              mbar_expect_tx(p.full(), bytes);
              LDW1(p.slot(1 + rank), mb, p.full(), 0, k * 64 + rank * 32, nb0);
              tma_ld2(p.slot(0), &P.act_ld, p.full(), C_XN + k * 64, r * 128);
            }
            p.advance(3);
          }
        }
      }
      if (!spare) {
        const int kvrow = (j >> 1) * SK + KV0;
#pragma unroll 1
        for (int t = 0; t < 2; t++) {
          const int nb0 = (4 * j + 2 * t) * 2;
#pragma unroll 1
          for (int k = 0; k < 16; k++) {
            p.acquire(3);
            if (lane == 0) {
              mbar_expect_tx(p.full(), 49152);
              LDW1(p.slot(1 + rank), &P.wq, p.full(), 0, k * 64 + rank * 32, nb0);
              tma_ld2(p.slot(0), &P.act_ld, p.full(), C_XN + k * 64, row0);
            }
            p.advance(3);
          }
#pragma unroll 1
          for (int i = 0; i < 16; i++) {
            const bool is_k = i == 0 || (i < 15 && (i & 1));
            const int ch = (is_k ? ((i + 1) >> 1) : (i == 15 ? 7 : (i >> 1) - 1)) & 3;
            p.acquire(2);
            if (lane == 0) {
              mbar_expect_tx(p.full(), 32768);
              if (is_k) tma_ld2_mc(p.slot(rank), &P.k_ld, p.full(), rank * 64, kvrow + ch * 128);
              else      tma_ld3_mc(p.slot(rank), &P.v_ld, p.full(), 0, kvrow + ch * 128 + rank * 64, 0);
            }
            p.advance(2);
            if (t == 1 && i == 4 && !is_s) wait_flag(&fl->h[rb][0], ep1 * 64);
          }
        }
        const int jn = j & 3;
        if (is_s) {
          unsigned ready = 0;
#pragma unroll 1
          for (int i = 0; i < 64; i++) {
            const int hi = i >> 1;
            const int head = 4 * ((hi & 15) >> 1) + (hi & 1) + ((hi >> 4) << 1);
            const int kc = head * 128 + (i & 1) * 64;
            p.acquire(3);
            if (lane == 0) { mbar_expect_tx(p.full(), 49152); LDW(p.slot(1 + rank), &P.wo, p.full(), 0, kc + rank * 32, jn * 4); }
            if (!((ready >> head) & 1)) {
              do { ready = __ballot_sync(~0u, (int)(ld_acquire(&fl->o[rb][lane]) - ep1 * 2) >= 0); } while (!((ready >> head) & 1));
              __syncwarp();
              fence_async_all();
            }
            if (lane == 0) LDA(p.slot(0), &P.act_ld, p.full(), C_O + kc, row0);
            if (i == 52) {
              if (lane == 0) { prefetch_map(&P.x_ld); prefetch_map(&P.out_st); }
              if (lane < 4) tma_pf2(&P.x_ld, jn * 256 + lane * 64, row0);
            }
            p.advance(3);
          }
          bool g_ready = false;
#pragma unroll 1
          for (int i = 0; i < 4; i++) {
            if (i < 3 && !g_ready) g_ready = (int)(ld_acquire(&fl->g[rb][jn]) - ep1 * 4) >= 0;
            p.acquire(2);
            if (i == 2) { TSP(20); if (g_ready) fence_async_all(); else wait_flag(&fl->g[rb][jn], ep1 * 4); TSP(21); }
            if (lane == 0) {
              mbar_expect_tx(p.full(), 32768);
              const CUtensorMap* m = i < 2 ? &P.x_ld : &P.act_ld;
              const int c0 = (i < 2 ? 0 : C_G) + jn * 256 + (i & 1) * 128;
              tma_ld2(p.slot(0), m, p.full(), c0, row0);
              tma_ld2(p.slot(1), m, p.full(), c0 + 64, row0);
            }
            p.advance(2);
          }
        } else {
#pragma unroll 1
          for (int k = 0; k < 56; k++) {
            p.acquire(3);
            if (lane == 0) { mbar_expect_tx(p.full(), 49152); LDW(p.slot(1 + rank), &P.w2, p.full(), 0, k * 64 + rank * 32, jn * 4); }
            if (k == H_SPARE0 / 64) wait_flag(&fl->h[rb][16], ep1 * 8);
            if (lane == 0) LDA(p.slot(0), &P.act_ld, p.full(), C_H + k * 64, row0);
            p.advance(3);
          }
        }
      }
      if (lane == 0) { *(volatile unsigned*)&fl->epoch[blockIdx.x] = ep1; mbar_arrive(sb + SM_BAR + B_DONE); }
    } else if (warp < 11) {
      const int wg = warp - 9;
      if (lane == 0) {
        const uint32_t stg = sb + SM_STG + wg * 16384;
        const int nev = spare ? 16 : is_s ? 8 : 10;
#pragma unroll 1
        for (int n = 0; n < nev; n++) {
          int col, row = row0, nbox = 2;
          unsigned* flag;
          if (spare) {
            const int r = ((cl & 1) * 4 + (n >> 2)) * 2 + rank;
            row = r * 128;
            col = C_H + H_SPARE0 + (n & 3) * 128;
            flag = &fl->h[r][16];
          } else if (n < 4) {
            col = C_H + j * H_REG + (n >> 1) * 192 + (n & 1) * 128;
            nbox = 2 - (n & 1);
            flag = &fl->h[rb][0];
          } else if (n < 8) {
            col = C_O + (4 * j + n - 4) * 128;
            flag = &fl->o[rb][4 * j + n - 4];
          } else {
            col = C_G + (j & 3) * 256 + (n - 8) * 128;
            flag = &fl->g[rb][j & 3];
          }
          mbar_wait(sb + SM_BAR + B_SFULL + wg * 8, n & 1);
          if (n == 9 && wg == 0) TSP(20);
          tma_st2(&P.act_st, stg, col, row + wg * 64);
          if (nbox == 2) tma_st2(&P.act_st, stg + 8192, col + 64, row + wg * 64);
          bulk_commit();
          bulk_wait_read0();
          mbar_arrive(sb + SM_BAR + B_SEMPTY + wg * 8);
          if (n == 9 && wg == 0) TSP(21);
          bulk_wait0();
          if (n == 9 && wg == 0) TSP(22);
          fence_async_all();
          red_release(flag, 1);
          if (n == 9 && wg == 0) TSP(23);
        }
        mbar_arrive(sb + SM_BAR + B_DONE);
      }
    } else {
      if (lane == 0) {
        const unsigned long long t0 = gtime();
        while (!mbar_try(sb + SM_BAR + B_DONE, 0)) {
          if (gtime() - t0 > 2000000000ull) __trap();
        }
      }
    }
    __syncwarp();
    cluster_arrive();
    cluster_wait();
  } else {
    const int wg = warp >> 2;
    TS(0);
    if (!spare) {
      const int r = row0 + j * 16 + warp * 2;
      uint32_t v[2][16];
#pragma unroll
      for (int a = 0; a < 2; a++)
#pragma unroll
        for (int i = 0; i < 4; i++)
          *(uint4*)&v[a][4 * i] = __ldg((const uint4*)(P.x + (size_t)(r + a) * DM + i * 256 + lane * 8));
      if (lane == 0) init_barriers(sb, warp);
      __syncwarp();
      cluster_arrive();
      float s[2], q[2];
#pragma unroll
      for (int a = 0; a < 2; a++) {
        float t0 = 0.f, t1 = 0.f;
#pragma unroll
        for (int i = 0; i < 16; i++) { t0 += bf_lo(v[a][i]); t1 += bf_hi(v[a][i]); }
        s[a] = t0 + t1;
      }
#pragma unroll
      for (int o = 16; o; o >>= 1) { s[0] += __shfl_xor_sync(~0u, s[0], o); s[1] += __shfl_xor_sync(~0u, s[1], o); }
#pragma unroll
      for (int a = 0; a < 2; a++) {
        s[a] *= 1.0f / DM;
        float t0 = 0.f, t1 = 0.f;
#pragma unroll
        for (int i = 0; i < 16; i++) {
          const float d0 = bf_lo(v[a][i]) - s[a], d1 = bf_hi(v[a][i]) - s[a];
          t0 = fmaf(d0, d0, t0); t1 = fmaf(d1, d1, t1);
        }
        q[a] = t0 + t1;
      }
#pragma unroll
      for (int o = 16; o; o >>= 1) { q[0] += __shfl_xor_sync(~0u, q[0], o); q[1] += __shfl_xor_sync(~0u, q[1], o); }
#pragma unroll
      for (int a = 0; a < 2; a++) {
        const uint32_t mb2 = pack_bf16(s[a], s[a]);
        const float inv = 1.0f / bf_round(sqrtf(bf_round(bf_round(q[a] * (1.0f / DM)) + 1e-5f)));
#pragma unroll
        for (int i = 0; i < 16; i++) {
          const __nv_bfloat162 d = __hsub2_rn(*(const __nv_bfloat162*)&v[a][i], *(const __nv_bfloat162*)&mb2);
          const uint32_t du = *(const uint32_t*)&d;
          v[a][i] = pack_bf16(bf_lo(du) * inv, bf_hi(du) * inv);
        }
#pragma unroll
        for (int i = 0; i < 4; i++)
          *(uint4*)(P.act + (size_t)(r + a) * ACT_W + C_XN + i * 256 + lane * 8) = *(const uint4*)&v[a][4 * i];
      }
      TS(11);
      fence_async_all();
      TS(12);
      __syncwarp();
      if (lane == 0) red_release(&fl->ln[rb][0], 1);
      TS(13);
    } else {
      if (lane == 0) init_barriers(sb, warp);
      __syncwarp();
      cluster_arrive();
    }
    cluster_wait();
    asm volatile("setmaxnreg.inc.sync.aligned.u32 240;");
    Cons c;
    c.zero = blockIdx.y; c.sb = sb; c.g = 0; c.pos = 0; c.nstg = 0; c.wg = wg; c.lane = lane;
    c.rel = mapa(sb + SM_BAR + B_EMPTY, lane & 1);
    float acc[128];
    TS(1);
    if (spare) {
      uint32_t pend[32];
#pragma unroll
      for (int i = 0; i < 32; i++) pend[i] = 0;
#pragma unroll 1
      for (int t = 0; t < 8; t++) {
        gemm_loop_flush<256, 2>(acc, c, pend, t > 0);
        h_epilogue<2>(acc, c, pend);
      }
      c.stg_acquire();
      stage_boxes<2>(pend, 0, c);
      TS(6);
    } else {
      if (wg == 1) bar_arrive(1, 256);
      {
        uint32_t pend[16];
#pragma unroll
        for (int i = 0; i < 16; i++) pend[i] = 0;
#pragma unroll 1
        for (int t = 0; t < 2; t++) {
          gemm_loop_flush<192, 1>(acc, c, pend, t > 0);
          h_epilogue<1>(acc, c, pend);
          TS(2 + t);
        }
        gemm_loop_flush<256, 1>(acc, c, pend, true);
      }
#pragma unroll 1
      for (int t = 0; t < 2; t++) {
        TS(8 + t);
        attn_tile(acc, c, t);
        TS(4 + t);
        gemm_loop<256>(acc, c, t == 0 ? 16 : is_s ? 64 : 56);
      }
      TS(6);
      uint32_t rowoff, xr;
      frag_addr(rowoff, xr);
      if (is_s) {
        const uint32_t x0 = c.pos;
#pragma unroll
        for (int b = 0; b < 4; b++) {
          if ((b & 1) == 0) { c.wait_full(c.g + (b >> 1)); c.wait_full(c.g + 2 + (b >> 1)); }
          if (b == 0) TS(22);
          if (b == 2) TS(23);
          const uint32_t xs = sb + wrap12(x0 + b) * SLOT + wg * 8192;
          const uint32_t sx = xs + rowoff, sg = sb + wrap12(wrap12(x0 + 4) + b) * SLOT + wg * 8192 + rowoff;
          uint32_t xv[16], gv[16];
#pragma unroll
          for (int kb = 0; kb < 4; kb++) {
            ldsm4(sx + ((32 * kb) ^ xr), xv[4 * kb], xv[4 * kb + 1], xv[4 * kb + 2], xv[4 * kb + 3]);
            ldsm4(sg + ((32 * kb) ^ xr), gv[4 * kb], gv[4 * kb + 1], gv[4 * kb + 2], gv[4 * kb + 3]);
          }
#pragma unroll
          for (int i = 0; i < 16; i++) {
            const uint32_t s2 = pack_bf16(acc[32 * b + 2 * i], acc[32 * b + 2 * i + 1]);
            const __nv_bfloat162 pr = __hmul2_rn(*(const __nv_bfloat162*)&s2, *(const __nv_bfloat162*)&gv[i]);
            const __nv_bfloat162 o = __hadd2_rn(*(const __nv_bfloat162*)&xv[i], pr);
            xv[i] = *(const uint32_t*)&o;
          }
#pragma unroll
          for (int kb = 0; kb < 4; kb++) stsm4(sx + ((32 * kb) ^ xr), xv[4 * kb], xv[4 * kb + 1], xv[4 * kb + 2], xv[4 * kb + 3]);
          if (b & 1) {
            fence_async_smem();
            bar_sync(3 + wg, 128);
            if ((threadIdx.x & 127) == 0) {
              tma_st2(&P.out_st, sb + wrap12(x0 + b - 1) * SLOT + wg * 8192, (j & 3) * 256 + b * 64 - 64, row0 + wg * 64);
              tma_st2(&P.out_st, xs, (j & 3) * 256 + b * 64, row0 + wg * 64);
              bulk_commit();
            }
          }
        }
        TS(24);
        if ((threadIdx.x & 127) == 0) bulk_wait_read0();
      } else {
        const uint32_t stg = sb + SM_STG + wg * 16384 + rowoff;
#pragma unroll
        for (int hh = 0; hh < 2; hh++) {
#pragma unroll
          for (int bx = 0; bx < 2; bx++) {
            uint32_t r[16];
            ONCE(c) {
#pragma unroll
              for (int i = 0; i < 16; i++) r[i] = silu2(pack_bf16(acc[64 * hh + 32 * bx + 2 * i], acc[64 * hh + 32 * bx + 2 * i + 1]) ^ once_);
            }
            if (bx == 0) c.stg_acquire();
#pragma unroll
            for (int kb = 0; kb < 4; kb++) stsm4(stg + bx * 8192 + ((32 * kb) ^ xr), r[4 * kb], r[4 * kb + 1], r[4 * kb + 2], r[4 * kb + 3]);
          }
          c.stg_publish();
          if (hh == 0) TS(22);
        }
      }
    }
    TS(7);
    __syncwarp();
    if (lane == 0) mbar_arrive(sb + SM_BAR + B_DONE);
    cluster_arrive();
    cluster_wait();
  }
}

typedef CUresult (*EncodeFn)(CUtensorMap*, CUtensorMapDataType, cuuint32_t, void*, const cuuint64_t*, const cuuint64_t*,
                             const cuuint32_t*, const cuuint32_t*, CUtensorMapInterleave, CUtensorMapSwizzle,
                             CUtensorMapL2promotion, CUtensorMapFloatOOBfill);

void map2d(EncodeFn enc, CUtensorMap* m, const void* base, uint64_t cols, uint64_t rows, uint32_t box_rows) {
  cuuint64_t dims[2] = {cols, rows};
  cuuint64_t strides[1] = {cols * 2};
  cuuint32_t box[2] = {64, box_rows};
  cuuint32_t es[2] = {1, 1};
  enc(m, CU_TENSOR_MAP_DATA_TYPE_BFLOAT16, 2, (void*)base, dims, strides, box, es, CU_TENSOR_MAP_INTERLEAVE_NONE,
      CU_TENSOR_MAP_SWIZZLE_128B, CU_TENSOR_MAP_L2_PROMOTION_L2_256B, CU_TENSOR_MAP_FLOAT_OOB_FILL_NONE);
}
void map3d(EncodeFn enc, CUtensorMap* m, const void* base, uint64_t cols, uint64_t rows, uint32_t box_rows, uint32_t box_blks) {
  cuuint64_t dims[3] = {64, rows, cols / 64};
  cuuint64_t strides[2] = {cols * 2, 128};
  cuuint32_t box[3] = {64, box_rows, box_blks};
  cuuint32_t es[3] = {1, 1, 1};
  enc(m, CU_TENSOR_MAP_DATA_TYPE_BFLOAT16, 3, (void*)base, dims, strides, box, es, CU_TENSOR_MAP_INTERLEAVE_NONE,
      CU_TENSOR_MAP_SWIZZLE_128B, CU_TENSOR_MAP_L2_PROMOTION_L2_256B, CU_TENSOR_MAP_FLOAT_OOB_FILL_NONE);
}

}

extern "C" void kernel_launch(void* const* d_in, const int* in_sizes, int n_in, void* d_out, int out_size) {
  (void)in_sizes; (void)n_in; (void)out_size;
  static EncodeFn enc = nullptr;
  static void* act = nullptr;
  static void* flags = nullptr;
  if (!enc) {
    void* fn = nullptr;
    cudaDriverEntryPointQueryResult qr;
    cudaGetDriverEntryPoint("cuTensorMapEncodeTiled", &fn, cudaEnableDefault, &qr);
    enc = (EncodeFn)fn;
    cudaGetSymbolAddress(&act, g_act);
    cudaGetSymbolAddress(&flags, g_flags);
    cudaFuncSetAttribute(fused_kernel, cudaFuncAttributeMaxDynamicSharedMemorySize, SMEM_BYTES);
  }
  Params P;
  map2d(enc, &P.act_ld, act, ACT_W, SEQ, 128);
  map2d(enc, &P.act_st, act, ACT_W, SEQ, 64);
  map2d(enc, &P.x_ld, d_in[0], DM, SEQ, 128);
  map2d(enc, &P.out_st, d_out, DM, SEQ, 64);
  map2d(enc, &P.k_ld, d_in[1], 128, 4 * SK, 128);
  map3d(enc, &P.v_ld, d_in[2], 128, 4 * SK, 64, 2);
  map3d(enc, &P.wq, d_in[3], NQ, DM, 32, 4);
  map3d(enc, &P.w1b4, d_in[6], DFF, DM, 32, 4);
  map3d(enc, &P.w1b3, d_in[6], DFF, DM, 32, 3);
  map3d(enc, &P.wo, d_in[4], DM, NQ, 32, 4);
  map3d(enc, &P.w2, d_in[7], DM, DFF, 32, 4);
  P.x = (const __nv_bfloat16*)d_in[0];
  P.act = (__nv_bfloat16*)act;
  P.flags = (Flags*)flags;
  fused_kernel<<<NCLUSTER * 2, 384, SMEM_BYTES>>>(P);
}
```

```cpp
#include <cuda_runtime.h>
#include <cuda_bf16.h>
#include <cuda.h>
#include <stdint.h>

namespace {

constexpr int SEQ    = 2048;
constexpr int DM     = 1024;
constexpr int NQ     = 4096;
constexpr int DFF    = 3584;
constexpr int SK     = 2048;
constexpr int WIN    = 512;
constexpr int KV0    = SK - WIN;
constexpr int C_XN = 0, C_O = 1024, C_H = 5120, C_G = 8704, ACT_W = 9728;

constexpr int H_REG = 384, H_SPARE0 = 8 * H_REG;
static_assert(H_SPARE0 + 512 == DFF, "H split");

constexpr int NSLOT = 12, SLOT = 16384, NBAR = 8;
constexpr int SM_STG = NSLOT * SLOT;
constexpr int SM_BAR = SM_STG + 2 * 16384;
constexpr int SMEM_BYTES = SM_BAR + 256 + 1024;
constexpr int B_FULL = 0, B_EMPTY = 64, B_SFULL = 128, B_SEMPTY = 144, B_DONE = 160;

constexpr int NCLUSTER = 66;

struct Flags {
  unsigned ln[16][32];
  unsigned h[16][32];
  unsigned o[16][32];
  unsigned g[16][32];
  unsigned epoch[160];
};
__device__ __nv_bfloat16 g_act[(size_t)SEQ * ACT_W];
__device__ Flags g_flags;

struct Params {
  CUtensorMap act_ld, act_st, x_ld, out_st, k_ld, v_ld, wq, w1b4, w1b3, wo, w2;
  const __nv_bfloat16* x;
  __nv_bfloat16* act;
  Flags* flags;
};

__device__ __forceinline__ uint32_t smem_u32(const void* p) { return (uint32_t)__cvta_generic_to_shared(p); }
__device__ __forceinline__ void mbar_init(uint32_t bar, uint32_t cnt) {
  asm volatile("mbarrier.init.shared::cta.b64 [%0], %1;" ::"r"(bar), "r"(cnt) : "memory");
}
__device__ __forceinline__ bool mbar_try(uint32_t bar, uint32_t parity) {
  uint32_t ok;
  asm volatile("{\n.reg .pred p;\nmbarrier.try_wait.parity.shared::cta.b64 p, [%1], %2;\nselp.u32 %0, 1, 0, p;\n}\n"
               : "=r"(ok) : "r"(bar), "r"(parity) : "memory");
  return ok;
}
__device__ __forceinline__ void mbar_wait(uint32_t bar, uint32_t parity) {
  asm volatile("{\n.reg .pred p;\nWAIT_%=:\nmbarrier.try_wait.parity.shared::cta.b64 p, [%0], %1;\n@p bra DONE_%=;\nbra WAIT_%=;\nDONE_%=:\n}\n"
               ::"r"(bar), "r"(parity) : "memory");
}
__device__ __forceinline__ void mbar_arrive(uint32_t bar) {
  asm volatile("mbarrier.arrive.shared::cta.b64 _, [%0];" ::"r"(bar) : "memory");
}
__device__ __forceinline__ void mbar_arrive_cluster(uint32_t cluster_addr) {
  asm volatile("mbarrier.arrive.shared::cluster.b64 _, [%0];" ::"r"(cluster_addr) : "memory");
}
__device__ __forceinline__ void mbar_expect_tx(uint32_t bar, uint32_t bytes) {
  asm volatile("mbarrier.arrive.expect_tx.shared::cta.b64 _, [%0], %1;" ::"r"(bar), "r"(bytes) : "memory");
}
__device__ __forceinline__ uint32_t mapa(uint32_t addr, uint32_t rank) {
  uint32_t r;
  asm("mapa.shared::cluster.u32 %0, %1, %2;" : "=r"(r) : "r"(addr), "r"(rank));
  return r;
}
__device__ __forceinline__ void cluster_arrive() { asm volatile("barrier.cluster.arrive.relaxed.aligned;" ::: "memory"); }
__device__ __forceinline__ void cluster_wait() { asm volatile("barrier.cluster.wait.acquire.aligned;" ::: "memory"); }
__device__ __forceinline__ void bar_sync(int id, int n) { asm volatile("bar.sync %0, %1;" ::"r"(id), "r"(n) : "memory"); }
__device__ __forceinline__ void bar_arrive(int id, int n) { asm volatile("bar.arrive %0, %1;" ::"r"(id), "r"(n) : "memory"); }
__device__ __forceinline__ void fence_async_smem() { asm volatile("fence.proxy.async.shared::cta;" ::: "memory"); }
__device__ __forceinline__ void fence_async_all() { asm volatile("fence.proxy.async.global;" ::: "memory"); }

__device__ __forceinline__ void tma_ld2(uint32_t dst, const CUtensorMap* m, uint32_t bar, int c0, int c1) {
  asm volatile("cp.async.bulk.tensor.2d.shared::cluster.global.mbarrier::complete_tx::bytes [%0], [%1, {%3, %4}], [%2];"
               ::"r"(dst), "l"(m), "r"(bar), "r"(c0), "r"(c1) : "memory");
}
__device__ __forceinline__ void tma_ld2_mc(uint32_t dst, const CUtensorMap* m, uint32_t bar, int c0, int c1) {
  asm volatile("cp.async.bulk.tensor.2d.shared::cluster.global.mbarrier::complete_tx::bytes.multicast::cluster [%0], [%1, {%3, %4}], [%2], %5;"
               ::"r"(dst), "l"(m), "r"(bar), "r"(c0), "r"(c1), "h"((uint16_t)3) : "memory");
}
__device__ __forceinline__ void tma_ld3_mc(uint32_t dst, const CUtensorMap* m, uint32_t bar, int c0, int c1, int c2) {
  asm volatile("cp.async.bulk.tensor.3d.shared::cluster.global.mbarrier::complete_tx::bytes.multicast::cluster [%0], [%1, {%3, %4, %5}], [%2], %6;"
               ::"r"(dst), "l"(m), "r"(bar), "r"(c0), "r"(c1), "r"(c2), "h"((uint16_t)3) : "memory");
}
__device__ __forceinline__ void tma_ld3_mc_hint(uint32_t dst, const CUtensorMap* m, uint32_t bar, int c0, int c1, int c2, uint64_t pol) {
  asm volatile("cp.async.bulk.tensor.3d.shared::cluster.global.mbarrier::complete_tx::bytes.multicast::cluster.L2::cache_hint [%0], [%1, {%3, %4, %5}], [%2], %6, %7;"
               ::"r"(dst), "l"(m), "r"(bar), "r"(c0), "r"(c1), "r"(c2), "h"((uint16_t)3), "l"(pol) : "memory");
}
__device__ __forceinline__ void tma_ld2_hint(uint32_t dst, const CUtensorMap* m, uint32_t bar, int c0, int c1, uint64_t pol) {
  asm volatile("cp.async.bulk.tensor.2d.shared::cluster.global.mbarrier::complete_tx::bytes.L2::cache_hint [%0], [%1, {%3, %4}], [%2], %5;"
               ::"r"(dst), "l"(m), "r"(bar), "r"(c0), "r"(c1), "l"(pol) : "memory");
}
__device__ __forceinline__ void tma_st2_hint(const CUtensorMap* m, uint32_t src, int c0, int c1, uint64_t pol) {
  asm volatile("cp.async.bulk.tensor.2d.global.shared::cta.bulk_group.L2::cache_hint [%0, {%2, %3}], [%1], %4;"
               ::"l"(m), "r"(src), "r"(c0), "r"(c1), "l"(pol) : "memory");
}
#define POL_FIRST 0x12F0000000000000ull
__device__ __forceinline__ uint64_t policy_evict_first() {
  uint64_t p;
  asm volatile("createpolicy.fractional.L2::evict_first.b64 %0, 1.0;" : "=l"(p));
  return p;
}
__device__ __forceinline__ void tma_st2(const CUtensorMap* m, uint32_t src, int c0, int c1) {
  asm volatile("cp.async.bulk.tensor.2d.global.shared::cta.bulk_group [%0, {%2, %3}], [%1];"
               ::"l"(m), "r"(src), "r"(c0), "r"(c1) : "memory");
}
__device__ __forceinline__ void tma_pf2(const CUtensorMap* m, int c0, int c1) {
  asm volatile("cp.async.bulk.prefetch.tensor.2d.L2.global [%0, {%1, %2}];" ::"l"(m), "r"(c0), "r"(c1) : "memory");
}
__device__ __forceinline__ void bulk_commit() { asm volatile("cp.async.bulk.commit_group;" ::: "memory"); }
__device__ __forceinline__ void bulk_wait_read0() { asm volatile("cp.async.bulk.wait_group.read 0;" ::: "memory"); }
__device__ __forceinline__ void bulk_wait0() { asm volatile("cp.async.bulk.wait_group 0;" ::: "memory"); }
__device__ __forceinline__ void prefetch_map(const CUtensorMap* m) {
  asm volatile("prefetch.tensormap [%0];" ::"l"(m) : "memory");
}
__device__ __forceinline__ unsigned ld_acquire(const unsigned* p) {
  unsigned v;
  asm volatile("ld.acquire.gpu.global.u32 %0, [%1];" : "=r"(v) : "l"(p) : "memory");
  return v;
}
__device__ __forceinline__ void red_release(unsigned* p, unsigned v) {
  asm volatile("red.release.gpu.global.add.u32 [%0], %1;" ::"l"(p), "r"(v) : "memory");
}
__device__ __forceinline__ void wg_fence() { asm volatile("wgmma.fence.sync.aligned;" ::: "memory"); }
__device__ __forceinline__ void wg_commit() { asm volatile("wgmma.commit_group.sync.aligned;" ::: "memory"); }
template <int N> __device__ __forceinline__ void wg_wait() { asm volatile("wgmma.wait_group.sync.aligned %0;" ::"n"(N) : "memory"); }
template <int N> __device__ __forceinline__ void fence_regs(float (&d)[N]) {
#pragma unroll
  for (int i = 0; i < N; i++) asm volatile("" : "+f"(d[i])::"memory");
}
template <int N> __device__ __forceinline__ void fence_regs(uint32_t (&d)[N]) {
#pragma unroll
  for (int i = 0; i < N; i++) asm volatile("" : "+r"(d[i])::"memory");
}
__device__ __forceinline__ uint64_t mkdesc(uint32_t addr, uint32_t lbo, uint32_t sbo) {
  return (uint64_t)((addr & 0x3FFFF) >> 4) | ((uint64_t)(lbo >> 4) << 16) | ((uint64_t)(sbo >> 4) << 32) | (1ull << 62);
}
__device__ __forceinline__ uint32_t pack_bf16(float lo, float hi) {
  uint32_t r;
  asm("cvt.rn.bf16x2.f32 %0, %1, %2;" : "=r"(r) : "f"(hi), "f"(lo));
  return r;
}
__device__ __forceinline__ uint32_t pack_bf16_relu(float lo, float hi) {
  uint32_t r;
  asm("cvt.rn.relu.bf16x2.f32 %0, %1, %2;" : "=r"(r) : "f"(hi), "f"(lo));
  return r;
}
__device__ __forceinline__ float bf_lo(uint32_t v) { return __uint_as_float(v << 16); }
__device__ __forceinline__ float bf_hi(uint32_t v) { return __uint_as_float(v & 0xFFFF0000u); }
__device__ __forceinline__ float bf_round(float v) { return __bfloat162float(__float2bfloat16_rn(v)); }
__device__ __forceinline__ float ex2(float x) {
  float r;
  asm("ex2.approx.ftz.f32 %0, %1;" : "=f"(r) : "f"(x));
  return r;
}
__device__ __forceinline__ float rcp(float x) {
  float r;
  asm("rcp.approx.ftz.f32 %0, %1;" : "=f"(r) : "f"(x));
  return r;
}
__device__ __forceinline__ uint32_t tid_x() {
  uint32_t t;
  asm volatile("mov.u32 %0, %%tid.x;" : "=r"(t));
  return t;
}
__device__ __forceinline__ void stsm4(uint32_t addr, uint32_t r0, uint32_t r1, uint32_t r2, uint32_t r3) {
  asm volatile("stmatrix.sync.aligned.m8n8.x4.shared.b16 [%0], {%1, %2, %3, %4};" ::"r"(addr), "r"(r0), "r"(r1), "r"(r2), "r"(r3) : "memory");
}
__device__ __forceinline__ void ldsm4(uint32_t addr, uint32_t& r0, uint32_t& r1, uint32_t& r2, uint32_t& r3) {
  asm volatile("ldmatrix.sync.aligned.m8n8.x4.shared.b16 {%0, %1, %2, %3}, [%4];" : "=r"(r0), "=r"(r1), "=r"(r2), "=r"(r3) : "r"(addr) : "memory");
}
__device__ __forceinline__ void sts128(uint32_t addr, uint32_t r0, uint32_t r1, uint32_t r2, uint32_t r3) {
  asm volatile("st.shared.v4.b32 [%0], {%1, %2, %3, %4};" ::"r"(addr), "r"(r0), "r"(r1), "r"(r2), "r"(r3) : "memory");
}
__device__ __forceinline__ void lds128(uint32_t addr, uint32_t& r0, uint32_t& r1, uint32_t& r2, uint32_t& r3) {
  asm volatile("ld.shared.v4.b32 {%0, %1, %2, %3}, [%4];" : "=r"(r0), "=r"(r1), "=r"(r2), "=r"(r3) : "r"(addr) : "memory");
}
__device__ __forceinline__ unsigned long long gtime() {
  unsigned long long t;
  asm volatile("mov.u64 %0, %globaltimer;" : "=l"(t));
  return t;
}

__device__ __forceinline__ void wgmma_ss_n256_tb(float (&d)[128], uint64_t da, uint64_t db, uint32_t sc) {
  asm volatile("{\n.reg .pred p;\nsetp.ne.b32 p, %130, 0;\n"
    "wgmma.mma_async.sync.aligned.m64n256k16.f32.bf16.bf16 "
    "{%0, %1, %2, %3, %4, %5, %6, %7, %8, %9, %10, %11, %12, %13, %14, %15, %16, %17, %18, %19, %20, %21, %22, %23, %24, %25, %26, %27, %28, %29, %30, %31, %32, %33, %34, %35, %36, %37, %38, %39, %40, %41, %42, %43, %44, %45, %46, %47, %48, %49, %50, %51, %52, %53, %54, %55, %56, %57, %58, %59, %60, %61, %62, %63, %64, %65, %66, %67, %68, %69, %70, %71, %72, %73, %74, %75, %76, %77, %78, %79, %80, %81, %82, %83, %84, %85, %86, %87, %88, %89, %90, %91, %92, %93, %94, %95, %96, %97, %98, %99, %100, %101, %102, %103, %104, %105, %106, %107, %108, %109, %110, %111, %112, %113, %114, %115, %116, %117, %118, %119, %120, %121, %122, %123, %124, %125, %126, %127}, %128, %129, p, 1, 1, 0, 1;\n}\n"
    : "+f"(d[0]), "+f"(d[1]), "+f"(d[2]), "+f"(d[3]), "+f"(d[4]), "+f"(d[5]), "+f"(d[6]), "+f"(d[7]), "+f"(d[8]), "+f"(d[9]), "+f"(d[10]), "+f"(d[11]), "+f"(d[12]), "+f"(d[13]), "+f"(d[14]), "+f"(d[15]), "+f"(d[16]), "+f"(d[17]), "+f"(d[18]), "+f"(d[19]), "+f"(d[20]), "+f"(d[21]), "+f"(d[22]), "+f"(d[23]), "+f"(d[24]), "+f"(d[25]), "+f"(d[26]), "+f"(d[27]), "+f"(d[28]), "+f"(d[29]), "+f"(d[30]), "+f"(d[31]), "+f"(d[32]), "+f"(d[33]), "+f"(d[34]), "+f"(d[35]), "+f"(d[36]), "+f"(d[37]), "+f"(d[38]), "+f"(d[39]), "+f"(d[40]), "+f"(d[41]), "+f"(d[42]), "+f"(d[43]), "+f"(d[44]), "+f"(d[45]), "+f"(d[46]), "+f"(d[47]), "+f"(d[48]), "+f"(d[49]), "+f"(d[50]), "+f"(d[51]), "+f"(d[52]), "+f"(d[53]), "+f"(d[54]), "+f"(d[55]), "+f"(d[56]), "+f"(d[57]), "+f"(d[58]), "+f"(d[59]), "+f"(d[60]), "+f"(d[61]), "+f"(d[62]), "+f"(d[63]), "+f"(d[64]), "+f"(d[65]), "+f"(d[66]), "+f"(d[67]), "+f"(d[68]), "+f"(d[69]), "+f"(d[70]), "+f"(d[71]), "+f"(d[72]), "+f"(d[73]), "+f"(d[74]), "+f"(d[75]), "+f"(d[76]), "+f"(d[77]), "+f"(d[78]), "+f"(d[79]), "+f"(d[80]), "+f"(d[81]), "+f"(d[82]), "+f"(d[83]), "+f"(d[84]), "+f"(d[85]), "+f"(d[86]), "+f"(d[87]), "+f"(d[88]), "+f"(d[89]), "+f"(d[90]), "+f"(d[91]), "+f"(d[92]), "+f"(d[93]), "+f"(d[94]), "+f"(d[95]), "+f"(d[96]), "+f"(d[97]), "+f"(d[98]), "+f"(d[99]), "+f"(d[100]), "+f"(d[101]), "+f"(d[102]), "+f"(d[103]), "+f"(d[104]), "+f"(d[105]), "+f"(d[106]), "+f"(d[107]), "+f"(d[108]), "+f"(d[109]), "+f"(d[110]), "+f"(d[111]), "+f"(d[112]), "+f"(d[113]), "+f"(d[114]), "+f"(d[115]), "+f"(d[116]), "+f"(d[117]), "+f"(d[118]), "+f"(d[119]), "+f"(d[120]), "+f"(d[121]), "+f"(d[122]), "+f"(d[123]), "+f"(d[124]), "+f"(d[125]), "+f"(d[126]), "+f"(d[127])
    : "l"(da), "l"(db), "r"(sc));
}
__device__ __forceinline__ void wgmma_ss_n192_tb(float (&d)[128], uint64_t da, uint64_t db, uint32_t sc) {
  asm volatile("{\n.reg .pred p;\nsetp.ne.b32 p, %98, 0;\n"
    "wgmma.mma_async.sync.aligned.m64n192k16.f32.bf16.bf16 "
    "{%0, %1, %2, %3, %4, %5, %6, %7, %8, %9, %10, %11, %12, %13, %14, %15, %16, %17, %18, %19, %20, %21, %22, %23, %24, %25, %26, %27, %28, %29, %30, %31, %32, %33, %34, %35, %36, %37, %38, %39, %40, %41, %42, %43, %44, %45, %46, %47, %48, %49, %50, %51, %52, %53, %54, %55, %56, %57, %58, %59, %60, %61, %62, %63, %64, %65, %66, %67, %68, %69, %70, %71, %72, %73, %74, %75, %76, %77, %78, %79, %80, %81, %82, %83, %84, %85, %86, %87, %88, %89, %90, %91, %92, %93, %94, %95}, %96, %97, p, 1, 1, 0, 1;\n}\n"
    : "+f"(d[0]), "+f"(d[1]), "+f"(d[2]), "+f"(d[3]), "+f"(d[4]), "+f"(d[5]), "+f"(d[6]), "+f"(d[7]), "+f"(d[8]), "+f"(d[9]), "+f"(d[10]), "+f"(d[11]), "+f"(d[12]), "+f"(d[13]), "+f"(d[14]), "+f"(d[15]), "+f"(d[16]), "+f"(d[17]), "+f"(d[18]), "+f"(d[19]), "+f"(d[20]), "+f"(d[21]), "+f"(d[22]), "+f"(d[23]), "+f"(d[24]), "+f"(d[25]), "+f"(d[26]), "+f"(d[27]), "+f"(d[28]), "+f"(d[29]), "+f"(d[30]), "+f"(d[31]), "+f"(d[32]), "+f"(d[33]), "+f"(d[34]), "+f"(d[35]), "+f"(d[36]), "+f"(d[37]), "+f"(d[38]), "+f"(d[39]), "+f"(d[40]), "+f"(d[41]), "+f"(d[42]), "+f"(d[43]), "+f"(d[44]), "+f"(d[45]), "+f"(d[46]), "+f"(d[47]), "+f"(d[48]), "+f"(d[49]), "+f"(d[50]), "+f"(d[51]), "+f"(d[52]), "+f"(d[53]), "+f"(d[54]), "+f"(d[55]), "+f"(d[56]), "+f"(d[57]), "+f"(d[58]), "+f"(d[59]), "+f"(d[60]), "+f"(d[61]), "+f"(d[62]), "+f"(d[63]), "+f"(d[64]), "+f"(d[65]), "+f"(d[66]), "+f"(d[67]), "+f"(d[68]), "+f"(d[69]), "+f"(d[70]), "+f"(d[71]), "+f"(d[72]), "+f"(d[73]), "+f"(d[74]), "+f"(d[75]), "+f"(d[76]), "+f"(d[77]), "+f"(d[78]), "+f"(d[79]), "+f"(d[80]), "+f"(d[81]), "+f"(d[82]), "+f"(d[83]), "+f"(d[84]), "+f"(d[85]), "+f"(d[86]), "+f"(d[87]), "+f"(d[88]), "+f"(d[89]), "+f"(d[90]), "+f"(d[91]), "+f"(d[92]), "+f"(d[93]), "+f"(d[94]), "+f"(d[95])
    : "l"(da), "l"(db), "r"(sc));
}
__device__ __forceinline__ void wgmma_rs_n128(float (&d)[64], uint32_t a0, uint32_t a1, uint32_t a2, uint32_t a3, uint64_t db, uint32_t sc) {
  asm volatile("{\n.reg .pred p;\nsetp.ne.b32 p, %69, 0;\n"
    "wgmma.mma_async.sync.aligned.m64n128k16.f32.bf16.bf16 "
    "{%0, %1, %2, %3, %4, %5, %6, %7, %8, %9, %10, %11, %12, %13, %14, %15, %16, %17, %18, %19, %20, %21, %22, %23, %24, %25, %26, %27, %28, %29, %30, %31, %32, %33, %34, %35, %36, %37, %38, %39, %40, %41, %42, %43, %44, %45, %46, %47, %48, %49, %50, %51, %52, %53, %54, %55, %56, %57, %58, %59, %60, %61, %62, %63}, {%64, %65, %66, %67}, %68, p, 1, 1, 0;\n}\n"
    : "+f"(d[0]), "+f"(d[1]), "+f"(d[2]), "+f"(d[3]), "+f"(d[4]), "+f"(d[5]), "+f"(d[6]), "+f"(d[7]), "+f"(d[8]), "+f"(d[9]), "+f"(d[10]), "+f"(d[11]), "+f"(d[12]), "+f"(d[13]), "+f"(d[14]), "+f"(d[15]), "+f"(d[16]), "+f"(d[17]), "+f"(d[18]), "+f"(d[19]), "+f"(d[20]), "+f"(d[21]), "+f"(d[22]), "+f"(d[23]), "+f"(d[24]), "+f"(d[25]), "+f"(d[26]), "+f"(d[27]), "+f"(d[28]), "+f"(d[29]), "+f"(d[30]), "+f"(d[31]), "+f"(d[32]), "+f"(d[33]), "+f"(d[34]), "+f"(d[35]), "+f"(d[36]), "+f"(d[37]), "+f"(d[38]), "+f"(d[39]), "+f"(d[40]), "+f"(d[41]), "+f"(d[42]), "+f"(d[43]), "+f"(d[44]), "+f"(d[45]), "+f"(d[46]), "+f"(d[47]), "+f"(d[48]), "+f"(d[49]), "+f"(d[50]), "+f"(d[51]), "+f"(d[52]), "+f"(d[53]), "+f"(d[54]), "+f"(d[55]), "+f"(d[56]), "+f"(d[57]), "+f"(d[58]), "+f"(d[59]), "+f"(d[60]), "+f"(d[61]), "+f"(d[62]), "+f"(d[63])
    : "r"(a0), "r"(a1), "r"(a2), "r"(a3), "l"(db), "r"(sc));
}
__device__ __forceinline__ void wgmma_rs_n128_tb(float (&d)[64], uint32_t a0, uint32_t a1, uint32_t a2, uint32_t a3, uint64_t db, uint32_t sc) {
  asm volatile("{\n.reg .pred p;\nsetp.ne.b32 p, %69, 0;\n"
    "wgmma.mma_async.sync.aligned.m64n128k16.f32.bf16.bf16 "
    "{%0, %1, %2, %3, %4, %5, %6, %7, %8, %9, %10, %11, %12, %13, %14, %15, %16, %17, %18, %19, %20, %21, %22, %23, %24, %25, %26, %27, %28, %29, %30, %31, %32, %33, %34, %35, %36, %37, %38, %39, %40, %41, %42, %43, %44, %45, %46, %47, %48, %49, %50, %51, %52, %53, %54, %55, %56, %57, %58, %59, %60, %61, %62, %63}, {%64, %65, %66, %67}, %68, p, 1, 1, 1;\n}\n"
    : "+f"(d[0]), "+f"(d[1]), "+f"(d[2]), "+f"(d[3]), "+f"(d[4]), "+f"(d[5]), "+f"(d[6]), "+f"(d[7]), "+f"(d[8]), "+f"(d[9]), "+f"(d[10]), "+f"(d[11]), "+f"(d[12]), "+f"(d[13]), "+f"(d[14]), "+f"(d[15]), "+f"(d[16]), "+f"(d[17]), "+f"(d[18]), "+f"(d[19]), "+f"(d[20]), "+f"(d[21]), "+f"(d[22]), "+f"(d[23]), "+f"(d[24]), "+f"(d[25]), "+f"(d[26]), "+f"(d[27]), "+f"(d[28]), "+f"(d[29]), "+f"(d[30]), "+f"(d[31]), "+f"(d[32]), "+f"(d[33]), "+f"(d[34]), "+f"(d[35]), "+f"(d[36]), "+f"(d[37]), "+f"(d[38]), "+f"(d[39]), "+f"(d[40]), "+f"(d[41]), "+f"(d[42]), "+f"(d[43]), "+f"(d[44]), "+f"(d[45]), "+f"(d[46]), "+f"(d[47]), "+f"(d[48]), "+f"(d[49]), "+f"(d[50]), "+f"(d[51]), "+f"(d[52]), "+f"(d[53]), "+f"(d[54]), "+f"(d[55]), "+f"(d[56]), "+f"(d[57]), "+f"(d[58]), "+f"(d[59]), "+f"(d[60]), "+f"(d[61]), "+f"(d[62]), "+f"(d[63])
    : "r"(a0), "r"(a1), "r"(a2), "r"(a3), "l"(db), "r"(sc));
}

#define TS(i) do {} while (0)
#define TR(j, i) do {} while (0)
#define TSS(i, c) do {} while (0)

__device__ __forceinline__ uint32_t wrap12(uint32_t p) { return p >= NSLOT ? p - NSLOT : p; }

#define ONCE(c) _Pragma("unroll 1") for (uint32_t once_ = 0; once_ <= (c).zero; once_++)
struct Cons {
  uint32_t sb;
  uint32_t g, pos;
  uint32_t rel;
  uint32_t nstg;
  uint32_t zero;
  int wg, lane;
  __device__ __forceinline__ void wait_full(uint32_t gg) const { mbar_wait(sb + SM_BAR + B_FULL + (gg & 7) * 8, (gg >> 3) & 1); }
  __device__ __forceinline__ void release(uint32_t gg) const { if (lane < 2) mbar_arrive_cluster(rel + (gg & 7) * 8); }
  __device__ __forceinline__ void stg_acquire() { mbar_wait(sb + SM_BAR + B_SEMPTY + wg * 8, (nstg & 1) ^ 1); nstg++; }
  __device__ __forceinline__ void stg_publish() const {
    fence_async_smem();
    __syncwarp();
    if (lane == 0) mbar_arrive(sb + SM_BAR + B_SFULL + wg * 8);
  }
};

__device__ __forceinline__ void frag_addr(uint32_t& rowoff, uint32_t& xr) {
  const uint32_t t = tid_x();
  rowoff = ((t >> 5) & 3) * 2048 + (t & 15) * 128;
  xr = (((t >> 4) & 1) ^ (t & 7)) << 4;
}
template <int NB, int NR>
__device__ __forceinline__ void stage_boxes(const uint32_t (&r)[NR], int r0, const Cons& c) {
  uint32_t rowoff, xr;
  frag_addr(rowoff, xr);
  const uint32_t stg = c.sb + SM_STG + c.wg * 16384 + rowoff;
#pragma unroll
  for (int b = 0; b < NB; b++)
#pragma unroll
    for (int kb = 0; kb < 4; kb++)
      stsm4(stg + b * 8192 + ((32 * kb) ^ xr), r[r0 + b * 16 + kb * 4], r[r0 + b * 16 + kb * 4 + 1], r[r0 + b * 16 + kb * 4 + 2], r[r0 + b * 16 + kb * 4 + 3]);
  c.stg_publish();
}

template <int N, bool FIRST>
__device__ __forceinline__ void gemm_step(float (&acc)[128], Cons& c) {
  const uint32_t p1 = wrap12(c.pos + 1), p2 = wrap12(c.pos + 2);
  const uint64_t da = mkdesc(c.sb + c.wg * 8192 + c.pos * SLOT, 16, 1024);
  const uint64_t b0 = mkdesc(c.sb + p1 * SLOT, 4096, 1024);
  const uint64_t b1 = mkdesc(c.sb + p2 * SLOT, 4096, 1024);
  c.wait_full(c.g);
  wg_fence();
  if (N == 256) {
    wgmma_ss_n256_tb(acc, da, b0, FIRST ? 0 : 1);
    wgmma_ss_n256_tb(acc, da + 2, b0 + 128, 1);
    wgmma_ss_n256_tb(acc, da + 4, b1, 1);
    wgmma_ss_n256_tb(acc, da + 6, b1 + 128, 1);
  } else {
    wgmma_ss_n192_tb(acc, da, b0, FIRST ? 0 : 1);
    wgmma_ss_n192_tb(acc, da + 2, b0 + 128, 1);
    wgmma_ss_n192_tb(acc, da + 4, b1, 1);
    wgmma_ss_n192_tb(acc, da + 6, b1 + 128, 1);
  }
  wg_commit();
  if (!FIRST) {
    wg_wait<1>();
    c.release(c.g - 1);
  }
  c.g++;
  c.pos = wrap12(p2 + 1);
}

template <int N>
__device__ __forceinline__ void gemm_loop(float (&acc)[128], Cons& c, int nk) {
  gemm_step<N, true>(acc, c);
#pragma unroll 1
  for (int k = 1; k < nk; k++) gemm_step<N, false>(acc, c);
  wg_wait<0>();
  c.release(c.g - 1);
  fence_regs(acc);
}
template <int N, int NB>
__device__ __forceinline__ void gemm_loop_flush(float (&acc)[128], Cons& c, const uint32_t (&pend)[NB * 16], bool flush) {
  gemm_step<N, true>(acc, c);
#pragma unroll 1
  for (int k = 1; k < 16; k++) {
    gemm_step<N, false>(acc, c);
    if (k == 3 && flush) {
      c.stg_acquire();
      stage_boxes<NB>(pend, 0, c);
    }
  }
  wg_wait<0>();
  c.release(c.g - 1);
  fence_regs(acc);
}
template <int NB>
__device__ __forceinline__ void h_epilogue(const float (&acc)[128], Cons& c, uint32_t (&pend)[NB * 16]) {
  uint32_t r[32];
#pragma unroll
  for (int i = 0; i < 32; i++) r[i] = pack_bf16_relu(acc[2 * i], acc[2 * i + 1]);
  c.stg_acquire();
  stage_boxes<2>(r, 0, c);
#pragma unroll
  for (int i = 0; i < NB * 16; i++) pend[i] = pack_bf16_relu(acc[64 + 2 * i], acc[65 + 2 * i]);
}

__device__ __forceinline__ uint32_t silu2(uint32_t f2) {
  const float a = bf_lo(f2), b = bf_hi(f2);
  return pack_bf16(a * rcp(1.0f + ex2(-1.4426950408889634f * a)), b * rcp(1.0f + ex2(-1.4426950408889634f * b)));
}

constexpr float SM_C = 0.08838834764831845f * 1.4426950408889634f;

__device__ __forceinline__ void row_max2(const float (&S)[64], float& n0, float& n1) {
  float x[4], y[4];
#pragma unroll
  for (int i = 0; i < 4; i++) { x[i] = fmaxf(S[4 * i], S[4 * i + 1]); y[i] = fmaxf(S[4 * i + 2], S[4 * i + 3]); }
#pragma unroll
  for (int i = 4; i < 16; i++) {
    x[i & 3] = fmaxf(x[i & 3], fmaxf(S[4 * i], S[4 * i + 1]));
    y[i & 3] = fmaxf(y[i & 3], fmaxf(S[4 * i + 2], S[4 * i + 3]));
  }
  n0 = fmaxf(fmaxf(x[0], x[1]), fmaxf(x[2], x[3]));
  n1 = fmaxf(fmaxf(y[0], y[1]), fmaxf(y[2], y[3]));
  n0 = fmaxf(n0, __shfl_xor_sync(~0u, n0, 1));
  n1 = fmaxf(n1, __shfl_xor_sync(~0u, n1, 1));
  n0 = fmaxf(n0, __shfl_xor_sync(~0u, n0, 2));
  n1 = fmaxf(n1, __shfl_xor_sync(~0u, n1, 2));
}
__device__ __forceinline__ void to_exponent(float (&S)[64], float cc0, float cc1) {
#pragma unroll
  for (int i = 0; i < 16; i++) {
    S[4 * i] = fmaf(S[4 * i], SM_C, cc0); S[4 * i + 1] = fmaf(S[4 * i + 1], SM_C, cc0);
    S[4 * i + 2] = fmaf(S[4 * i + 2], SM_C, cc1); S[4 * i + 3] = fmaf(S[4 * i + 3], SM_C, cc1);
  }
}
__device__ __forceinline__ void scale_o(float (&O)[64], float f0, float f1) {
#pragma unroll
  for (int i = 0; i < 16; i++) { O[4 * i] *= f0; O[4 * i + 1] *= f0; O[4 * i + 2] *= f1; O[4 * i + 3] *= f1; }
}
template <int G0>
__device__ __forceinline__ void exp_pack(const float (&S)[64], uint32_t (&p)[32], float (&a)[4]) {
#pragma unroll
  for (int i = G0; i < 16; i++) {
    const float e0 = ex2(S[4 * i]), e1 = ex2(S[4 * i + 1]), e2 = ex2(S[4 * i + 2]), e3 = ex2(S[4 * i + 3]);
    a[0] += e0; a[1] += e1; a[2] += e2; a[3] += e3;
    p[2 * i] = pack_bf16(e0, e1);
    p[2 * i + 1] = pack_bf16(e2, e3);
  }
}
#define EARLY 4
__device__ __forceinline__ void softmax_early(float (&S)[64], float cc0, float cc1, float (&a)[4], uint32_t (&pe)[2 * EARLY + 1], const Cons& c) {
  a[0] = a[1] = a[2] = a[3] = 0.f;
  ONCE(c) {
    to_exponent(S, cc0, cc1);
#pragma unroll
    for (int i = 0; i < EARLY; i++) {
      const float e0 = ex2(S[4 * i]), e1 = ex2(S[4 * i + 1]), e2 = ex2(S[4 * i + 2]), e3 = ex2(S[4 * i + 3]);
      a[0] += e0; a[1] += e1; a[2] += e2; a[3] += e3;
      pe[2 * i] = pack_bf16(e0, e1);
      pe[2 * i + 1] = pack_bf16(e2, e3);
    }
  }
}
__device__ __forceinline__ void softmax_late(float (&S)[64], uint32_t (&p)[32], float (&O)[64], float& cc0, float& cc1, float& l0, float& l1,
                                             float (&a)[4], const uint32_t (&pe)[2 * EARLY + 1], uint32_t zero) {
#pragma unroll
  for (int i = 0; i < 2 * EARLY; i++) p[i] = pe[i] ^ zero;
  exp_pack<EARLY>(S, p, a);
  if (__any_sync(~0u, !(fmaxf(a[0] + a[1], a[2] + a[3]) <= 65536.f))) {
    float d0, d1;
    row_max2(S, d0, d1);
    d0 = fmaxf(d0, 0.f); d1 = fmaxf(d1, 0.f);
#pragma unroll
    for (int i = 0; i < 16; i++) { S[4 * i] -= d0; S[4 * i + 1] -= d0; S[4 * i + 2] -= d1; S[4 * i + 3] -= d1; }
    cc0 -= d0; cc1 -= d1;
    const float f0 = ex2(-d0), f1 = ex2(-d1);
    scale_o(O, f0, f1);
    l0 *= f0; l1 *= f1;
    a[0] = a[1] = a[2] = a[3] = 0.f;
    exp_pack<0>(S, p, a);
  }
  l0 += a[0] + a[1];
  l1 += a[2] + a[3];
}

__device__ __forceinline__ void inv_rowsum(float l0, float l1, float& i0, float& i1) {
  l0 += __shfl_xor_sync(~0u, l0, 1); l1 += __shfl_xor_sync(~0u, l1, 1);
  l0 += __shfl_xor_sync(~0u, l0, 2); l1 += __shfl_xor_sync(~0u, l1, 2);
  i0 = rcp(l0); i1 = rcp(l1);
}
__device__ __forceinline__ void write_o(const float (&O)[64], const Cons& c) {
  uint32_t rowoff, xr;
  frag_addr(rowoff, xr);
  const uint32_t stg = c.sb + SM_STG + c.wg * 16384 + rowoff;
#pragma unroll
  for (int kb = 0; kb < 8; kb++)
    stsm4(stg + (kb >> 2) * 8192 + ((32 * (kb & 3)) ^ xr),
          pack_bf16(O[8 * kb], O[8 * kb + 1]), pack_bf16(O[8 * kb + 2], O[8 * kb + 3]),
          pack_bf16(O[8 * kb + 4], O[8 * kb + 5]), pack_bf16(O[8 * kb + 6], O[8 * kb + 7]));
  c.stg_publish();
}

__device__ __forceinline__ void issue_qk(float (&S)[64], const uint32_t (&q)[32], uint32_t s0, uint32_t s1, uint32_t zero) {
  const uint64_t d0 = mkdesc(s0, 16, 1024), d1 = mkdesc(s1, 16, 1024);
#pragma unroll
  for (int kk = 0; kk < 8; kk++)
    wgmma_rs_n128(S, q[4 * kk], q[4 * kk + 1], q[4 * kk + 2], q[4 * kk + 3], (kk < 4 ? d0 : d1) + (kk & 3) * 2, kk > 0 ? 1u : zero);
}
__device__ __forceinline__ void issue_pv(float (&O)[64], const uint32_t (&p)[32], uint32_t s0, uint32_t s1, uint32_t accum) {
  const uint64_t d0 = mkdesc(s0, 8192, 1024), d1 = mkdesc(s1, 8192, 1024);
#pragma unroll
  for (int kk = 0; kk < 8; kk++)
    wgmma_rs_n128_tb(O, p[4 * kk], p[4 * kk + 1], p[4 * kk + 2], p[4 * kk + 3], (kk < 4 ? d0 : d1) + (kk & 3) * 128, kk > 0 ? 1u : accum);
}

#define TURN_SYNC()   bar_sync(1 + c.wg, 256)
#define TURN_PASS()   bar_arrive(2 - c.wg, 256)

__device__ __forceinline__ void attn_tile(const float (&acc)[128], Cons& c, int t) {
  uint32_t q[32], p[32];
  float S[64], O[64];
  const uint32_t stash = c.sb + SM_STG + c.wg * 16384 + ((threadIdx.x >> 5) & 3) * 2048 + c.lane * 16;
#pragma unroll
  for (int i = 0; i < 32; i++) q[i] = pack_bf16(acc[2 * i], acc[2 * i + 1]);
  c.stg_acquire();
#pragma unroll
  for (int i = 0; i < 8; i++)
    sts128(stash + (i >> 2) * 8192 + (i & 3) * 512, pack_bf16(acc[64 + 8 * i], acc[65 + 8 * i]), pack_bf16(acc[66 + 8 * i], acc[67 + 8 * i]),
           pack_bf16(acc[68 + 8 * i], acc[69 + 8 * i]), pack_bf16(acc[70 + 8 * i], acc[71 + 8 * i]));
  fence_regs(q);
  TR(0, 0);
  TURN_SYNC();
  TR(0, 1);
  c.wait_full(c.g);
  wg_fence();
  issue_qk(O, q, c.sb + c.pos * SLOT, c.sb + wrap12(c.pos + 1) * SLOT, 0);
  wg_commit();
  c.wait_full(c.g + 1);
  wg_fence();
  issue_qk(S, q, c.sb + wrap12(c.pos + 2) * SLOT, c.sb + wrap12(c.pos + 3) * SLOT, 0);
  wg_commit();
  TURN_PASS();
  TR(0, 2);
  wg_wait<1>();
  TR(0, 3);
  fence_regs(O);
  c.release(c.g);
  float cc0, cc1, l0, l1, f0 = 0.f, f1 = 0.f;
  float a[4] = {0.f, 0.f, 0.f, 0.f};
  uint32_t pe[2 * EARLY + 1];
  row_max2(O, cc0, cc1);
  cc0 *= -SM_C; cc1 *= -SM_C;
  ONCE(c) { to_exponent(O, cc0, cc1); }
  wg_wait<0>();
  fence_regs(S);
  fence_regs(q);
  c.release(c.g + 1);
  exp_pack<0>(O, p, a);
  l0 = a[0] + a[1];
  l1 = a[2] + a[3];
  c.pos = wrap12(c.pos + 4);
  TR(1, 0);
  TURN_SYNC();
  TR(1, 1);
  c.wait_full(c.g + 2);
  wg_fence();
  issue_pv(O, p, c.sb + c.pos * SLOT, c.sb + wrap12(c.pos + 1) * SLOT, 0);
  wg_commit();
  TURN_PASS();
  TR(1, 2);
  softmax_early(S, cc0, cc1, a, pe, c);
  TR(1, 4);
  wg_wait<0>();
  TR(1, 5);
  fence_regs(O);
  fence_regs(p);
  c.release(c.g + 2);
  c.g += 3;
  c.pos = wrap12(c.pos + 2);
  softmax_late(S, p, O, cc0, cc1, l0, l1, a, pe, c.zero);
#pragma unroll 1
  for (int j = 1; j < 7 + (int)c.zero; j++) {
    const uint32_t k0 = c.pos, k1 = wrap12(k0 + 1), v0 = wrap12(k0 + 2), v1 = wrap12(k0 + 3);
    TR(j + 1, 0);
    TURN_SYNC();
    TR(j + 1, 1);
    c.wait_full(c.g);
    wg_fence();
    issue_qk(S, q, c.sb + k0 * SLOT, c.sb + k1 * SLOT, 0);
    wg_commit();
    if (j == 4) {
      scale_o(O, f0, f1);
      write_o(O, c);
    }
    c.wait_full(c.g + 1);
    wg_fence();
    issue_pv(O, p, c.sb + v0 * SLOT, c.sb + v1 * SLOT, j != 4);
    wg_commit();
    TURN_PASS();
    TR(j + 1, 2);
    wg_wait<1>();
    TR(j + 1, 3);
    fence_regs(S);
    fence_regs(q);
    c.release(c.g);
    if (j == 3) {
      row_max2(S, cc0, cc1);
      cc0 *= -SM_C; cc1 *= -SM_C;
      inv_rowsum(l0, l1, f0, f1);
      l0 = 0.f; l1 = 0.f;
    }
    softmax_early(S, cc0, cc1, a, pe, c);
    if (j == 2) {
#pragma unroll
      for (int i = 0; i < 8; i++) lds128(stash + (i >> 2) * 8192 + (i & 3) * 512, q[4 * i], q[4 * i + 1], q[4 * i + 2], q[4 * i + 3]);
      __syncwarp();
    }
    TR(j + 1, 4);
    wg_wait<0>();
    TR(j + 1, 5);
    fence_regs(O);
    fence_regs(p);
    c.release(c.g + 1);
    c.g += 2;
    c.pos = wrap12(v1 + 1);
    softmax_late(S, p, O, cc0, cc1, l0, l1, a, pe, c.zero);
  }
  TR(8, 0);
  TURN_SYNC();
  TR(8, 1);
  c.wait_full(c.g);
  wg_fence();
  issue_pv(O, p, c.sb + c.pos * SLOT, c.sb + wrap12(c.pos + 1) * SLOT, 1);
  wg_commit();
  TURN_PASS();
  TR(8, 2);
  c.stg_acquire();
  float a0, a1;
  inv_rowsum(l0, l1, a0, a1);
  wg_wait<0>();
  TR(8, 5);
  fence_regs(O);
  fence_regs(p);
  c.release(c.g);
  c.g++;
  c.pos = wrap12(c.pos + 2);
  scale_o(O, a0, a1);
  write_o(O, c);
  TR(9, 0);
}

struct Prod {
  uint32_t sb, g, pos, head, tail_g, tail_pos, hist;
  __device__ __forceinline__ uint32_t full() const { return sb + SM_BAR + B_FULL + (g & 7) * 8; }
  __device__ __forceinline__ uint32_t slot(uint32_t i) const { return sb + wrap12(pos + i) * SLOT; }
  __device__ __forceinline__ void acquire(uint32_t size) {
#pragma unroll 1
    while (head + size - tail_pos > NSLOT) {
      mbar_wait(sb + SM_BAR + B_EMPTY + (tail_g & 7) * 8, (tail_g >> 3) & 1);
      tail_pos += 2 + ((hist >> (tail_g & 31)) & 1);
      tail_g++;
    }
    hist = (hist & ~(1u << (g & 31))) | ((size - 2) << (g & 31));
  }
  __device__ __forceinline__ void advance(uint32_t size) { g++; head += size; pos = wrap12(pos + size); }
};

__device__ __forceinline__ void wait_flag(const unsigned* p, unsigned target) {
  while ((int)(ld_acquire(p) - target) < 0) {}
  fence_async_all();
}

__device__ __forceinline__ void init_barriers(uint32_t sb, int warp) {
  const uint32_t cnt = warp < 4 ? 1 : warp < 8 ? 16 : warp == 8 ? 4 : warp == 9 ? 1 : 11;
  if (warp < 11) mbar_init(sb + SM_BAR + warp * 16, cnt);
  if (warp < 10) mbar_init(sb + SM_BAR + warp * 16 + 8, cnt);
  asm volatile("fence.mbarrier_init.release.cluster;" ::: "memory");
}

#define TSP(i) do {} while (0)

__global__ void __cluster_dims__(2, 1, 1) __launch_bounds__(384, 1) fused_kernel(const __grid_constant__ Params P) {
  extern __shared__ uint8_t smem_raw[];
  const uint32_t sb = (smem_u32(smem_raw) + 1023u) & ~1023u;
  const int warp = __shfl_sync(~0u, (int)(threadIdx.x >> 5), 0);
  const int lane = threadIdx.x & 31;
  const int rank = blockIdx.x & 1;
  const int cl = blockIdx.x >> 1;
  const int j = cl >> 3;
  const int rb = (cl & 7) * 2 + rank;
  const bool is_s = j < 4, spare = j == 8;
  const int row0 = rb * 128;
  Flags* fl = P.flags;

  if (warp >= 8) {
    unsigned ep0 = 0;
    if (warp == 8) asm volatile("ld.volatile.global.u32 %0, [%1];" : "=r"(ep0) : "l"(&fl->epoch[blockIdx.x]));
    if (lane == 0) {
      if (warp == 8) prefetch_map(spare ? &P.w1b4 : &P.w1b3);
      if (warp == 9) prefetch_map(&P.act_ld);
      init_barriers(sb, warp);
    }
    __syncwarp();
    cluster_arrive();
    if (warp == 10 && lane == 0) {
      prefetch_map(&P.act_st); prefetch_map(&P.wq); prefetch_map(&P.k_ld); prefetch_map(&P.v_ld);
      prefetch_map(is_s ? &P.wo : &P.w2); prefetch_map(&P.x_ld); prefetch_map(&P.out_st);
    }
    __syncwarp();
    cluster_wait();
    asm volatile("setmaxnreg.dec.sync.aligned.u32 24;");
    if (warp == 8) {
      TSP(17);
#define ep1 (ep0 + 1)
      Prod p{sb, 0, 0, 0, 0, 0, 0};
#define LDA(dst, m, bar, c0, c1) tma_ld2(dst, m, bar, c0, c1)
#define LDW1(dst, m, bar, c0, c1, c2) tma_ld3_mc(dst, m, bar, c0, c1, c2)
#define LDW(dst, m, bar, c0, c1, c2) tma_ld3_mc(dst, m, bar, c0, c1, c2)
      {
        const CUtensorMap* mb = spare ? &P.w1b4 : &P.w1b3;
        const uint32_t bytes = spare ? 49152 : 40960;
        const int nt = spare ? 8 : 2;
#pragma unroll 1
        for (int t = 0; t < nt; t++) {
          const int r = spare ? ((cl & 1) * 4 + (t >> 1)) * 2 + rank : rb;
          const int nb0 = spare ? (H_SPARE0 >> 6) + (t & 1) * 4 : j * 6 + t * 3;
          int k = 0;
          if (t == 0) {
#pragma unroll 1
            for (; k < 4; k++) {
              p.acquire(3);
              if (lane == 0) { mbar_expect_tx(p.full(), bytes); LDW1(p.slot(1 + rank), mb, p.full(), 0, k * 64 + rank * 32, nb0); }
              p.advance(3);
            }
            TSP(14);
            asm volatile("" : "+r"(ep0));
            wait_flag(&fl->ln[r][0], ep1 * 64);
            TSP(15);
            if (lane == 0)
              for (int i = 0; i < 4; i++) tma_ld2(sb + i * 3 * SLOT, &P.act_ld, sb + SM_BAR + B_FULL + i * 8, C_XN + i * 64, r * 128);
          } else if (spare && !(t & 1)) {
            wait_flag(&fl->ln[r][0], ep1 * 64);
          }
#pragma unroll 1
          for (; k < 16; k++) {
            p.acquire(3);
            if (lane == 0) {
              mbar_expect_tx(p.full(), bytes);
              LDW1(p.slot(1 + rank), mb, p.full(), 0, k * 64 + rank * 32, nb0);
              tma_ld2(p.slot(0), &P.act_ld, p.full(), C_XN + k * 64, r * 128);
            }
            p.advance(3);
          }
        }
      }
      if (!spare) {
        const int kvrow = (j >> 1) * SK + KV0;
#pragma unroll 1
        for (int t = 0; t < 2; t++) {
          const int nb0 = (4 * j + 2 * t) * 2;
#pragma unroll 1
          for (int k = 0; k < 16; k++) {
            p.acquire(3);
            if (lane == 0) {
              mbar_expect_tx(p.full(), 49152);
              LDW1(p.slot(1 + rank), &P.wq, p.full(), 0, k * 64 + rank * 32, nb0);
              tma_ld2(p.slot(0), &P.act_ld, p.full(), C_XN + k * 64, row0);
            }
            p.advance(3);
          }
#pragma unroll 1
          for (int i = 0; i < 16; i++) {
            const bool is_k = i == 0 || (i < 15 && (i & 1));
            const int ch = (is_k ? ((i + 1) >> 1) : (i == 15 ? 7 : (i >> 1) - 1)) & 3;
            p.acquire(2);
            if (lane == 0) {
              mbar_expect_tx(p.full(), 32768);
              if (is_k) tma_ld2_mc(p.slot(rank), &P.k_ld, p.full(), rank * 64, kvrow + ch * 128);
              else      tma_ld3_mc(p.slot(rank), &P.v_ld, p.full(), 0, kvrow + ch * 128 + rank * 64, 0);
            }
            p.advance(2);
            if (t == 1 && i == 4 && !is_s) wait_flag(&fl->h[rb][0], ep1 * 64);
          }
        }
        const int jn = j & 3;
        if (is_s) {
          unsigned ready = 0;
#pragma unroll 1
          for (int i = 0; i < 64; i++) {
            const int hi = i >> 1;
            const int head = 4 * ((hi & 15) >> 1) + (hi & 1) + ((hi >> 4) << 1);
            const int kc = head * 128 + (i & 1) * 64;
            p.acquire(3);
            if (lane == 0) { mbar_expect_tx(p.full(), 49152); LDW(p.slot(1 + rank), &P.wo, p.full(), 0, kc + rank * 32, jn * 4); }
            if (!((ready >> head) & 1)) {
              do { ready = __ballot_sync(~0u, (int)(ld_acquire(&fl->o[rb][lane]) - ep1 * 2) >= 0); } while (!((ready >> head) & 1));
              __syncwarp();
              fence_async_all();
            }
            if (lane == 0) LDA(p.slot(0), &P.act_ld, p.full(), C_O + kc, row0);
            if (i == 52) {
              if (lane == 0) { prefetch_map(&P.x_ld); prefetch_map(&P.out_st); }
              if (lane < 4) tma_pf2(&P.x_ld, jn * 256 + lane * 64, row0);
            }
            p.advance(3);
          }
#pragma unroll 1
          for (int i = 0; i < 4; i++) {
            if (i == 2) { TSP(20); wait_flag(&fl->g[rb][jn], ep1 * 4); TSP(21); }
            p.acquire(2);
            if (lane == 0) {
              mbar_expect_tx(p.full(), 32768);
              const CUtensorMap* m = i < 2 ? &P.x_ld : &P.act_ld;
              const int c0 = (i < 2 ? 0 : C_G) + jn * 256 + (i & 1) * 128;
              tma_ld2(p.slot(0), m, p.full(), c0, row0);
              tma_ld2(p.slot(1), m, p.full(), c0 + 64, row0);
            }
            p.advance(2);
          }
        } else {
#pragma unroll 1
          for (int k = 0; k < 56; k++) {
            p.acquire(3);
            if (lane == 0) { mbar_expect_tx(p.full(), 49152); LDW(p.slot(1 + rank), &P.w2, p.full(), 0, k * 64 + rank * 32, jn * 4); }
            if (k == H_SPARE0 / 64) wait_flag(&fl->h[rb][16], ep1 * 8);
            if (lane == 0) LDA(p.slot(0), &P.act_ld, p.full(), C_H + k * 64, row0);
            p.advance(3);
          }
        }
      }
      if (lane == 0) { *(volatile unsigned*)&fl->epoch[blockIdx.x] = ep1; mbar_arrive(sb + SM_BAR + B_DONE); }
    } else if (warp < 11) {
      const int wg = warp - 9;
      if (lane == 0) {
        const uint32_t stg = sb + SM_STG + wg * 16384;
        const int nev = spare ? 16 : is_s ? 8 : 10;
#pragma unroll 1
        for (int n = 0; n < nev; n++) {
          int col, row = row0, nbox = 2;
          unsigned* flag;
          if (spare) {
            const int r = ((cl & 1) * 4 + (n >> 2)) * 2 + rank;
            row = r * 128;
            col = C_H + H_SPARE0 + (n & 3) * 128;
            flag = &fl->h[r][16];
          } else if (n < 4) {
            col = C_H + j * H_REG + (n >> 1) * 192 + (n & 1) * 128;
            nbox = 2 - (n & 1);
            flag = &fl->h[rb][0];
          } else if (n < 8) {
            col = C_O + (4 * j + n - 4) * 128;
            flag = &fl->o[rb][4 * j + n - 4];
          } else {
            col = C_G + (j & 3) * 256 + (n - 8) * 128;
            flag = &fl->g[rb][j & 3];
          }
          mbar_wait(sb + SM_BAR + B_SFULL + wg * 8, n & 1);
          if (n == 9 && wg == 0) TSP(20);
          tma_st2(&P.act_st, stg, col, row + wg * 64);
          if (nbox == 2) tma_st2(&P.act_st, stg + 8192, col + 64, row + wg * 64);
          bulk_commit();
          bulk_wait_read0();
          mbar_arrive(sb + SM_BAR + B_SEMPTY + wg * 8);
          if (n == 9 && wg == 0) TSP(21);
          bulk_wait0();
          if (n == 9 && wg == 0) TSP(22);
          red_release(flag, 1);
          if (n == 9 && wg == 0) TSP(23);
        }
        mbar_arrive(sb + SM_BAR + B_DONE);
      }
    } else {
      if (lane == 0) {
        const unsigned long long t0 = gtime();
        while (!mbar_try(sb + SM_BAR + B_DONE, 0)) {
          if (gtime() - t0 > 2000000000ull) __trap();
        }
      }
    }
    __syncwarp();
    cluster_arrive();
    cluster_wait();
  } else {
    const int wg = warp >> 2;
    TS(0);
    if (!spare) {
      const int r = row0 + j * 16 + warp * 2;
      uint32_t v[2][16];
#pragma unroll
      for (int a = 0; a < 2; a++)
#pragma unroll
        for (int i = 0; i < 4; i++)
          *(uint4*)&v[a][4 * i] = __ldg((const uint4*)(P.x + (size_t)(r + a) * DM + i * 256 + lane * 8));
      if (lane == 0) init_barriers(sb, warp);
      __syncwarp();
      cluster_arrive();
      float s[2], q[2];
#pragma unroll
      for (int a = 0; a < 2; a++) {
        float t0 = 0.f, t1 = 0.f;
#pragma unroll
        for (int i = 0; i < 16; i++) { t0 += bf_lo(v[a][i]); t1 += bf_hi(v[a][i]); }
        s[a] = t0 + t1;
      }
#pragma unroll
      for (int o = 16; o; o >>= 1) { s[0] += __shfl_xor_sync(~0u, s[0], o); s[1] += __shfl_xor_sync(~0u, s[1], o); }
#pragma unroll
      for (int a = 0; a < 2; a++) {
        s[a] *= 1.0f / DM;
        float t0 = 0.f, t1 = 0.f;
#pragma unroll
        for (int i = 0; i < 16; i++) {
          const float d0 = bf_lo(v[a][i]) - s[a], d1 = bf_hi(v[a][i]) - s[a];
          t0 = fmaf(d0, d0, t0); t1 = fmaf(d1, d1, t1);
        }
        q[a] = t0 + t1;
      }
#pragma unroll
      for (int o = 16; o; o >>= 1) { q[0] += __shfl_xor_sync(~0u, q[0], o); q[1] += __shfl_xor_sync(~0u, q[1], o); }
#pragma unroll
      for (int a = 0; a < 2; a++) {
        const uint32_t mb2 = pack_bf16(s[a], s[a]);
        const float inv = 1.0f / bf_round(sqrtf(bf_round(bf_round(q[a] * (1.0f / DM)) + 1e-5f)));
#pragma unroll
        for (int i = 0; i < 16; i++) {
          const __nv_bfloat162 d = __hsub2_rn(*(const __nv_bfloat162*)&v[a][i], *(const __nv_bfloat162*)&mb2);
          const uint32_t du = *(const uint32_t*)&d;
          v[a][i] = pack_bf16(bf_lo(du) * inv, bf_hi(du) * inv);
        }
#pragma unroll
        for (int i = 0; i < 4; i++)
          *(uint4*)(P.act + (size_t)(r + a) * ACT_W + C_XN + i * 256 + lane * 8) = *(const uint4*)&v[a][4 * i];
      }
      TS(11);
      fence_async_all();
      TS(12);
      __syncwarp();
      if (lane == 0) red_release(&fl->ln[rb][0], 1);
      TS(13);
    } else {
      if (lane == 0) init_barriers(sb, warp);
      __syncwarp();
      cluster_arrive();
    }
    cluster_wait();
    asm volatile("setmaxnreg.inc.sync.aligned.u32 240;");
    Cons c;
    c.zero = blockIdx.y; c.sb = sb; c.g = 0; c.pos = 0; c.nstg = 0; c.wg = wg; c.lane = lane;
    c.rel = mapa(sb + SM_BAR + B_EMPTY, lane & 1);
    float acc[128];
    TS(1);
    if (spare) {
      uint32_t pend[32];
#pragma unroll
      for (int i = 0; i < 32; i++) pend[i] = 0;
#pragma unroll 1
      for (int t = 0; t < 8; t++) {
        gemm_loop_flush<256, 2>(acc, c, pend, t > 0);
        h_epilogue<2>(acc, c, pend);
      }
      c.stg_acquire();
      stage_boxes<2>(pend, 0, c);
      TS(6);
    } else {
      if (wg == 1) bar_arrive(1, 256);
      {
        uint32_t pend[16];
#pragma unroll
        for (int i = 0; i < 16; i++) pend[i] = 0;
#pragma unroll 1
        for (int t = 0; t < 2; t++) {
          gemm_loop_flush<192, 1>(acc, c, pend, t > 0);
          h_epilogue<1>(acc, c, pend);
          TS(2 + t);
        }
        gemm_loop_flush<256, 1>(acc, c, pend, true);
      }
#pragma unroll 1
      for (int t = 0; t < 2; t++) {
        TS(8 + t);
        attn_tile(acc, c, t);
        TS(4 + t);
        gemm_loop<256>(acc, c, t == 0 ? 16 : is_s ? 64 : 56);
      }
      TS(6);
      uint32_t rowoff, xr;
      frag_addr(rowoff, xr);
      if (is_s) {
        const uint32_t x0 = c.pos;
#pragma unroll
        for (int b = 0; b < 4; b++) {
          if ((b & 1) == 0) { c.wait_full(c.g + (b >> 1)); c.wait_full(c.g + 2 + (b >> 1)); }
          if (b == 0) TS(22);
          if (b == 2) TS(23);
          const uint32_t xs = sb + wrap12(x0 + b) * SLOT + wg * 8192;
          const uint32_t sx = xs + rowoff, sg = sb + wrap12(wrap12(x0 + 4) + b) * SLOT + wg * 8192 + rowoff;
          uint32_t xv[16], gv[16];
#pragma unroll
          for (int kb = 0; kb < 4; kb++) {
            ldsm4(sx + ((32 * kb) ^ xr), xv[4 * kb], xv[4 * kb + 1], xv[4 * kb + 2], xv[4 * kb + 3]);
            ldsm4(sg + ((32 * kb) ^ xr), gv[4 * kb], gv[4 * kb + 1], gv[4 * kb + 2], gv[4 * kb + 3]);
          }
#pragma unroll
          for (int i = 0; i < 16; i++) {
            const uint32_t s2 = pack_bf16(acc[32 * b + 2 * i], acc[32 * b + 2 * i + 1]);
            const __nv_bfloat162 pr = __hmul2_rn(*(const __nv_bfloat162*)&s2, *(const __nv_bfloat162*)&gv[i]);
            const __nv_bfloat162 o = __hadd2_rn(*(const __nv_bfloat162*)&xv[i], pr);
            xv[i] = *(const uint32_t*)&o;
          }
#pragma unroll
          for (int kb = 0; kb < 4; kb++) stsm4(sx + ((32 * kb) ^ xr), xv[4 * kb], xv[4 * kb + 1], xv[4 * kb + 2], xv[4 * kb + 3]);
          if (b & 1) {
            fence_async_smem();
            bar_sync(3 + wg, 128);
            if ((threadIdx.x & 127) == 0) {
              tma_st2(&P.out_st, sb + wrap12(x0 + b - 1) * SLOT + wg * 8192, (j & 3) * 256 + b * 64 - 64, row0 + wg * 64);
              tma_st2(&P.out_st, xs, (j & 3) * 256 + b * 64, row0 + wg * 64);
              bulk_commit();
            }
          }
        }
        TS(24);
        if ((threadIdx.x & 127) == 0) bulk_wait_read0();
      } else {
        const uint32_t stg = sb + SM_STG + wg * 16384 + rowoff;
#pragma unroll
        for (int hh = 0; hh < 2; hh++) {
#pragma unroll
          for (int bx = 0; bx < 2; bx++) {
            uint32_t r[16];
            ONCE(c) {
#pragma unroll
              for (int i = 0; i < 16; i++) r[i] = silu2(pack_bf16(acc[64 * hh + 32 * bx + 2 * i], acc[64 * hh + 32 * bx + 2 * i + 1]) ^ once_);
            }
            if (bx == 0) c.stg_acquire();
#pragma unroll
            for (int kb = 0; kb < 4; kb++) stsm4(stg + bx * 8192 + ((32 * kb) ^ xr), r[4 * kb], r[4 * kb + 1], r[4 * kb + 2], r[4 * kb + 3]);
          }
          c.stg_publish();
          if (hh == 0) TS(22);
        }
      }
    }
    TS(7);
    __syncwarp();
    if (lane == 0) mbar_arrive(sb + SM_BAR + B_DONE);
    cluster_arrive();
    cluster_wait();
  }
}

typedef CUresult (*EncodeFn)(CUtensorMap*, CUtensorMapDataType, cuuint32_t, void*, const cuuint64_t*, const cuuint64_t*,
                             const cuuint32_t*, const cuuint32_t*, CUtensorMapInterleave, CUtensorMapSwizzle,
                             CUtensorMapL2promotion, CUtensorMapFloatOOBfill);

void map2d(EncodeFn enc, CUtensorMap* m, const void* base, uint64_t cols, uint64_t rows, uint32_t box_rows) {
  cuuint64_t dims[2] = {cols, rows};
  cuuint64_t strides[1] = {cols * 2};
  cuuint32_t box[2] = {64, box_rows};
  cuuint32_t es[2] = {1, 1};
  enc(m, CU_TENSOR_MAP_DATA_TYPE_BFLOAT16, 2, (void*)base, dims, strides, box, es, CU_TENSOR_MAP_INTERLEAVE_NONE,
      CU_TENSOR_MAP_SWIZZLE_128B, CU_TENSOR_MAP_L2_PROMOTION_L2_256B, CU_TENSOR_MAP_FLOAT_OOB_FILL_NONE);
}
void map3d(EncodeFn enc, CUtensorMap* m, const void* base, uint64_t cols, uint64_t rows, uint32_t box_rows, uint32_t box_blks) {
  cuuint64_t dims[3] = {64, rows, cols / 64};
  cuuint64_t strides[2] = {cols * 2, 128};
  cuuint32_t box[3] = {64, box_rows, box_blks};
  cuuint32_t es[3] = {1, 1, 1};
  enc(m, CU_TENSOR_MAP_DATA_TYPE_BFLOAT16, 3, (void*)base, dims, strides, box, es, CU_TENSOR_MAP_INTERLEAVE_NONE,
      CU_TENSOR_MAP_SWIZZLE_128B, CU_TENSOR_MAP_L2_PROMOTION_L2_256B, CU_TENSOR_MAP_FLOAT_OOB_FILL_NONE);
}

}

extern "C" void kernel_launch(void* const* d_in, const int* in_sizes, int n_in, void* d_out, int out_size) {
  (void)in_sizes; (void)n_in; (void)out_size;
  static EncodeFn enc = nullptr;
  static void* act = nullptr;
  static void* flags = nullptr;
  if (!enc) {
    void* fn = nullptr;
    cudaDriverEntryPointQueryResult qr;
    cudaGetDriverEntryPoint("cuTensorMapEncodeTiled", &fn, cudaEnableDefault, &qr);
    enc = (EncodeFn)fn;
    cudaGetSymbolAddress(&act, g_act);
    cudaGetSymbolAddress(&flags, g_flags);
    cudaFuncSetAttribute(fused_kernel, cudaFuncAttributeMaxDynamicSharedMemorySize, SMEM_BYTES);
  }
  Params P;
  map2d(enc, &P.act_ld, act, ACT_W, SEQ, 128);
  map2d(enc, &P.act_st, act, ACT_W, SEQ, 64);
  map2d(enc, &P.x_ld, d_in[0], DM, SEQ, 128);
  map2d(enc, &P.out_st, d_out, DM, SEQ, 64);
  map2d(enc, &P.k_ld, d_in[1], 128, 4 * SK, 128);
  map3d(enc, &P.v_ld, d_in[2], 128, 4 * SK, 64, 2);
  map3d(enc, &P.wq, d_in[3], NQ, DM, 32, 4);
  map3d(enc, &P.w1b4, d_in[6], DFF, DM, 32, 4);
  map3d(enc, &P.w1b3, d_in[6], DFF, DM, 32, 3);
  map3d(enc, &P.wo, d_in[4], DM, NQ, 32, 4);
  map3d(enc, &P.w2, d_in[7], DM, DFF, 32, 4);
  P.x = (const __nv_bfloat16*)d_in[0];
  P.act = (__nv_bfloat16*)act;
  P.flags = (Flags*)flags;
  fused_kernel<<<NCLUSTER * 2, 384, SMEM_BYTES>>>(P);
}
```

```cpp
#include <cuda_runtime.h>
#include <cuda_bf16.h>
#include <cuda.h>
#include <stdint.h>

namespace {

constexpr int SEQ    = 2048;
constexpr int DM     = 1024;
constexpr int NQ     = 4096;
constexpr int DFF    = 3584;
constexpr int SK     = 2048;
constexpr int WIN    = 512;
constexpr int KV0    = SK - WIN;
constexpr int C_XN = 0, C_O = 1024, C_H = 5120, C_G = 8704, ACT_W = 9728;

constexpr int H_REG = 384, H_SPARE0 = 8 * H_REG;
static_assert(H_SPARE0 + 512 == DFF, "H split");

constexpr int NSLOT = 12, SLOT = 16384, NBAR = 8;
constexpr int SM_STG = NSLOT * SLOT;
constexpr int SM_BAR = SM_STG + 2 * 16384;
constexpr int SMEM_BYTES = SM_BAR + 256 + 1024;
constexpr int B_FULL = 0, B_EMPTY = 64, B_SFULL = 128, B_SEMPTY = 144, B_DONE = 160;

constexpr int NCLUSTER = 66;

struct Flags {
  unsigned ln[16][32];
  unsigned h[16][32];
  unsigned o[16][32];
  unsigned g[16][32];
  unsigned epoch[160];
};
__device__ __nv_bfloat16 g_act[(size_t)SEQ * ACT_W];
__device__ Flags g_flags;

struct Params {
  CUtensorMap act_ld, act_st, x_ld, out_st, k_ld, v_ld, wq, w1b4, w1b3, wo, w2;
  const __nv_bfloat16* x;
  __nv_bfloat16* act;
  Flags* flags;
};

__device__ __forceinline__ uint32_t smem_u32(const void* p) { return (uint32_t)__cvta_generic_to_shared(p); }
__device__ __forceinline__ void mbar_init(uint32_t bar, uint32_t cnt) {
  asm volatile("mbarrier.init.shared::cta.b64 [%0], %1;" ::"r"(bar), "r"(cnt) : "memory");
}
__device__ __forceinline__ bool mbar_try(uint32_t bar, uint32_t parity) {
  uint32_t ok;
  asm volatile("{\n.reg .pred p;\nmbarrier.try_wait.parity.shared::cta.b64 p, [%1], %2;\nselp.u32 %0, 1, 0, p;\n}\n"
               : "=r"(ok) : "r"(bar), "r"(parity) : "memory");
  return ok;
}
__device__ __forceinline__ void mbar_wait(uint32_t bar, uint32_t parity) {
  asm volatile("{\n.reg .pred p;\nWAIT_%=:\nmbarrier.try_wait.parity.shared::cta.b64 p, [%0], %1;\n@p bra DONE_%=;\nbra WAIT_%=;\nDONE_%=:\n}\n"
               ::"r"(bar), "r"(parity) : "memory");
}
__device__ __forceinline__ void mbar_arrive(uint32_t bar) {
  asm volatile("mbarrier.arrive.shared::cta.b64 _, [%0];" ::"r"(bar) : "memory");
}
__device__ __forceinline__ void mbar_arrive_cluster(uint32_t cluster_addr) {
  asm volatile("mbarrier.arrive.shared::cluster.b64 _, [%0];" ::"r"(cluster_addr) : "memory");
}
__device__ __forceinline__ void mbar_expect_tx(uint32_t bar, uint32_t bytes) {
  asm volatile("mbarrier.arrive.expect_tx.shared::cta.b64 _, [%0], %1;" ::"r"(bar), "r"(bytes) : "memory");
}
__device__ __forceinline__ uint32_t mapa(uint32_t addr, uint32_t rank) {
  uint32_t r;
  asm("mapa.shared::cluster.u32 %0, %1, %2;" : "=r"(r) : "r"(addr), "r"(rank));
  return r;
}
__device__ __forceinline__ void cluster_arrive() { asm volatile("barrier.cluster.arrive.relaxed.aligned;" ::: "memory"); }
__device__ __forceinline__ void cluster_wait() { asm volatile("barrier.cluster.wait.acquire.aligned;" ::: "memory"); }
__device__ __forceinline__ void bar_sync(int id, int n) { asm volatile("bar.sync %0, %1;" ::"r"(id), "r"(n) : "memory"); }
__device__ __forceinline__ void bar_arrive(int id, int n) { asm volatile("bar.arrive %0, %1;" ::"r"(id), "r"(n) : "memory"); }
__device__ __forceinline__ void fence_async_smem() { asm volatile("fence.proxy.async.shared::cta;" ::: "memory"); }
__device__ __forceinline__ void fence_async_all() { asm volatile("fence.proxy.async.global;" ::: "memory"); }

__device__ __forceinline__ void tma_ld2(uint32_t dst, const CUtensorMap* m, uint32_t bar, int c0, int c1) {
  asm volatile("cp.async.bulk.tensor.2d.shared::cluster.global.mbarrier::complete_tx::bytes [%0], [%1, {%3, %4}], [%2];"
               ::"r"(dst), "l"(m), "r"(bar), "r"(c0), "r"(c1) : "memory");
}
__device__ __forceinline__ void tma_ld2_mc(uint32_t dst, const CUtensorMap* m, uint32_t bar, int c0, int c1) {
  asm volatile("cp.async.bulk.tensor.2d.shared::cluster.global.mbarrier::complete_tx::bytes.multicast::cluster [%0], [%1, {%3, %4}], [%2], %5;"
               ::"r"(dst), "l"(m), "r"(bar), "r"(c0), "r"(c1), "h"((uint16_t)3) : "memory");
}
__device__ __forceinline__ void tma_ld3_mc(uint32_t dst, const CUtensorMap* m, uint32_t bar, int c0, int c1, int c2) {
  asm volatile("cp.async.bulk.tensor.3d.shared::cluster.global.mbarrier::complete_tx::bytes.multicast::cluster [%0], [%1, {%3, %4, %5}], [%2], %6;"
               ::"r"(dst), "l"(m), "r"(bar), "r"(c0), "r"(c1), "r"(c2), "h"((uint16_t)3) : "memory");
}
__device__ __forceinline__ void tma_ld3_mc_hint(uint32_t dst, const CUtensorMap* m, uint32_t bar, int c0, int c1, int c2, uint64_t pol) {
  asm volatile("cp.async.bulk.tensor.3d.shared::cluster.global.mbarrier::complete_tx::bytes.multicast::cluster.L2::cache_hint [%0], [%1, {%3, %4, %5}], [%2], %6, %7;"
               ::"r"(dst), "l"(m), "r"(bar), "r"(c0), "r"(c1), "r"(c2), "h"((uint16_t)3), "l"(pol) : "memory");
}
__device__ __forceinline__ void tma_ld2_hint(uint32_t dst, const CUtensorMap* m, uint32_t bar, int c0, int c1, uint64_t pol) {
  asm volatile("cp.async.bulk.tensor.2d.shared::cluster.global.mbarrier::complete_tx::bytes.L2::cache_hint [%0], [%1, {%3, %4}], [%2], %5;"
               ::"r"(dst), "l"(m), "r"(bar), "r"(c0), "r"(c1), "l"(pol) : "memory");
}
__device__ __forceinline__ void tma_st2_hint(const CUtensorMap* m, uint32_t src, int c0, int c1, uint64_t pol) {
  asm volatile("cp.async.bulk.tensor.2d.global.shared::cta.bulk_group.L2::cache_hint [%0, {%2, %3}], [%1], %4;"
               ::"l"(m), "r"(src), "r"(c0), "r"(c1), "l"(pol) : "memory");
}
#define POL_FIRST 0x12F0000000000000ull
__device__ __forceinline__ uint64_t policy_evict_first() {
  uint64_t p;
  asm volatile("createpolicy.fractional.L2::evict_first.b64 %0, 1.0;" : "=l"(p));
  return p;
}
__device__ __forceinline__ void tma_st2(const CUtensorMap* m, uint32_t src, int c0, int c1) {
  asm volatile("cp.async.bulk.tensor.2d.global.shared::cta.bulk_group [%0, {%2, %3}], [%1];"
               ::"l"(m), "r"(src), "r"(c0), "r"(c1) : "memory");
}
__device__ __forceinline__ void tma_pf2(const CUtensorMap* m, int c0, int c1) {
  asm volatile("cp.async.bulk.prefetch.tensor.2d.L2.global [%0, {%1, %2}];" ::"l"(m), "r"(c0), "r"(c1) : "memory");
}
__device__ __forceinline__ void bulk_commit() { asm volatile("cp.async.bulk.commit_group;" ::: "memory"); }
__device__ __forceinline__ void bulk_wait_read0() { asm volatile("cp.async.bulk.wait_group.read 0;" ::: "memory"); }
__device__ __forceinline__ void bulk_wait0() { asm volatile("cp.async.bulk.wait_group 0;" ::: "memory"); }
__device__ __forceinline__ void prefetch_map(const CUtensorMap* m) {
  asm volatile("prefetch.tensormap [%0];" ::"l"(m) : "memory");
}
__device__ __forceinline__ unsigned ld_acquire(const unsigned* p) {
  unsigned v;
  asm volatile("ld.acquire.gpu.global.u32 %0, [%1];" : "=r"(v) : "l"(p) : "memory");
  return v;
}
__device__ __forceinline__ void red_release(unsigned* p, unsigned v) {
  asm volatile("red.release.gpu.global.add.u32 [%0], %1;" ::"l"(p), "r"(v) : "memory");
}
__device__ __forceinline__ void wg_fence() { asm volatile("wgmma.fence.sync.aligned;" ::: "memory"); }
__device__ __forceinline__ void wg_commit() { asm volatile("wgmma.commit_group.sync.aligned;" ::: "memory"); }
template <int N> __device__ __forceinline__ void wg_wait() { asm volatile("wgmma.wait_group.sync.aligned %0;" ::"n"(N) : "memory"); }
template <int N> __device__ __forceinline__ void fence_regs(float (&d)[N]) {
#pragma unroll
  for (int i = 0; i < N; i++) asm volatile("" : "+f"(d[i])::"memory");
}
template <int N> __device__ __forceinline__ void fence_regs(uint32_t (&d)[N]) {
#pragma unroll
  for (int i = 0; i < N; i++) asm volatile("" : "+r"(d[i])::"memory");
}
__device__ __forceinline__ uint64_t mkdesc(uint32_t addr, uint32_t lbo, uint32_t sbo) {
  return (uint64_t)((addr & 0x3FFFF) >> 4) | ((uint64_t)(lbo >> 4) << 16) | ((uint64_t)(sbo >> 4) << 32) | (1ull << 62);
}
__device__ __forceinline__ uint32_t pack_bf16(float lo, float hi) {
  uint32_t r;
  asm("cvt.rn.bf16x2.f32 %0, %1, %2;" : "=r"(r) : "f"(hi), "f"(lo));
  return r;
}
__device__ __forceinline__ uint32_t pack_bf16_relu(float lo, float hi) {
  uint32_t r;
  asm("cvt.rn.relu.bf16x2.f32 %0, %1, %2;" : "=r"(r) : "f"(hi), "f"(lo));
  return r;
}
__device__ __forceinline__ float bf_lo(uint32_t v) { return __uint_as_float(v << 16); }
__device__ __forceinline__ float bf_hi(uint32_t v) { return __uint_as_float(v & 0xFFFF0000u); }
__device__ __forceinline__ float bf_round(float v) { return __bfloat162float(__float2bfloat16_rn(v)); }
__device__ __forceinline__ float ex2(float x) {
  float r;
  asm("ex2.approx.ftz.f32 %0, %1;" : "=f"(r) : "f"(x));
  return r;
}
__device__ __forceinline__ float rcp(float x) {
  float r;
  asm("rcp.approx.ftz.f32 %0, %1;" : "=f"(r) : "f"(x));
  return r;
}
__device__ __forceinline__ uint32_t tid_x() {
  uint32_t t;
  asm volatile("mov.u32 %0, %%tid.x;" : "=r"(t));
  return t;
}
__device__ __forceinline__ void stsm4(uint32_t addr, uint32_t r0, uint32_t r1, uint32_t r2, uint32_t r3) {
  asm volatile("stmatrix.sync.aligned.m8n8.x4.shared.b16 [%0], {%1, %2, %3, %4};" ::"r"(addr), "r"(r0), "r"(r1), "r"(r2), "r"(r3) : "memory");
}
__device__ __forceinline__ void ldsm4(uint32_t addr, uint32_t& r0, uint32_t& r1, uint32_t& r2, uint32_t& r3) {
  asm volatile("ldmatrix.sync.aligned.m8n8.x4.shared.b16 {%0, %1, %2, %3}, [%4];" : "=r"(r0), "=r"(r1), "=r"(r2), "=r"(r3) : "r"(addr) : "memory");
}
__device__ __forceinline__ void sts128(uint32_t addr, uint32_t r0, uint32_t r1, uint32_t r2, uint32_t r3) {
  asm volatile("st.shared.v4.b32 [%0], {%1, %2, %3, %4};" ::"r"(addr), "r"(r0), "r"(r1), "r"(r2), "r"(r3) : "memory");
}
__device__ __forceinline__ void lds128(uint32_t addr, uint32_t& r0, uint32_t& r1, uint32_t& r2, uint32_t& r3) {
  asm volatile("ld.shared.v4.b32 {%0, %1, %2, %3}, [%4];" : "=r"(r0), "=r"(r1), "=r"(r2), "=r"(r3) : "r"(addr) : "memory");
}
__device__ __forceinline__ unsigned long long gtime() {
  unsigned long long t;
  asm volatile("mov.u64 %0, %globaltimer;" : "=l"(t));
  return t;
}

__device__ __forceinline__ void wgmma_ss_n256_tb(float (&d)[128], uint64_t da, uint64_t db, uint32_t sc) {
  asm volatile("{\n.reg .pred p;\nsetp.ne.b32 p, %130, 0;\n"
    "wgmma.mma_async.sync.aligned.m64n256k16.f32.bf16.bf16 "
    "{%0, %1, %2, %3, %4, %5, %6, %7, %8, %9, %10, %11, %12, %13, %14, %15, %16, %17, %18, %19, %20, %21, %22, %23, %24, %25, %26, %27, %28, %29, %30, %31, %32, %33, %34, %35, %36, %37, %38, %39, %40, %41, %42, %43, %44, %45, %46, %47, %48, %49, %50, %51, %52, %53, %54, %55, %56, %57, %58, %59, %60, %61, %62, %63, %64, %65, %66, %67, %68, %69, %70, %71, %72, %73, %74, %75, %76, %77, %78, %79, %80, %81, %82, %83, %84, %85, %86, %87, %88, %89, %90, %91, %92, %93, %94, %95, %96, %97, %98, %99, %100, %101, %102, %103, %104, %105, %106, %107, %108, %109, %110, %111, %112, %113, %114, %115, %116, %117, %118, %119, %120, %121, %122, %123, %124, %125, %126, %127}, %128, %129, p, 1, 1, 0, 1;\n}\n"
    : "+f"(d[0]), "+f"(d[1]), "+f"(d[2]), "+f"(d[3]), "+f"(d[4]), "+f"(d[5]), "+f"(d[6]), "+f"(d[7]), "+f"(d[8]), "+f"(d[9]), "+f"(d[10]), "+f"(d[11]), "+f"(d[12]), "+f"(d[13]), "+f"(d[14]), "+f"(d[15]), "+f"(d[16]), "+f"(d[17]), "+f"(d[18]), "+f"(d[19]), "+f"(d[20]), "+f"(d[21]), "+f"(d[22]), "+f"(d[23]), "+f"(d[24]), "+f"(d[25]), "+f"(d[26]), "+f"(d[27]), "+f"(d[28]), "+f"(d[29]), "+f"(d[30]), "+f"(d[31]), "+f"(d[32]), "+f"(d[33]), "+f"(d[34]), "+f"(d[35]), "+f"(d[36]), "+f"(d[37]), "+f"(d[38]), "+f"(d[39]), "+f"(d[40]), "+f"(d[41]), "+f"(d[42]), "+f"(d[43]), "+f"(d[44]), "+f"(d[45]), "+f"(d[46]), "+f"(d[47]), "+f"(d[48]), "+f"(d[49]), "+f"(d[50]), "+f"(d[51]), "+f"(d[52]), "+f"(d[53]), "+f"(d[54]), "+f"(d[55]), "+f"(d[56]), "+f"(d[57]), "+f"(d[58]), "+f"(d[59]), "+f"(d[60]), "+f"(d[61]), "+f"(d[62]), "+f"(d[63]), "+f"(d[64]), "+f"(d[65]), "+f"(d[66]), "+f"(d[67]), "+f"(d[68]), "+f"(d[69]), "+f"(d[70]), "+f"(d[71]), "+f"(d[72]), "+f"(d[73]), "+f"(d[74]), "+f"(d[75]), "+f"(d[76]), "+f"(d[77]), "+f"(d[78]), "+f"(d[79]), "+f"(d[80]), "+f"(d[81]), "+f"(d[82]), "+f"(d[83]), "+f"(d[84]), "+f"(d[85]), "+f"(d[86]), "+f"(d[87]), "+f"(d[88]), "+f"(d[89]), "+f"(d[90]), "+f"(d[91]), "+f"(d[92]), "+f"(d[93]), "+f"(d[94]), "+f"(d[95]), "+f"(d[96]), "+f"(d[97]), "+f"(d[98]), "+f"(d[99]), "+f"(d[100]), "+f"(d[101]), "+f"(d[102]), "+f"(d[103]), "+f"(d[104]), "+f"(d[105]), "+f"(d[106]), "+f"(d[107]), "+f"(d[108]), "+f"(d[109]), "+f"(d[110]), "+f"(d[111]), "+f"(d[112]), "+f"(d[113]), "+f"(d[114]), "+f"(d[115]), "+f"(d[116]), "+f"(d[117]), "+f"(d[118]), "+f"(d[119]), "+f"(d[120]), "+f"(d[121]), "+f"(d[122]), "+f"(d[123]), "+f"(d[124]), "+f"(d[125]), "+f"(d[126]), "+f"(d[127])
    : "l"(da), "l"(db), "r"(sc));
}
__device__ __forceinline__ void wgmma_ss_n192_tb(float (&d)[128], uint64_t da, uint64_t db, uint32_t sc) {
  asm volatile("{\n.reg .pred p;\nsetp.ne.b32 p, %98, 0;\n"
    "wgmma.mma_async.sync.aligned.m64n192k16.f32.bf16.bf16 "
    "{%0, %1, %2, %3, %4, %5, %6, %7, %8, %9, %10, %11, %12, %13, %14, %15, %16, %17, %18, %19, %20, %21, %22, %23, %24, %25, %26, %27, %28, %29, %30, %31, %32, %33, %34, %35, %36, %37, %38, %39, %40, %41, %42, %43, %44, %45, %46, %47, %48, %49, %50, %51, %52, %53, %54, %55, %56, %57, %58, %59, %60, %61, %62, %63, %64, %65, %66, %67, %68, %69, %70, %71, %72, %73, %74, %75, %76, %77, %78, %79, %80, %81, %82, %83, %84, %85, %86, %87, %88, %89, %90, %91, %92, %93, %94, %95}, %96, %97, p, 1, 1, 0, 1;\n}\n"
    : "+f"(d[0]), "+f"(d[1]), "+f"(d[2]), "+f"(d[3]), "+f"(d[4]), "+f"(d[5]), "+f"(d[6]), "+f"(d[7]), "+f"(d[8]), "+f"(d[9]), "+f"(d[10]), "+f"(d[11]), "+f"(d[12]), "+f"(d[13]), "+f"(d[14]), "+f"(d[15]), "+f"(d[16]), "+f"(d[17]), "+f"(d[18]), "+f"(d[19]), "+f"(d[20]), "+f"(d[21]), "+f"(d[22]), "+f"(d[23]), "+f"(d[24]), "+f"(d[25]), "+f"(d[26]), "+f"(d[27]), "+f"(d[28]), "+f"(d[29]), "+f"(d[30]), "+f"(d[31]), "+f"(d[32]), "+f"(d[33]), "+f"(d[34]), "+f"(d[35]), "+f"(d[36]), "+f"(d[37]), "+f"(d[38]), "+f"(d[39]), "+f"(d[40]), "+f"(d[41]), "+f"(d[42]), "+f"(d[43]), "+f"(d[44]), "+f"(d[45]), "+f"(d[46]), "+f"(d[47]), "+f"(d[48]), "+f"(d[49]), "+f"(d[50]), "+f"(d[51]), "+f"(d[52]), "+f"(d[53]), "+f"(d[54]), "+f"(d[55]), "+f"(d[56]), "+f"(d[57]), "+f"(d[58]), "+f"(d[59]), "+f"(d[60]), "+f"(d[61]), "+f"(d[62]), "+f"(d[63]), "+f"(d[64]), "+f"(d[65]), "+f"(d[66]), "+f"(d[67]), "+f"(d[68]), "+f"(d[69]), "+f"(d[70]), "+f"(d[71]), "+f"(d[72]), "+f"(d[73]), "+f"(d[74]), "+f"(d[75]), "+f"(d[76]), "+f"(d[77]), "+f"(d[78]), "+f"(d[79]), "+f"(d[80]), "+f"(d[81]), "+f"(d[82]), "+f"(d[83]), "+f"(d[84]), "+f"(d[85]), "+f"(d[86]), "+f"(d[87]), "+f"(d[88]), "+f"(d[89]), "+f"(d[90]), "+f"(d[91]), "+f"(d[92]), "+f"(d[93]), "+f"(d[94]), "+f"(d[95])
    : "l"(da), "l"(db), "r"(sc));
}
__device__ __forceinline__ void wgmma_rs_n128(float (&d)[64], uint32_t a0, uint32_t a1, uint32_t a2, uint32_t a3, uint64_t db, uint32_t sc) {
  asm volatile("{\n.reg .pred p;\nsetp.ne.b32 p, %69, 0;\n"
    "wgmma.mma_async.sync.aligned.m64n128k16.f32.bf16.bf16 "
    "{%0, %1, %2, %3, %4, %5, %6, %7, %8, %9, %10, %11, %12, %13, %14, %15, %16, %17, %18, %19, %20, %21, %22, %23, %24, %25, %26, %27, %28, %29, %30, %31, %32, %33, %34, %35, %36, %37, %38, %39, %40, %41, %42, %43, %44, %45, %46, %47, %48, %49, %50, %51, %52, %53, %54, %55, %56, %57, %58, %59, %60, %61, %62, %63}, {%64, %65, %66, %67}, %68, p, 1, 1, 0;\n}\n"
    : "+f"(d[0]), "+f"(d[1]), "+f"(d[2]), "+f"(d[3]), "+f"(d[4]), "+f"(d[5]), "+f"(d[6]), "+f"(d[7]), "+f"(d[8]), "+f"(d[9]), "+f"(d[10]), "+f"(d[11]), "+f"(d[12]), "+f"(d[13]), "+f"(d[14]), "+f"(d[15]), "+f"(d[16]), "+f"(d[17]), "+f"(d[18]), "+f"(d[19]), "+f"(d[20]), "+f"(d[21]), "+f"(d[22]), "+f"(d[23]), "+f"(d[24]), "+f"(d[25]), "+f"(d[26]), "+f"(d[27]), "+f"(d[28]), "+f"(d[29]), "+f"(d[30]), "+f"(d[31]), "+f"(d[32]), "+f"(d[33]), "+f"(d[34]), "+f"(d[35]), "+f"(d[36]), "+f"(d[37]), "+f"(d[38]), "+f"(d[39]), "+f"(d[40]), "+f"(d[41]), "+f"(d[42]), "+f"(d[43]), "+f"(d[44]), "+f"(d[45]), "+f"(d[46]), "+f"(d[47]), "+f"(d[48]), "+f"(d[49]), "+f"(d[50]), "+f"(d[51]), "+f"(d[52]), "+f"(d[53]), "+f"(d[54]), "+f"(d[55]), "+f"(d[56]), "+f"(d[57]), "+f"(d[58]), "+f"(d[59]), "+f"(d[60]), "+f"(d[61]), "+f"(d[62]), "+f"(d[63])
    : "r"(a0), "r"(a1), "r"(a2), "r"(a3), "l"(db), "r"(sc));
}
__device__ __forceinline__ void wgmma_rs_n128_tb(float (&d)[64], uint32_t a0, uint32_t a1, uint32_t a2, uint32_t a3, uint64_t db, uint32_t sc) {
  asm volatile("{\n.reg .pred p;\nsetp.ne.b32 p, %69, 0;\n"
    "wgmma.mma_async.sync.aligned.m64n128k16.f32.bf16.bf16 "
    "{%0, %1, %2, %3, %4, %5, %6, %7, %8, %9, %10, %11, %12, %13, %14, %15, %16, %17, %18, %19, %20, %21, %22, %23, %24, %25, %26, %27, %28, %29, %30, %31, %32, %33, %34, %35, %36, %37, %38, %39, %40, %41, %42, %43, %44, %45, %46, %47, %48, %49, %50, %51, %52, %53, %54, %55, %56, %57, %58, %59, %60, %61, %62, %63}, {%64, %65, %66, %67}, %68, p, 1, 1, 1;\n}\n"
    : "+f"(d[0]), "+f"(d[1]), "+f"(d[2]), "+f"(d[3]), "+f"(d[4]), "+f"(d[5]), "+f"(d[6]), "+f"(d[7]), "+f"(d[8]), "+f"(d[9]), "+f"(d[10]), "+f"(d[11]), "+f"(d[12]), "+f"(d[13]), "+f"(d[14]), "+f"(d[15]), "+f"(d[16]), "+f"(d[17]), "+f"(d[18]), "+f"(d[19]), "+f"(d[20]), "+f"(d[21]), "+f"(d[22]), "+f"(d[23]), "+f"(d[24]), "+f"(d[25]), "+f"(d[26]), "+f"(d[27]), "+f"(d[28]), "+f"(d[29]), "+f"(d[30]), "+f"(d[31]), "+f"(d[32]), "+f"(d[33]), "+f"(d[34]), "+f"(d[35]), "+f"(d[36]), "+f"(d[37]), "+f"(d[38]), "+f"(d[39]), "+f"(d[40]), "+f"(d[41]), "+f"(d[42]), "+f"(d[43]), "+f"(d[44]), "+f"(d[45]), "+f"(d[46]), "+f"(d[47]), "+f"(d[48]), "+f"(d[49]), "+f"(d[50]), "+f"(d[51]), "+f"(d[52]), "+f"(d[53]), "+f"(d[54]), "+f"(d[55]), "+f"(d[56]), "+f"(d[57]), "+f"(d[58]), "+f"(d[59]), "+f"(d[60]), "+f"(d[61]), "+f"(d[62]), "+f"(d[63])
    : "r"(a0), "r"(a1), "r"(a2), "r"(a3), "l"(db), "r"(sc));
}

#define TS(i) do {} while (0)
#define TR(j, i) do {} while (0)
#define TSS(i, c) do {} while (0)

__device__ __forceinline__ uint32_t wrap12(uint32_t p) { return p >= NSLOT ? p - NSLOT : p; }

#define ONCE(c) _Pragma("unroll 1") for (uint32_t once_ = 0; once_ <= (c).zero; once_++)
struct Cons {
  uint32_t sb;
  uint32_t g, pos;
  uint32_t rel;
  uint32_t nstg;
  uint32_t zero;
  int wg, lane;
  __device__ __forceinline__ void wait_full(uint32_t gg) const { mbar_wait(sb + SM_BAR + B_FULL + (gg & 7) * 8, (gg >> 3) & 1); }
  __device__ __forceinline__ void release(uint32_t gg) const { if (lane < 2) mbar_arrive_cluster(rel + (gg & 7) * 8); }
  __device__ __forceinline__ void stg_acquire() { mbar_wait(sb + SM_BAR + B_SEMPTY + wg * 8, (nstg & 1) ^ 1); nstg++; }
  __device__ __forceinline__ void stg_publish() const {
    fence_async_smem();
    __syncwarp();
    if (lane == 0) mbar_arrive(sb + SM_BAR + B_SFULL + wg * 8);
  }
};

__device__ __forceinline__ void frag_addr(uint32_t& rowoff, uint32_t& xr) {
  const uint32_t t = tid_x();
  rowoff = ((t >> 5) & 3) * 2048 + (t & 15) * 128;
  xr = (((t >> 4) & 1) ^ (t & 7)) << 4;
}
template <int NB, int NR>
__device__ __forceinline__ void stage_boxes(const uint32_t (&r)[NR], int r0, const Cons& c) {
  uint32_t rowoff, xr;
  frag_addr(rowoff, xr);
  const uint32_t stg = c.sb + SM_STG + c.wg * 16384 + rowoff;
#pragma unroll
  for (int b = 0; b < NB; b++)
#pragma unroll
    for (int kb = 0; kb < 4; kb++)
      stsm4(stg + b * 8192 + ((32 * kb) ^ xr), r[r0 + b * 16 + kb * 4], r[r0 + b * 16 + kb * 4 + 1], r[r0 + b * 16 + kb * 4 + 2], r[r0 + b * 16 + kb * 4 + 3]);
  c.stg_publish();
}

template <int N, bool FIRST>
__device__ __forceinline__ void gemm_step(float (&acc)[128], Cons& c) {
  const uint32_t p1 = wrap12(c.pos + 1), p2 = wrap12(c.pos + 2);
  const uint64_t da = mkdesc(c.sb + c.wg * 8192 + c.pos * SLOT, 16, 1024);
  const uint64_t b0 = mkdesc(c.sb + p1 * SLOT, 4096, 1024);
  const uint64_t b1 = mkdesc(c.sb + p2 * SLOT, 4096, 1024);
  c.wait_full(c.g);
  wg_fence();
  if (N == 256) {
    wgmma_ss_n256_tb(acc, da, b0, FIRST ? 0 : 1);
    wgmma_ss_n256_tb(acc, da + 2, b0 + 128, 1);
    wgmma_ss_n256_tb(acc, da + 4, b1, 1);
    wgmma_ss_n256_tb(acc, da + 6, b1 + 128, 1);
  } else {
    wgmma_ss_n192_tb(acc, da, b0, FIRST ? 0 : 1);
    wgmma_ss_n192_tb(acc, da + 2, b0 + 128, 1);
    wgmma_ss_n192_tb(acc, da + 4, b1, 1);
    wgmma_ss_n192_tb(acc, da + 6, b1 + 128, 1);
  }
  wg_commit();
  if (!FIRST) {
    wg_wait<1>();
    c.release(c.g - 1);
  }
  c.g++;
  c.pos = wrap12(p2 + 1);
}

template <int N>
__device__ __forceinline__ void gemm_loop(float (&acc)[128], Cons& c, int nk) {
  gemm_step<N, true>(acc, c);
#pragma unroll 1
  for (int k = 1; k < nk; k++) gemm_step<N, false>(acc, c);
  wg_wait<0>();
  c.release(c.g - 1);
  fence_regs(acc);
}
template <int N, int NB>
__device__ __forceinline__ void gemm_loop_flush(float (&acc)[128], Cons& c, const uint32_t (&pend)[NB * 16], bool flush) {
  gemm_step<N, true>(acc, c);
#pragma unroll 1
  for (int k = 1; k < 16; k++) {
    gemm_step<N, false>(acc, c);
    if (k == 3 && flush) {
      c.stg_acquire();
      stage_boxes<NB>(pend, 0, c);
    }
  }
  wg_wait<0>();
  c.release(c.g - 1);
  fence_regs(acc);
}
template <int NB>
__device__ __forceinline__ void h_epilogue(const float (&acc)[128], Cons& c, uint32_t (&pend)[NB * 16]) {
  uint32_t r[32];
#pragma unroll
  for (int i = 0; i < 32; i++) r[i] = pack_bf16_relu(acc[2 * i], acc[2 * i + 1]);
  c.stg_acquire();
  stage_boxes<2>(r, 0, c);
#pragma unroll
  for (int i = 0; i < NB * 16; i++) pend[i] = pack_bf16_relu(acc[64 + 2 * i], acc[65 + 2 * i]);
}

__device__ __forceinline__ uint32_t silu2(uint32_t f2) {
  const float a = bf_lo(f2), b = bf_hi(f2);
  return pack_bf16(a * rcp(1.0f + ex2(-1.4426950408889634f * a)), b * rcp(1.0f + ex2(-1.4426950408889634f * b)));
}

constexpr float SM_C = 0.08838834764831845f * 1.4426950408889634f;

__device__ __forceinline__ void row_max2(const float (&S)[64], float& n0, float& n1) {
  float x[4], y[4];
#pragma unroll
  for (int i = 0; i < 4; i++) { x[i] = fmaxf(S[4 * i], S[4 * i + 1]); y[i] = fmaxf(S[4 * i + 2], S[4 * i + 3]); }
#pragma unroll
  for (int i = 4; i < 16; i++) {
    x[i & 3] = fmaxf(x[i & 3], fmaxf(S[4 * i], S[4 * i + 1]));
    y[i & 3] = fmaxf(y[i & 3], fmaxf(S[4 * i + 2], S[4 * i + 3]));
  }
  n0 = fmaxf(fmaxf(x[0], x[1]), fmaxf(x[2], x[3]));
  n1 = fmaxf(fmaxf(y[0], y[1]), fmaxf(y[2], y[3]));
  n0 = fmaxf(n0, __shfl_xor_sync(~0u, n0, 1));
  n1 = fmaxf(n1, __shfl_xor_sync(~0u, n1, 1));
  n0 = fmaxf(n0, __shfl_xor_sync(~0u, n0, 2));
  n1 = fmaxf(n1, __shfl_xor_sync(~0u, n1, 2));
}
__device__ __forceinline__ void to_exponent(float (&S)[64], float cc0, float cc1) {
#pragma unroll
  for (int i = 0; i < 16; i++) {
    S[4 * i] = fmaf(S[4 * i], SM_C, cc0); S[4 * i + 1] = fmaf(S[4 * i + 1], SM_C, cc0);
    S[4 * i + 2] = fmaf(S[4 * i + 2], SM_C, cc1); S[4 * i + 3] = fmaf(S[4 * i + 3], SM_C, cc1);
  }
}
__device__ __forceinline__ void scale_o(float (&O)[64], float f0, float f1) {
#pragma unroll
  for (int i = 0; i < 16; i++) { O[4 * i] *= f0; O[4 * i + 1] *= f0; O[4 * i + 2] *= f1; O[4 * i + 3] *= f1; }
}
template <int G0>
__device__ __forceinline__ void exp_pack(const float (&S)[64], uint32_t (&p)[32], float (&a)[4]) {
#pragma unroll
  for (int i = G0; i < 16; i++) {
    const float e0 = ex2(S[4 * i]), e1 = ex2(S[4 * i + 1]), e2 = ex2(S[4 * i + 2]), e3 = ex2(S[4 * i + 3]);
    a[0] += e0; a[1] += e1; a[2] += e2; a[3] += e3;
    p[2 * i] = pack_bf16(e0, e1);
    p[2 * i + 1] = pack_bf16(e2, e3);
  }
}
#define EARLY 4
__device__ __forceinline__ void softmax_early(float (&S)[64], float cc0, float cc1, float (&a)[4], uint32_t (&pe)[2 * EARLY + 1], const Cons& c) {
  a[0] = a[1] = a[2] = a[3] = 0.f;
  ONCE(c) {
    to_exponent(S, cc0, cc1);
#pragma unroll
    for (int i = 0; i < EARLY; i++) {
      const float e0 = ex2(S[4 * i]), e1 = ex2(S[4 * i + 1]), e2 = ex2(S[4 * i + 2]), e3 = ex2(S[4 * i + 3]);
      a[0] += e0; a[1] += e1; a[2] += e2; a[3] += e3;
      pe[2 * i] = pack_bf16(e0, e1);
      pe[2 * i + 1] = pack_bf16(e2, e3);
    }
  }
}
__device__ __forceinline__ void softmax_late(float (&S)[64], uint32_t (&p)[32], float (&O)[64], float& cc0, float& cc1, float& l0, float& l1,
                                             float (&a)[4], const uint32_t (&pe)[2 * EARLY + 1], uint32_t zero) {
#pragma unroll
  for (int i = 0; i < 2 * EARLY; i++) p[i] = pe[i] ^ zero;
  exp_pack<EARLY>(S, p, a);
  if (__any_sync(~0u, !(fmaxf(a[0] + a[1], a[2] + a[3]) <= 65536.f))) {
    float d0, d1;
    row_max2(S, d0, d1);
    d0 = fmaxf(d0, 0.f); d1 = fmaxf(d1, 0.f);
#pragma unroll
    for (int i = 0; i < 16; i++) { S[4 * i] -= d0; S[4 * i + 1] -= d0; S[4 * i + 2] -= d1; S[4 * i + 3] -= d1; }
    cc0 -= d0; cc1 -= d1;
    const float f0 = ex2(-d0), f1 = ex2(-d1);
    scale_o(O, f0, f1);
    l0 *= f0; l1 *= f1;
    a[0] = a[1] = a[2] = a[3] = 0.f;
    exp_pack<0>(S, p, a);
  }
  l0 += a[0] + a[1];
  l1 += a[2] + a[3];
}

__device__ __forceinline__ void inv_rowsum(float l0, float l1, float& i0, float& i1) {
  l0 += __shfl_xor_sync(~0u, l0, 1); l1 += __shfl_xor_sync(~0u, l1, 1);
  l0 += __shfl_xor_sync(~0u, l0, 2); l1 += __shfl_xor_sync(~0u, l1, 2);
  i0 = rcp(l0); i1 = rcp(l1);
}
__device__ __forceinline__ void write_o(const float (&O)[64], const Cons& c) {
  uint32_t rowoff, xr;
  frag_addr(rowoff, xr);
  const uint32_t stg = c.sb + SM_STG + c.wg * 16384 + rowoff;
#pragma unroll
  for (int kb = 0; kb < 8; kb++)
    stsm4(stg + (kb >> 2) * 8192 + ((32 * (kb & 3)) ^ xr),
          pack_bf16(O[8 * kb], O[8 * kb + 1]), pack_bf16(O[8 * kb + 2], O[8 * kb + 3]),
          pack_bf16(O[8 * kb + 4], O[8 * kb + 5]), pack_bf16(O[8 * kb + 6], O[8 * kb + 7]));
  c.stg_publish();
}

__device__ __forceinline__ void issue_qk(float (&S)[64], const uint32_t (&q)[32], uint32_t s0, uint32_t s1, uint32_t zero) {
  const uint64_t d0 = mkdesc(s0, 16, 1024), d1 = mkdesc(s1, 16, 1024);
#pragma unroll
  for (int kk = 0; kk < 8; kk++)
    wgmma_rs_n128(S, q[4 * kk], q[4 * kk + 1], q[4 * kk + 2], q[4 * kk + 3], (kk < 4 ? d0 : d1) + (kk & 3) * 2, kk > 0 ? 1u : zero);
}
__device__ __forceinline__ void issue_pv(float (&O)[64], const uint32_t (&p)[32], uint32_t s0, uint32_t s1, uint32_t accum) {
  const uint64_t d0 = mkdesc(s0, 8192, 1024), d1 = mkdesc(s1, 8192, 1024);
#pragma unroll
  for (int kk = 0; kk < 8; kk++)
    wgmma_rs_n128_tb(O, p[4 * kk], p[4 * kk + 1], p[4 * kk + 2], p[4 * kk + 3], (kk < 4 ? d0 : d1) + (kk & 3) * 128, kk > 0 ? 1u : accum);
}

#define TURN_SYNC()   bar_sync(1 + c.wg, 256)
#define TURN_PASS()   bar_arrive(2 - c.wg, 256)

__device__ __forceinline__ void attn_tile(const float (&acc)[128], Cons& c, int t) {
  uint32_t q[32], p[32];
  float S[64], O[64];
  const uint32_t stash = c.sb + SM_STG + c.wg * 16384 + ((threadIdx.x >> 5) & 3) * 2048 + c.lane * 16;
#pragma unroll
  for (int i = 0; i < 32; i++) q[i] = pack_bf16(acc[2 * i], acc[2 * i + 1]);
  c.stg_acquire();
#pragma unroll
  for (int i = 0; i < 8; i++)
    sts128(stash + (i >> 2) * 8192 + (i & 3) * 512, pack_bf16(acc[64 + 8 * i], acc[65 + 8 * i]), pack_bf16(acc[66 + 8 * i], acc[67 + 8 * i]),
           pack_bf16(acc[68 + 8 * i], acc[69 + 8 * i]), pack_bf16(acc[70 + 8 * i], acc[71 + 8 * i]));
  fence_regs(q);
  TR(0, 0);
  TURN_SYNC();
  TR(0, 1);
  c.wait_full(c.g);
  wg_fence();
  issue_qk(O, q, c.sb + c.pos * SLOT, c.sb + wrap12(c.pos + 1) * SLOT, 0);
  wg_commit();
  c.wait_full(c.g + 1);
  wg_fence();
  issue_qk(S, q, c.sb + wrap12(c.pos + 2) * SLOT, c.sb + wrap12(c.pos + 3) * SLOT, 0);
  wg_commit();
  TURN_PASS();
  TR(0, 2);
  wg_wait<1>();
  TR(0, 3);
  fence_regs(O);
  c.release(c.g);
  float cc0, cc1, l0, l1, f0 = 0.f, f1 = 0.f;
  float a[4] = {0.f, 0.f, 0.f, 0.f};
  uint32_t pe[2 * EARLY + 1];
  row_max2(O, cc0, cc1);
  cc0 *= -SM_C; cc1 *= -SM_C;
  ONCE(c) { to_exponent(O, cc0, cc1); }
  wg_wait<0>();
  fence_regs(S);
  fence_regs(q);
  c.release(c.g + 1);
  exp_pack<0>(O, p, a);
  l0 = a[0] + a[1];
  l1 = a[2] + a[3];
  c.pos = wrap12(c.pos + 4);
  TR(1, 0);
  TURN_SYNC();
  TR(1, 1);
  c.wait_full(c.g + 2);
  wg_fence();
  issue_pv(O, p, c.sb + c.pos * SLOT, c.sb + wrap12(c.pos + 1) * SLOT, 0);
  wg_commit();
  TURN_PASS();
  TR(1, 2);
  softmax_early(S, cc0, cc1, a, pe, c);
  TR(1, 4);
  wg_wait<0>();
  TR(1, 5);
  fence_regs(O);
  fence_regs(p);
  c.release(c.g + 2);
  c.g += 3;
  c.pos = wrap12(c.pos + 2);
  softmax_late(S, p, O, cc0, cc1, l0, l1, a, pe, c.zero);
#pragma unroll 1
  for (int j = 1; j < 7 + (int)c.zero; j++) {
    const uint32_t k0 = c.pos, k1 = wrap12(k0 + 1), v0 = wrap12(k0 + 2), v1 = wrap12(k0 + 3);
    TR(j + 1, 0);
    TURN_SYNC();
    TR(j + 1, 1);
    c.wait_full(c.g);
    wg_fence();
    issue_qk(S, q, c.sb + k0 * SLOT, c.sb + k1 * SLOT, 0);
    wg_commit();
    if (j == 4) {
      scale_o(O, f0, f1);
      write_o(O, c);
    }
    c.wait_full(c.g + 1);
    wg_fence();
    issue_pv(O, p, c.sb + v0 * SLOT, c.sb + v1 * SLOT, j != 4);
    wg_commit();
    TURN_PASS();
    TR(j + 1, 2);
    wg_wait<1>();
    TR(j + 1, 3);
    fence_regs(S);
    fence_regs(q);
    c.release(c.g);
    if (j == 3) {
      row_max2(S, cc0, cc1);
      cc0 *= -SM_C; cc1 *= -SM_C;
      inv_rowsum(l0, l1, f0, f1);
      l0 = 0.f; l1 = 0.f;
    }
    softmax_early(S, cc0, cc1, a, pe, c);
    if (j == 2) {
#pragma unroll
      for (int i = 0; i < 8; i++) lds128(stash + (i >> 2) * 8192 + (i & 3) * 512, q[4 * i], q[4 * i + 1], q[4 * i + 2], q[4 * i + 3]);
      __syncwarp();
    }
    TR(j + 1, 4);
    wg_wait<0>();
    TR(j + 1, 5);
    fence_regs(O);
    fence_regs(p);
    c.release(c.g + 1);
    c.g += 2;
    c.pos = wrap12(v1 + 1);
    softmax_late(S, p, O, cc0, cc1, l0, l1, a, pe, c.zero);
  }
  TR(8, 0);
  TURN_SYNC();
  TR(8, 1);
  c.wait_full(c.g);
  wg_fence();
  issue_pv(O, p, c.sb + c.pos * SLOT, c.sb + wrap12(c.pos + 1) * SLOT, 1);
  wg_commit();
  TURN_PASS();
  TR(8, 2);
  c.stg_acquire();
  float a0, a1;
  inv_rowsum(l0, l1, a0, a1);
  wg_wait<0>();
  TR(8, 5);
  fence_regs(O);
  fence_regs(p);
  c.release(c.g);
  c.g++;
  c.pos = wrap12(c.pos + 2);
  scale_o(O, a0, a1);
  write_o(O, c);
  TR(9, 0);
}

struct Prod {
  uint32_t sb, g, pos, head, tail_g, tail_pos, hist;
  __device__ __forceinline__ uint32_t full() const { return sb + SM_BAR + B_FULL + (g & 7) * 8; }
  __device__ __forceinline__ uint32_t slot(uint32_t i) const { return sb + wrap12(pos + i) * SLOT; }
  __device__ __forceinline__ void acquire(uint32_t size) {
#pragma unroll 1
    while (head + size - tail_pos > NSLOT) {
      mbar_wait(sb + SM_BAR + B_EMPTY + (tail_g & 7) * 8, (tail_g >> 3) & 1);
      tail_pos += 2 + ((hist >> (tail_g & 31)) & 1);
      tail_g++;
    }
    hist = (hist & ~(1u << (g & 31))) | ((size - 2) << (g & 31));
  }
  __device__ __forceinline__ void advance(uint32_t size) { g++; head += size; pos = wrap12(pos + size); }
};

__device__ __forceinline__ void wait_flag(const unsigned* p, unsigned target) {
  while ((int)(ld_acquire(p) - target) < 0) {}
  fence_async_all();
}

__device__ __forceinline__ void init_barriers(uint32_t sb, int warp) {
  const uint32_t cnt = warp < 4 ? 1 : warp < 8 ? 16 : warp == 8 ? 4 : warp == 9 ? 1 : 11;
  if (warp < 11) mbar_init(sb + SM_BAR + warp * 16, cnt);
  if (warp < 10) mbar_init(sb + SM_BAR + warp * 16 + 8, cnt);
  asm volatile("fence.mbarrier_init.release.cluster;" ::: "memory");
}

#define TSP(i) do {} while (0)

__global__ void __cluster_dims__(2, 1, 1) __launch_bounds__(384, 1) fused_kernel(const __grid_constant__ Params P) {
  extern __shared__ uint8_t smem_raw[];
  const uint32_t sb = (smem_u32(smem_raw) + 1023u) & ~1023u;
  const int warp = __shfl_sync(~0u, (int)(threadIdx.x >> 5), 0);
  const int lane = threadIdx.x & 31;
  const int rank = blockIdx.x & 1;
  const int cl = blockIdx.x >> 1;
  const int j = cl >> 3;
  const int rb = (cl & 7) * 2 + rank;
  const bool is_s = j < 4, spare = j == 8;
  const int row0 = rb * 128;
  Flags* fl = P.flags;

  if (warp >= 8) {
    unsigned ep0 = 0;
    if (warp == 8) asm volatile("ld.volatile.global.u32 %0, [%1];" : "=r"(ep0) : "l"(&fl->epoch[blockIdx.x]));
    if (lane == 0) {
      if (warp == 8) prefetch_map(spare ? &P.w1b4 : &P.w1b3);
      if (warp == 9) prefetch_map(&P.act_ld);
      init_barriers(sb, warp);
    }
    __syncwarp();
    cluster_arrive();
    if (warp == 10 && lane == 0) {
      prefetch_map(&P.act_st); prefetch_map(&P.wq); prefetch_map(&P.k_ld); prefetch_map(&P.v_ld);
      prefetch_map(is_s ? &P.wo : &P.w2); prefetch_map(&P.x_ld); prefetch_map(&P.out_st);
    }
    __syncwarp();
    cluster_wait();
    asm volatile("setmaxnreg.dec.sync.aligned.u32 24;");
    if (warp == 8) {
      TSP(17);
#define ep1 (ep0 + 1)
      Prod p{sb, 0, 0, 0, 0, 0, 0};
#define LDA(dst, m, bar, c0, c1) tma_ld2(dst, m, bar, c0, c1)
#define LDW1(dst, m, bar, c0, c1, c2) tma_ld3_mc(dst, m, bar, c0, c1, c2)
#define LDW(dst, m, bar, c0, c1, c2) tma_ld3_mc(dst, m, bar, c0, c1, c2)
      {
        const CUtensorMap* mb = spare ? &P.w1b4 : &P.w1b3;
        const uint32_t bytes = spare ? 49152 : 40960;
        const int nt = spare ? 8 : 2;
#pragma unroll 1
        for (int t = 0; t < nt; t++) {
          const int r = spare ? ((cl & 1) * 4 + (t >> 1)) * 2 + rank : rb;
          const int nb0 = spare ? (H_SPARE0 >> 6) + (t & 1) * 4 : j * 6 + t * 3;
          int k = 0;
          if (t == 0) {
#pragma unroll 1
            for (; k < 4; k++) {
              p.acquire(3);
              if (lane == 0) { mbar_expect_tx(p.full(), bytes); LDW1(p.slot(1 + rank), mb, p.full(), 0, k * 64 + rank * 32, nb0); }
              p.advance(3);
            }
            TSP(14);
            asm volatile("" : "+r"(ep0));
            wait_flag(&fl->ln[r][0], ep1 * 64);
            TSP(15);
            if (lane == 0)
              for (int i = 0; i < 4; i++) tma_ld2(sb + i * 3 * SLOT, &P.act_ld, sb + SM_BAR + B_FULL + i * 8, C_XN + i * 64, r * 128);
          } else if (spare && !(t & 1)) {
            wait_flag(&fl->ln[r][0], ep1 * 64);
          }
#pragma unroll 1
          for (; k < 16; k++) {
            p.acquire(3);
            if (lane == 0) {
              mbar_expect_tx(p.full(), bytes);
              LDW1(p.slot(1 + rank), mb, p.full(), 0, k * 64 + rank * 32, nb0);
              tma_ld2(p.slot(0), &P.act_ld, p.full(), C_XN + k * 64, r * 128);
            }
            p.advance(3);
          }
        }
      }
      if (!spare) {
        const int kvrow = (j >> 1) * SK + KV0;
#pragma unroll 1
        for (int t = 0; t < 2; t++) {
          const int nb0 = (4 * j + 2 * t) * 2;
#pragma unroll 1
          for (int k = 0; k < 16; k++) {
            p.acquire(3);
            if (lane == 0) {
              mbar_expect_tx(p.full(), 49152);
              LDW1(p.slot(1 + rank), &P.wq, p.full(), 0, k * 64 + rank * 32, nb0);
              tma_ld2(p.slot(0), &P.act_ld, p.full(), C_XN + k * 64, row0);
            }
            p.advance(3);
          }
#pragma unroll 1
          for (int i = 0; i < 16; i++) {
            const bool is_k = i == 0 || (i < 15 && (i & 1));
            const int ch = (is_k ? ((i + 1) >> 1) : (i == 15 ? 7 : (i >> 1) - 1)) & 3;
            p.acquire(2);
            if (lane == 0) {
              mbar_expect_tx(p.full(), 32768);
              if (is_k) tma_ld2_mc(p.slot(rank), &P.k_ld, p.full(), rank * 64, kvrow + ch * 128);
              else      tma_ld3_mc(p.slot(rank), &P.v_ld, p.full(), 0, kvrow + ch * 128 + rank * 64, 0);
            }
            p.advance(2);
            if (t == 1 && i == 4 && !is_s) wait_flag(&fl->h[rb][0], ep1 * 64);
          }
        }
        const int jn = j & 3;
        if (is_s) {
          unsigned ready = 0;
#pragma unroll 1
          for (int i = 0; i < 64; i++) {
            const int hi = i >> 1;
            const int head = 4 * ((hi & 15) >> 1) + (hi & 1) + ((hi >> 4) << 1);
            const int kc = head * 128 + (i & 1) * 64;
            p.acquire(3);
            if (lane == 0) { mbar_expect_tx(p.full(), 49152); LDW(p.slot(1 + rank), &P.wo, p.full(), 0, kc + rank * 32, jn * 4); }
            if (!((ready >> head) & 1)) {
              do { ready = __ballot_sync(~0u, (int)(ld_acquire(&fl->o[rb][lane]) - ep1 * 2) >= 0); } while (!((ready >> head) & 1));
              __syncwarp();
              fence_async_all();
            }
            if (lane == 0) LDA(p.slot(0), &P.act_ld, p.full(), C_O + kc, row0);
            if (i == 52) {
              if (lane == 0) { prefetch_map(&P.x_ld); prefetch_map(&P.out_st); }
              if (lane < 4) tma_pf2(&P.x_ld, jn * 256 + lane * 64, row0);
            }
            p.advance(3);
          }
#pragma unroll 1
          for (int i = 0; i < 4; i++) {
            if (i == 1) { TSP(20); wait_flag(&fl->g[rb][jn], ep1 * 4); TSP(21); }
            p.acquire(2);
            if (lane == 0) {
              mbar_expect_tx(p.full(), 32768);
              const CUtensorMap* m = i < 2 ? &P.x_ld : &P.act_ld;
              const int c0 = (i < 2 ? 0 : C_G) + jn * 256 + (i & 1) * 128;
              tma_ld2(p.slot(0), m, p.full(), c0, row0);
              tma_ld2(p.slot(1), m, p.full(), c0 + 64, row0);
            }
            p.advance(2);
          }
        } else {
#pragma unroll 1
          for (int k = 0; k < 56; k++) {
            p.acquire(3);
            if (lane == 0) { mbar_expect_tx(p.full(), 49152); LDW(p.slot(1 + rank), &P.w2, p.full(), 0, k * 64 + rank * 32, jn * 4); }
            if (k == H_SPARE0 / 64) wait_flag(&fl->h[rb][16], ep1 * 8);
            if (lane == 0) LDA(p.slot(0), &P.act_ld, p.full(), C_H + k * 64, row0);
            p.advance(3);
          }
        }
      }
      if (lane == 0) { *(volatile unsigned*)&fl->epoch[blockIdx.x] = ep1; mbar_arrive(sb + SM_BAR + B_DONE); }
    } else if (warp < 11) {
      const int wg = warp - 9;
      if (lane == 0) {
        const uint32_t stg = sb + SM_STG + wg * 16384;
        const int nev = spare ? 16 : is_s ? 8 : 10;
#pragma unroll 1
        for (int n = 0; n < nev; n++) {
          int col, row = row0, nbox = 2;
          unsigned* flag;
          if (spare) {
            const int r = ((cl & 1) * 4 + (n >> 2)) * 2 + rank;
            row = r * 128;
            col = C_H + H_SPARE0 + (n & 3) * 128;
            flag = &fl->h[r][16];
          } else if (n < 4) {
            col = C_H + j * H_REG + (n >> 1) * 192 + (n & 1) * 128;
            nbox = 2 - (n & 1);
            flag = &fl->h[rb][0];
          } else if (n < 8) {
            col = C_O + (4 * j + n - 4) * 128;
            flag = &fl->o[rb][4 * j + n - 4];
          } else {
            col = C_G + (j & 3) * 256 + (n - 8) * 128;
            flag = &fl->g[rb][j & 3];
          }
          mbar_wait(sb + SM_BAR + B_SFULL + wg * 8, n & 1);
          if (n == 9 && wg == 0) TSP(20);
          tma_st2(&P.act_st, stg, col, row + wg * 64);
          if (nbox == 2) tma_st2(&P.act_st, stg + 8192, col + 64, row + wg * 64);
          bulk_commit();
          bulk_wait_read0();
          mbar_arrive(sb + SM_BAR + B_SEMPTY + wg * 8);
          if (n == 9 && wg == 0) TSP(21);
          bulk_wait0();
          if (n == 9 && wg == 0) TSP(22);
          red_release(flag, 1);
          if (n == 9 && wg == 0) TSP(23);
        }
        mbar_arrive(sb + SM_BAR + B_DONE);
      }
    } else {
      if (lane == 0) {
        const unsigned long long t0 = gtime();
        while (!mbar_try(sb + SM_BAR + B_DONE, 0)) {
          if (gtime() - t0 > 2000000000ull) __trap();
        }
      }
    }
    __syncwarp();
    cluster_arrive();
    cluster_wait();
  } else {
    const int wg = warp >> 2;
    TS(0);
    if (!spare) {
      const int r = row0 + j * 16 + warp * 2;
      uint32_t v[2][16];
#pragma unroll
      for (int a = 0; a < 2; a++)
#pragma unroll
        for (int i = 0; i < 4; i++)
          *(uint4*)&v[a][4 * i] = __ldg((const uint4*)(P.x + (size_t)(r + a) * DM + i * 256 + lane * 8));
      if (lane == 0) init_barriers(sb, warp);
      __syncwarp();
      cluster_arrive();
      float s[2], q[2];
#pragma unroll
      for (int a = 0; a < 2; a++) {
        float t0 = 0.f, t1 = 0.f;
#pragma unroll
        for (int i = 0; i < 16; i++) { t0 += bf_lo(v[a][i]); t1 += bf_hi(v[a][i]); }
        s[a] = t0 + t1;
      }
#pragma unroll
      for (int o = 16; o; o >>= 1) { s[0] += __shfl_xor_sync(~0u, s[0], o); s[1] += __shfl_xor_sync(~0u, s[1], o); }
#pragma unroll
      for (int a = 0; a < 2; a++) {
        s[a] *= 1.0f / DM;
        float t0 = 0.f, t1 = 0.f;
#pragma unroll
        for (int i = 0; i < 16; i++) {
          const float d0 = bf_lo(v[a][i]) - s[a], d1 = bf_hi(v[a][i]) - s[a];
          t0 = fmaf(d0, d0, t0); t1 = fmaf(d1, d1, t1);
        }
        q[a] = t0 + t1;
      }
#pragma unroll
      for (int o = 16; o; o >>= 1) { q[0] += __shfl_xor_sync(~0u, q[0], o); q[1] += __shfl_xor_sync(~0u, q[1], o); }
#pragma unroll
      for (int a = 0; a < 2; a++) {
        const uint32_t mb2 = pack_bf16(s[a], s[a]);
        const float inv = 1.0f / bf_round(sqrtf(bf_round(bf_round(q[a] * (1.0f / DM)) + 1e-5f)));
#pragma unroll
        for (int i = 0; i < 16; i++) {
          const __nv_bfloat162 d = __hsub2_rn(*(const __nv_bfloat162*)&v[a][i], *(const __nv_bfloat162*)&mb2);
          const uint32_t du = *(const uint32_t*)&d;
          v[a][i] = pack_bf16(bf_lo(du) * inv, bf_hi(du) * inv);
        }
#pragma unroll
        for (int i = 0; i < 4; i++)
          *(uint4*)(P.act + (size_t)(r + a) * ACT_W + C_XN + i * 256 + lane * 8) = *(const uint4*)&v[a][4 * i];
      }
      TS(11);
      fence_async_all();
      TS(12);
      __syncwarp();
      if (lane == 0) red_release(&fl->ln[rb][0], 1);
      TS(13);
    } else {
      if (lane == 0) init_barriers(sb, warp);
      __syncwarp();
      cluster_arrive();
    }
    cluster_wait();
    asm volatile("setmaxnreg.inc.sync.aligned.u32 240;");
    Cons c;
    c.zero = blockIdx.y; c.sb = sb; c.g = 0; c.pos = 0; c.nstg = 0; c.wg = wg; c.lane = lane;
    c.rel = mapa(sb + SM_BAR + B_EMPTY, lane & 1);
    float acc[128];
    TS(1);
    if (spare) {
      uint32_t pend[32];
#pragma unroll
      for (int i = 0; i < 32; i++) pend[i] = 0;
#pragma unroll 1
      for (int t = 0; t < 8; t++) {
        gemm_loop_flush<256, 2>(acc, c, pend, t > 0);
        h_epilogue<2>(acc, c, pend);
      }
      c.stg_acquire();
      stage_boxes<2>(pend, 0, c);
      TS(6);
    } else {
      if (wg == 1) bar_arrive(1, 256);
      {
        uint32_t pend[16];
#pragma unroll
        for (int i = 0; i < 16; i++) pend[i] = 0;
#pragma unroll 1
        for (int t = 0; t < 2; t++) {
          gemm_loop_flush<192, 1>(acc, c, pend, t > 0);
          h_epilogue<1>(acc, c, pend);
          TS(2 + t);
        }
        gemm_loop_flush<256, 1>(acc, c, pend, true);
      }
#pragma unroll 1
      for (int t = 0; t < 2; t++) {
        TS(8 + t);
        attn_tile(acc, c, t);
        TS(4 + t);
        gemm_loop<256>(acc, c, t == 0 ? 16 : is_s ? 64 : 56);
      }
      TS(6);
      uint32_t rowoff, xr;
      frag_addr(rowoff, xr);
      if (is_s) {
        const uint32_t x0 = c.pos;
#pragma unroll
        for (int b = 0; b < 4; b++) {
          if ((b & 1) == 0) { c.wait_full(c.g + (b >> 1)); c.wait_full(c.g + 2 + (b >> 1)); }
          if (b == 0) TS(22);
          if (b == 2) TS(23);
          const uint32_t xs = sb + wrap12(x0 + b) * SLOT + wg * 8192;
          const uint32_t sx = xs + rowoff, sg = sb + wrap12(wrap12(x0 + 4) + b) * SLOT + wg * 8192 + rowoff;
          uint32_t xv[16], gv[16];
#pragma unroll
          for (int kb = 0; kb < 4; kb++) {
            ldsm4(sx + ((32 * kb) ^ xr), xv[4 * kb], xv[4 * kb + 1], xv[4 * kb + 2], xv[4 * kb + 3]);
            ldsm4(sg + ((32 * kb) ^ xr), gv[4 * kb], gv[4 * kb + 1], gv[4 * kb + 2], gv[4 * kb + 3]);
          }
#pragma unroll
          for (int i = 0; i < 16; i++) {
            const uint32_t s2 = pack_bf16(acc[32 * b + 2 * i], acc[32 * b + 2 * i + 1]);
            const __nv_bfloat162 pr = __hmul2_rn(*(const __nv_bfloat162*)&s2, *(const __nv_bfloat162*)&gv[i]);
            const __nv_bfloat162 o = __hadd2_rn(*(const __nv_bfloat162*)&xv[i], pr);
            xv[i] = *(const uint32_t*)&o;
          }
#pragma unroll
          for (int kb = 0; kb < 4; kb++) stsm4(sx + ((32 * kb) ^ xr), xv[4 * kb], xv[4 * kb + 1], xv[4 * kb + 2], xv[4 * kb + 3]);
          fence_async_smem();
          __syncwarp();
          if (lane == 0) {
            tma_st2(&P.out_st, xs + (warp & 3) * 2048, (j & 3) * 256 + b * 64, row0 + warp * 16);
            bulk_commit();
          }
        }
        TS(24);
        if (lane == 0) bulk_wait_read0();
      } else {
        const uint32_t stg = sb + SM_STG + wg * 16384 + rowoff;
#pragma unroll
        for (int hh = 0; hh < 2; hh++) {
#pragma unroll
          for (int bx = 0; bx < 2; bx++) {
            uint32_t r[16];
            ONCE(c) {
#pragma unroll
              for (int i = 0; i < 16; i++) r[i] = silu2(pack_bf16(acc[64 * hh + 32 * bx + 2 * i], acc[64 * hh + 32 * bx + 2 * i + 1]) ^ once_);
            }
            if (bx == 0) c.stg_acquire();
#pragma unroll
            for (int kb = 0; kb < 4; kb++) stsm4(stg + bx * 8192 + ((32 * kb) ^ xr), r[4 * kb], r[4 * kb + 1], r[4 * kb + 2], r[4 * kb + 3]);
          }
          c.stg_publish();
          if (hh == 0) TS(22);
        }
      }
    }
    TS(7);
    __syncwarp();
    if (lane == 0) mbar_arrive(sb + SM_BAR + B_DONE);
    cluster_arrive();
    cluster_wait();
  }
}

typedef CUresult (*EncodeFn)(CUtensorMap*, CUtensorMapDataType, cuuint32_t, void*, const cuuint64_t*, const cuuint64_t*,
                             const cuuint32_t*, const cuuint32_t*, CUtensorMapInterleave, CUtensorMapSwizzle,
                             CUtensorMapL2promotion, CUtensorMapFloatOOBfill);

void map2d(EncodeFn enc, CUtensorMap* m, const void* base, uint64_t cols, uint64_t rows, uint32_t box_rows) {
  cuuint64_t dims[2] = {cols, rows};
  cuuint64_t strides[1] = {cols * 2};
  cuuint32_t box[2] = {64, box_rows};
  cuuint32_t es[2] = {1, 1};
  enc(m, CU_TENSOR_MAP_DATA_TYPE_BFLOAT16, 2, (void*)base, dims, strides, box, es, CU_TENSOR_MAP_INTERLEAVE_NONE,
      CU_TENSOR_MAP_SWIZZLE_128B, CU_TENSOR_MAP_L2_PROMOTION_L2_256B, CU_TENSOR_MAP_FLOAT_OOB_FILL_NONE);
}
void map3d(EncodeFn enc, CUtensorMap* m, const void* base, uint64_t cols, uint64_t rows, uint32_t box_rows, uint32_t box_blks) {
  cuuint64_t dims[3] = {64, rows, cols / 64};
  cuuint64_t strides[2] = {cols * 2, 128};
  cuuint32_t box[3] = {64, box_rows, box_blks};
  cuuint32_t es[3] = {1, 1, 1};
  enc(m, CU_TENSOR_MAP_DATA_TYPE_BFLOAT16, 3, (void*)base, dims, strides, box, es, CU_TENSOR_MAP_INTERLEAVE_NONE,
      CU_TENSOR_MAP_SWIZZLE_128B, CU_TENSOR_MAP_L2_PROMOTION_L2_256B, CU_TENSOR_MAP_FLOAT_OOB_FILL_NONE);
}

}

extern "C" void kernel_launch(void* const* d_in, const int* in_sizes, int n_in, void* d_out, int out_size) {
  (void)in_sizes; (void)n_in; (void)out_size;
  static EncodeFn enc = nullptr;
  static void* act = nullptr;
  static void* flags = nullptr;
  if (!enc) {
    void* fn = nullptr;
    cudaDriverEntryPointQueryResult qr;
    cudaGetDriverEntryPoint("cuTensorMapEncodeTiled", &fn, cudaEnableDefault, &qr);
    enc = (EncodeFn)fn;
    cudaGetSymbolAddress(&act, g_act);
    cudaGetSymbolAddress(&flags, g_flags);
    cudaFuncSetAttribute(fused_kernel, cudaFuncAttributeMaxDynamicSharedMemorySize, SMEM_BYTES);
  }
  Params P;
  map2d(enc, &P.act_ld, act, ACT_W, SEQ, 128);
  map2d(enc, &P.act_st, act, ACT_W, SEQ, 64);
  map2d(enc, &P.x_ld, d_in[0], DM, SEQ, 128);
  map2d(enc, &P.out_st, d_out, DM, SEQ, 16);
  map2d(enc, &P.k_ld, d_in[1], 128, 4 * SK, 128);
  map3d(enc, &P.v_ld, d_in[2], 128, 4 * SK, 64, 2);
  map3d(enc, &P.wq, d_in[3], NQ, DM, 32, 4);
  map3d(enc, &P.w1b4, d_in[6], DFF, DM, 32, 4);
  map3d(enc, &P.w1b3, d_in[6], DFF, DM, 32, 3);
  map3d(enc, &P.wo, d_in[4], DM, NQ, 32, 4);
  map3d(enc, &P.w2, d_in[7], DM, DFF, 32, 4);
  P.x = (const __nv_bfloat16*)d_in[0];
  P.act = (__nv_bfloat16*)act;
  P.flags = (Flags*)flags;
  fused_kernel<<<NCLUSTER * 2, 384, SMEM_BYTES>>>(P);
}
```

```cpp
#include <cuda_runtime.h>
#include <cuda_bf16.h>
#include <cuda.h>
#include <stdint.h>

namespace {

constexpr int SEQ    = 2048;
constexpr int DM     = 1024;
constexpr int NQ     = 4096;
constexpr int DFF    = 3584;
constexpr int SK     = 2048;
constexpr int WIN    = 512;
constexpr int KV0    = SK - WIN;
constexpr int C_XN = 0, C_O = 1024, C_H = 5120, C_G = 8704, ACT_W = 9728;

constexpr int H_REG = 384, H_SPARE0 = 8 * H_REG;
static_assert(H_SPARE0 + 512 == DFF, "H split");

constexpr int NSLOT = 12, SLOT = 16384, NBAR = 8;
constexpr int SM_STG = NSLOT * SLOT;
constexpr int SM_BAR = SM_STG + 2 * 16384;
constexpr int SMEM_BYTES = SM_BAR + 256 + 1024;
constexpr int B_FULL = 0, B_EMPTY = 64, B_SFULL = 128, B_SEMPTY = 144, B_DONE = 160;

constexpr int NCLUSTER = 66;

struct Flags {
  unsigned ln[16][32];
  unsigned h[16][32];
  unsigned o[16][32];
  unsigned g[16][32];
  unsigned epoch[160];
};
__device__ __nv_bfloat16 g_act[(size_t)SEQ * ACT_W];
__device__ Flags g_flags;

struct Params {
  CUtensorMap act_ld, act_st, x_ld, out_st, k_ld, v_ld, wq, w1b4, w1b3, wo, w2;
  const __nv_bfloat16* x;
  __nv_bfloat16* act;
  Flags* flags;
};

__device__ __forceinline__ uint32_t smem_u32(const void* p) { return (uint32_t)__cvta_generic_to_shared(p); }
__device__ __forceinline__ void mbar_init(uint32_t bar, uint32_t cnt) {
  asm volatile("mbarrier.init.shared::cta.b64 [%0], %1;" ::"r"(bar), "r"(cnt) : "memory");
}
__device__ __forceinline__ bool mbar_try(uint32_t bar, uint32_t parity) {
  uint32_t ok;
  asm volatile("{\n.reg .pred p;\nmbarrier.try_wait.parity.shared::cta.b64 p, [%1], %2;\nselp.u32 %0, 1, 0, p;\n}\n"
               : "=r"(ok) : "r"(bar), "r"(parity) : "memory");
  return ok;
}
__device__ __forceinline__ void mbar_wait(uint32_t bar, uint32_t parity) {
  asm volatile("{\n.reg .pred p;\nWAIT_%=:\nmbarrier.try_wait.parity.shared::cta.b64 p, [%0], %1;\n@p bra DONE_%=;\nbra WAIT_%=;\nDONE_%=:\n}\n"
               ::"r"(bar), "r"(parity) : "memory");
}
__device__ __forceinline__ void mbar_arrive(uint32_t bar) {
  asm volatile("mbarrier.arrive.shared::cta.b64 _, [%0];" ::"r"(bar) : "memory");
}
__device__ __forceinline__ void mbar_arrive_cluster(uint32_t cluster_addr) {
  asm volatile("mbarrier.arrive.shared::cluster.b64 _, [%0];" ::"r"(cluster_addr) : "memory");
}
__device__ __forceinline__ void mbar_expect_tx(uint32_t bar, uint32_t bytes) {
  asm volatile("mbarrier.arrive.expect_tx.shared::cta.b64 _, [%0], %1;" ::"r"(bar), "r"(bytes) : "memory");
}
__device__ __forceinline__ uint32_t mapa(uint32_t addr, uint32_t rank) {
  uint32_t r;
  asm("mapa.shared::cluster.u32 %0, %1, %2;" : "=r"(r) : "r"(addr), "r"(rank));
  return r;
}
__device__ __forceinline__ void cluster_arrive() { asm volatile("barrier.cluster.arrive.relaxed.aligned;" ::: "memory"); }
__device__ __forceinline__ void cluster_wait() { asm volatile("barrier.cluster.wait.acquire.aligned;" ::: "memory"); }
__device__ __forceinline__ void bar_sync(int id, int n) { asm volatile("bar.sync %0, %1;" ::"r"(id), "r"(n) : "memory"); }
__device__ __forceinline__ void bar_arrive(int id, int n) { asm volatile("bar.arrive %0, %1;" ::"r"(id), "r"(n) : "memory"); }
__device__ __forceinline__ void fence_async_smem() { asm volatile("fence.proxy.async.shared::cta;" ::: "memory"); }
__device__ __forceinline__ void fence_async_all() { asm volatile("fence.proxy.async.global;" ::: "memory"); }

__device__ __forceinline__ void tma_ld2(uint32_t dst, const CUtensorMap* m, uint32_t bar, int c0, int c1) {
  asm volatile("cp.async.bulk.tensor.2d.shared::cluster.global.mbarrier::complete_tx::bytes [%0], [%1, {%3, %4}], [%2];"
               ::"r"(dst), "l"(m), "r"(bar), "r"(c0), "r"(c1) : "memory");
}
__device__ __forceinline__ void tma_ld2_mc(uint32_t dst, const CUtensorMap* m, uint32_t bar, int c0, int c1) {
  asm volatile("cp.async.bulk.tensor.2d.shared::cluster.global.mbarrier::complete_tx::bytes.multicast::cluster [%0], [%1, {%3, %4}], [%2], %5;"
               ::"r"(dst), "l"(m), "r"(bar), "r"(c0), "r"(c1), "h"((uint16_t)3) : "memory");
}
__device__ __forceinline__ void tma_ld3_mc(uint32_t dst, const CUtensorMap* m, uint32_t bar, int c0, int c1, int c2) {
  asm volatile("cp.async.bulk.tensor.3d.shared::cluster.global.mbarrier::complete_tx::bytes.multicast::cluster [%0], [%1, {%3, %4, %5}], [%2], %6;"
               ::"r"(dst), "l"(m), "r"(bar), "r"(c0), "r"(c1), "r"(c2), "h"((uint16_t)3) : "memory");
}
__device__ __forceinline__ void tma_ld3_mc_hint(uint32_t dst, const CUtensorMap* m, uint32_t bar, int c0, int c1, int c2, uint64_t pol) {
  asm volatile("cp.async.bulk.tensor.3d.shared::cluster.global.mbarrier::complete_tx::bytes.multicast::cluster.L2::cache_hint [%0], [%1, {%3, %4, %5}], [%2], %6, %7;"
               ::"r"(dst), "l"(m), "r"(bar), "r"(c0), "r"(c1), "r"(c2), "h"((uint16_t)3), "l"(pol) : "memory");
}
__device__ __forceinline__ void tma_ld2_hint(uint32_t dst, const CUtensorMap* m, uint32_t bar, int c0, int c1, uint64_t pol) {
  asm volatile("cp.async.bulk.tensor.2d.shared::cluster.global.mbarrier::complete_tx::bytes.L2::cache_hint [%0], [%1, {%3, %4}], [%2], %5;"
               ::"r"(dst), "l"(m), "r"(bar), "r"(c0), "r"(c1), "l"(pol) : "memory");
}
__device__ __forceinline__ void tma_st2_hint(const CUtensorMap* m, uint32_t src, int c0, int c1, uint64_t pol) {
  asm volatile("cp.async.bulk.tensor.2d.global.shared::cta.bulk_group.L2::cache_hint [%0, {%2, %3}], [%1], %4;"
               ::"l"(m), "r"(src), "r"(c0), "r"(c1), "l"(pol) : "memory");
}
#define POL_FIRST 0x12F0000000000000ull
__device__ __forceinline__ uint64_t policy_evict_first() {
  uint64_t p;
  asm volatile("createpolicy.fractional.L2::evict_first.b64 %0, 1.0;" : "=l"(p));
  return p;
}
__device__ __forceinline__ void tma_st2(const CUtensorMap* m, uint32_t src, int c0, int c1) {
  asm volatile("cp.async.bulk.tensor.2d.global.shared::cta.bulk_group [%0, {%2, %3}], [%1];"
               ::"l"(m), "r"(src), "r"(c0), "r"(c1) : "memory");
}
__device__ __forceinline__ void tma_pf2(const CUtensorMap* m, int c0, int c1) {
  asm volatile("cp.async.bulk.prefetch.tensor.2d.L2.global [%0, {%1, %2}];" ::"l"(m), "r"(c0), "r"(c1) : "memory");
}
__device__ __forceinline__ void bulk_commit() { asm volatile("cp.async.bulk.commit_group;" ::: "memory"); }
__device__ __forceinline__ void bulk_wait_read0() { asm volatile("cp.async.bulk.wait_group.read 0;" ::: "memory"); }
__device__ __forceinline__ void bulk_wait0() { asm volatile("cp.async.bulk.wait_group 0;" ::: "memory"); }
__device__ __forceinline__ void prefetch_map(const CUtensorMap* m) {
  asm volatile("prefetch.tensormap [%0];" ::"l"(m) : "memory");
}
__device__ __forceinline__ unsigned ld_acquire(const unsigned* p) {
  unsigned v;
  asm volatile("ld.acquire.gpu.global.u32 %0, [%1];" : "=r"(v) : "l"(p) : "memory");
  return v;
}
__device__ __forceinline__ void red_release(unsigned* p, unsigned v) {
  asm volatile("red.release.gpu.global.add.u32 [%0], %1;" ::"l"(p), "r"(v) : "memory");
}
__device__ __forceinline__ void wg_fence() { asm volatile("wgmma.fence.sync.aligned;" ::: "memory"); }
__device__ __forceinline__ void wg_commit() { asm volatile("wgmma.commit_group.sync.aligned;" ::: "memory"); }
template <int N> __device__ __forceinline__ void wg_wait() { asm volatile("wgmma.wait_group.sync.aligned %0;" ::"n"(N) : "memory"); }
template <int N> __device__ __forceinline__ void fence_regs(float (&d)[N]) {
#pragma unroll
  for (int i = 0; i < N; i++) asm volatile("" : "+f"(d[i])::"memory");
}
template <int N> __device__ __forceinline__ void fence_regs(uint32_t (&d)[N]) {
#pragma unroll
  for (int i = 0; i < N; i++) asm volatile("" : "+r"(d[i])::"memory");
}
__device__ __forceinline__ uint64_t mkdesc(uint32_t addr, uint32_t lbo, uint32_t sbo) {
  return (uint64_t)((addr & 0x3FFFF) >> 4) | ((uint64_t)(lbo >> 4) << 16) | ((uint64_t)(sbo >> 4) << 32) | (1ull << 62);
}
__device__ __forceinline__ uint32_t pack_bf16(float lo, float hi) {
  uint32_t r;
  asm("cvt.rn.bf16x2.f32 %0, %1, %2;" : "=r"(r) : "f"(hi), "f"(lo));
  return r;
}
__device__ __forceinline__ uint32_t pack_bf16_relu(float lo, float hi) {
  uint32_t r;
  asm("cvt.rn.relu.bf16x2.f32 %0, %1, %2;" : "=r"(r) : "f"(hi), "f"(lo));
  return r;
}
__device__ __forceinline__ float bf_lo(uint32_t v) { return __uint_as_float(v << 16); }
__device__ __forceinline__ float bf_hi(uint32_t v) { return __uint_as_float(v & 0xFFFF0000u); }
__device__ __forceinline__ float bf_round(float v) { return __bfloat162float(__float2bfloat16_rn(v)); }
__device__ __forceinline__ float ex2(float x) {
  float r;
  asm("ex2.approx.ftz.f32 %0, %1;" : "=f"(r) : "f"(x));
  return r;
}
__device__ __forceinline__ float rcp(float x) {
  float r;
  asm("rcp.approx.ftz.f32 %0, %1;" : "=f"(r) : "f"(x));
  return r;
}
__device__ __forceinline__ uint32_t tid_x() {
  uint32_t t;
  asm volatile("mov.u32 %0, %%tid.x;" : "=r"(t));
  return t;
}
__device__ __forceinline__ void stsm4(uint32_t addr, uint32_t r0, uint32_t r1, uint32_t r2, uint32_t r3) {
  asm volatile("stmatrix.sync.aligned.m8n8.x4.shared.b16 [%0], {%1, %2, %3, %4};" ::"r"(addr), "r"(r0), "r"(r1), "r"(r2), "r"(r3) : "memory");
}
__device__ __forceinline__ void ldsm4(uint32_t addr, uint32_t& r0, uint32_t& r1, uint32_t& r2, uint32_t& r3) {
  asm volatile("ldmatrix.sync.aligned.m8n8.x4.shared.b16 {%0, %1, %2, %3}, [%4];" : "=r"(r0), "=r"(r1), "=r"(r2), "=r"(r3) : "r"(addr) : "memory");
}
__device__ __forceinline__ void sts128(uint32_t addr, uint32_t r0, uint32_t r1, uint32_t r2, uint32_t r3) {
  asm volatile("st.shared.v4.b32 [%0], {%1, %2, %3, %4};" ::"r"(addr), "r"(r0), "r"(r1), "r"(r2), "r"(r3) : "memory");
}
__device__ __forceinline__ void lds128(uint32_t addr, uint32_t& r0, uint32_t& r1, uint32_t& r2, uint32_t& r3) {
  asm volatile("ld.shared.v4.b32 {%0, %1, %2, %3}, [%4];" : "=r"(r0), "=r"(r1), "=r"(r2), "=r"(r3) : "r"(addr) : "memory");
}
__device__ __forceinline__ unsigned long long gtime() {
  unsigned long long t;
  asm volatile("mov.u64 %0, %globaltimer;" : "=l"(t));
  return t;
}

__device__ __forceinline__ void wgmma_ss_n256_tb(float (&d)[128], uint64_t da, uint64_t db, uint32_t sc) {
  asm volatile("{\n.reg .pred p;\nsetp.ne.b32 p, %130, 0;\n"
    "wgmma.mma_async.sync.aligned.m64n256k16.f32.bf16.bf16 "
    "{%0, %1, %2, %3, %4, %5, %6, %7, %8, %9, %10, %11, %12, %13, %14, %15, %16, %17, %18, %19, %20, %21, %22, %23, %24, %25, %26, %27, %28, %29, %30, %31, %32, %33, %34, %35, %36, %37, %38, %39, %40, %41, %42, %43, %44, %45, %46, %47, %48, %49, %50, %51, %52, %53, %54, %55, %56, %57, %58, %59, %60, %61, %62, %63, %64, %65, %66, %67, %68, %69, %70, %71, %72, %73, %74, %75, %76, %77, %78, %79, %80, %81, %82, %83, %84, %85, %86, %87, %88, %89, %90, %91, %92, %93, %94, %95, %96, %97, %98, %99, %100, %101, %102, %103, %104, %105, %106, %107, %108, %109, %110, %111, %112, %113, %114, %115, %116, %117, %118, %119, %120, %121, %122, %123, %124, %125, %126, %127}, %128, %129, p, 1, 1, 0, 1;\n}\n"
    : "+f"(d[0]), "+f"(d[1]), "+f"(d[2]), "+f"(d[3]), "+f"(d[4]), "+f"(d[5]), "+f"(d[6]), "+f"(d[7]), "+f"(d[8]), "+f"(d[9]), "+f"(d[10]), "+f"(d[11]), "+f"(d[12]), "+f"(d[13]), "+f"(d[14]), "+f"(d[15]), "+f"(d[16]), "+f"(d[17]), "+f"(d[18]), "+f"(d[19]), "+f"(d[20]), "+f"(d[21]), "+f"(d[22]), "+f"(d[23]), "+f"(d[24]), "+f"(d[25]), "+f"(d[26]), "+f"(d[27]), "+f"(d[28]), "+f"(d[29]), "+f"(d[30]), "+f"(d[31]), "+f"(d[32]), "+f"(d[33]), "+f"(d[34]), "+f"(d[35]), "+f"(d[36]), "+f"(d[37]), "+f"(d[38]), "+f"(d[39]), "+f"(d[40]), "+f"(d[41]), "+f"(d[42]), "+f"(d[43]), "+f"(d[44]), "+f"(d[45]), "+f"(d[46]), "+f"(d[47]), "+f"(d[48]), "+f"(d[49]), "+f"(d[50]), "+f"(d[51]), "+f"(d[52]), "+f"(d[53]), "+f"(d[54]), "+f"(d[55]), "+f"(d[56]), "+f"(d[57]), "+f"(d[58]), "+f"(d[59]), "+f"(d[60]), "+f"(d[61]), "+f"(d[62]), "+f"(d[63]), "+f"(d[64]), "+f"(d[65]), "+f"(d[66]), "+f"(d[67]), "+f"(d[68]), "+f"(d[69]), "+f"(d[70]), "+f"(d[71]), "+f"(d[72]), "+f"(d[73]), "+f"(d[74]), "+f"(d[75]), "+f"(d[76]), "+f"(d[77]), "+f"(d[78]), "+f"(d[79]), "+f"(d[80]), "+f"(d[81]), "+f"(d[82]), "+f"(d[83]), "+f"(d[84]), "+f"(d[85]), "+f"(d[86]), "+f"(d[87]), "+f"(d[88]), "+f"(d[89]), "+f"(d[90]), "+f"(d[91]), "+f"(d[92]), "+f"(d[93]), "+f"(d[94]), "+f"(d[95]), "+f"(d[96]), "+f"(d[97]), "+f"(d[98]), "+f"(d[99]), "+f"(d[100]), "+f"(d[101]), "+f"(d[102]), "+f"(d[103]), "+f"(d[104]), "+f"(d[105]), "+f"(d[106]), "+f"(d[107]), "+f"(d[108]), "+f"(d[109]), "+f"(d[110]), "+f"(d[111]), "+f"(d[112]), "+f"(d[113]), "+f"(d[114]), "+f"(d[115]), "+f"(d[116]), "+f"(d[117]), "+f"(d[118]), "+f"(d[119]), "+f"(d[120]), "+f"(d[121]), "+f"(d[122]), "+f"(d[123]), "+f"(d[124]), "+f"(d[125]), "+f"(d[126]), "+f"(d[127])
    : "l"(da), "l"(db), "r"(sc));
}
__device__ __forceinline__ void wgmma_ss_n192_tb(float (&d)[128], uint64_t da, uint64_t db, uint32_t sc) {
  asm volatile("{\n.reg .pred p;\nsetp.ne.b32 p, %98, 0;\n"
    "wgmma.mma_async.sync.aligned.m64n192k16.f32.bf16.bf16 "
    "{%0, %1, %2, %3, %4, %5, %6, %7, %8, %9, %10, %11, %12, %13, %14, %15, %16, %17, %18, %19, %20, %21, %22, %23, %24, %25, %26, %27, %28, %29, %30, %31, %32, %33, %34, %35, %36, %37, %38, %39, %40, %41, %42, %43, %44, %45, %46, %47, %48, %49, %50, %51, %52, %53, %54, %55, %56, %57, %58, %59, %60, %61, %62, %63, %64, %65, %66, %67, %68, %69, %70, %71, %72, %73, %74, %75, %76, %77, %78, %79, %80, %81, %82, %83, %84, %85, %86, %87, %88, %89, %90, %91, %92, %93, %94, %95}, %96, %97, p, 1, 1, 0, 1;\n}\n"
    : "+f"(d[0]), "+f"(d[1]), "+f"(d[2]), "+f"(d[3]), "+f"(d[4]), "+f"(d[5]), "+f"(d[6]), "+f"(d[7]), "+f"(d[8]), "+f"(d[9]), "+f"(d[10]), "+f"(d[11]), "+f"(d[12]), "+f"(d[13]), "+f"(d[14]), "+f"(d[15]), "+f"(d[16]), "+f"(d[17]), "+f"(d[18]), "+f"(d[19]), "+f"(d[20]), "+f"(d[21]), "+f"(d[22]), "+f"(d[23]), "+f"(d[24]), "+f"(d[25]), "+f"(d[26]), "+f"(d[27]), "+f"(d[28]), "+f"(d[29]), "+f"(d[30]), "+f"(d[31]), "+f"(d[32]), "+f"(d[33]), "+f"(d[34]), "+f"(d[35]), "+f"(d[36]), "+f"(d[37]), "+f"(d[38]), "+f"(d[39]), "+f"(d[40]), "+f"(d[41]), "+f"(d[42]), "+f"(d[43]), "+f"(d[44]), "+f"(d[45]), "+f"(d[46]), "+f"(d[47]), "+f"(d[48]), "+f"(d[49]), "+f"(d[50]), "+f"(d[51]), "+f"(d[52]), "+f"(d[53]), "+f"(d[54]), "+f"(d[55]), "+f"(d[56]), "+f"(d[57]), "+f"(d[58]), "+f"(d[59]), "+f"(d[60]), "+f"(d[61]), "+f"(d[62]), "+f"(d[63]), "+f"(d[64]), "+f"(d[65]), "+f"(d[66]), "+f"(d[67]), "+f"(d[68]), "+f"(d[69]), "+f"(d[70]), "+f"(d[71]), "+f"(d[72]), "+f"(d[73]), "+f"(d[74]), "+f"(d[75]), "+f"(d[76]), "+f"(d[77]), "+f"(d[78]), "+f"(d[79]), "+f"(d[80]), "+f"(d[81]), "+f"(d[82]), "+f"(d[83]), "+f"(d[84]), "+f"(d[85]), "+f"(d[86]), "+f"(d[87]), "+f"(d[88]), "+f"(d[89]), "+f"(d[90]), "+f"(d[91]), "+f"(d[92]), "+f"(d[93]), "+f"(d[94]), "+f"(d[95])
    : "l"(da), "l"(db), "r"(sc));
}
__device__ __forceinline__ void wgmma_rs_n128(float (&d)[64], uint32_t a0, uint32_t a1, uint32_t a2, uint32_t a3, uint64_t db, uint32_t sc) {
  asm volatile("{\n.reg .pred p;\nsetp.ne.b32 p, %69, 0;\n"
    "wgmma.mma_async.sync.aligned.m64n128k16.f32.bf16.bf16 "
    "{%0, %1, %2, %3, %4, %5, %6, %7, %8, %9, %10, %11, %12, %13, %14, %15, %16, %17, %18, %19, %20, %21, %22, %23, %24, %25, %26, %27, %28, %29, %30, %31, %32, %33, %34, %35, %36, %37, %38, %39, %40, %41, %42, %43, %44, %45, %46, %47, %48, %49, %50, %51, %52, %53, %54, %55, %56, %57, %58, %59, %60, %61, %62, %63}, {%64, %65, %66, %67}, %68, p, 1, 1, 0;\n}\n"
    : "+f"(d[0]), "+f"(d[1]), "+f"(d[2]), "+f"(d[3]), "+f"(d[4]), "+f"(d[5]), "+f"(d[6]), "+f"(d[7]), "+f"(d[8]), "+f"(d[9]), "+f"(d[10]), "+f"(d[11]), "+f"(d[12]), "+f"(d[13]), "+f"(d[14]), "+f"(d[15]), "+f"(d[16]), "+f"(d[17]), "+f"(d[18]), "+f"(d[19]), "+f"(d[20]), "+f"(d[21]), "+f"(d[22]), "+f"(d[23]), "+f"(d[24]), "+f"(d[25]), "+f"(d[26]), "+f"(d[27]), "+f"(d[28]), "+f"(d[29]), "+f"(d[30]), "+f"(d[31]), "+f"(d[32]), "+f"(d[33]), "+f"(d[34]), "+f"(d[35]), "+f"(d[36]), "+f"(d[37]), "+f"(d[38]), "+f"(d[39]), "+f"(d[40]), "+f"(d[41]), "+f"(d[42]), "+f"(d[43]), "+f"(d[44]), "+f"(d[45]), "+f"(d[46]), "+f"(d[47]), "+f"(d[48]), "+f"(d[49]), "+f"(d[50]), "+f"(d[51]), "+f"(d[52]), "+f"(d[53]), "+f"(d[54]), "+f"(d[55]), "+f"(d[56]), "+f"(d[57]), "+f"(d[58]), "+f"(d[59]), "+f"(d[60]), "+f"(d[61]), "+f"(d[62]), "+f"(d[63])
    : "r"(a0), "r"(a1), "r"(a2), "r"(a3), "l"(db), "r"(sc));
}
__device__ __forceinline__ void wgmma_rs_n128_tb(float (&d)[64], uint32_t a0, uint32_t a1, uint32_t a2, uint32_t a3, uint64_t db, uint32_t sc) {
  asm volatile("{\n.reg .pred p;\nsetp.ne.b32 p, %69, 0;\n"
    "wgmma.mma_async.sync.aligned.m64n128k16.f32.bf16.bf16 "
    "{%0, %1, %2, %3, %4, %5, %6, %7, %8, %9, %10, %11, %12, %13, %14, %15, %16, %17, %18, %19, %20, %21, %22, %23, %24, %25, %26, %27, %28, %29, %30, %31, %32, %33, %34, %35, %36, %37, %38, %39, %40, %41, %42, %43, %44, %45, %46, %47, %48, %49, %50, %51, %52, %53, %54, %55, %56, %57, %58, %59, %60, %61, %62, %63}, {%64, %65, %66, %67}, %68, p, 1, 1, 1;\n}\n"
    : "+f"(d[0]), "+f"(d[1]), "+f"(d[2]), "+f"(d[3]), "+f"(d[4]), "+f"(d[5]), "+f"(d[6]), "+f"(d[7]), "+f"(d[8]), "+f"(d[9]), "+f"(d[10]), "+f"(d[11]), "+f"(d[12]), "+f"(d[13]), "+f"(d[14]), "+f"(d[15]), "+f"(d[16]), "+f"(d[17]), "+f"(d[18]), "+f"(d[19]), "+f"(d[20]), "+f"(d[21]), "+f"(d[22]), "+f"(d[23]), "+f"(d[24]), "+f"(d[25]), "+f"(d[26]), "+f"(d[27]), "+f"(d[28]), "+f"(d[29]), "+f"(d[30]), "+f"(d[31]), "+f"(d[32]), "+f"(d[33]), "+f"(d[34]), "+f"(d[35]), "+f"(d[36]), "+f"(d[37]), "+f"(d[38]), "+f"(d[39]), "+f"(d[40]), "+f"(d[41]), "+f"(d[42]), "+f"(d[43]), "+f"(d[44]), "+f"(d[45]), "+f"(d[46]), "+f"(d[47]), "+f"(d[48]), "+f"(d[49]), "+f"(d[50]), "+f"(d[51]), "+f"(d[52]), "+f"(d[53]), "+f"(d[54]), "+f"(d[55]), "+f"(d[56]), "+f"(d[57]), "+f"(d[58]), "+f"(d[59]), "+f"(d[60]), "+f"(d[61]), "+f"(d[62]), "+f"(d[63])
    : "r"(a0), "r"(a1), "r"(a2), "r"(a3), "l"(db), "r"(sc));
}

#define TS(i) do {} while (0)
#define TR(j, i) do {} while (0)
#define TSS(i, c) do {} while (0)

__device__ __forceinline__ uint32_t wrap12(uint32_t p) { return p >= NSLOT ? p - NSLOT : p; }

#define ONCE(c) _Pragma("unroll 1") for (uint32_t once_ = 0; once_ <= (c).zero; once_++)
struct Cons {
  uint32_t sb;
  uint32_t g, pos;
  uint32_t rel;
  uint32_t nstg;
  uint32_t zero;
  int wg, lane;
  __device__ __forceinline__ void wait_full(uint32_t gg) const { mbar_wait(sb + SM_BAR + B_FULL + (gg & 7) * 8, (gg >> 3) & 1); }
  __device__ __forceinline__ void release(uint32_t gg) const { if (lane < 2) mbar_arrive_cluster(rel + (gg & 7) * 8); }
  __device__ __forceinline__ void stg_acquire() { mbar_wait(sb + SM_BAR + B_SEMPTY + wg * 8, (nstg & 1) ^ 1); nstg++; }
  __device__ __forceinline__ void stg_publish() const {
    fence_async_smem();
    __syncwarp();
    if (lane == 0) mbar_arrive(sb + SM_BAR + B_SFULL + wg * 8);
  }
};

__device__ __forceinline__ void frag_addr(uint32_t& rowoff, uint32_t& xr) {
  const uint32_t t = tid_x();
  rowoff = ((t >> 5) & 3) * 2048 + (t & 15) * 128;
  xr = (((t >> 4) & 1) ^ (t & 7)) << 4;
}
template <int NB, int NR>
__device__ __forceinline__ void stage_boxes(const uint32_t (&r)[NR], int r0, const Cons& c) {
  uint32_t rowoff, xr;
  frag_addr(rowoff, xr);
  const uint32_t stg = c.sb + SM_STG + c.wg * 16384 + rowoff;
#pragma unroll
  for (int b = 0; b < NB; b++)
#pragma unroll
    for (int kb = 0; kb < 4; kb++)
      stsm4(stg + b * 8192 + ((32 * kb) ^ xr), r[r0 + b * 16 + kb * 4], r[r0 + b * 16 + kb * 4 + 1], r[r0 + b * 16 + kb * 4 + 2], r[r0 + b * 16 + kb * 4 + 3]);
  c.stg_publish();
}

template <int N, bool FIRST>
__device__ __forceinline__ void gemm_step(float (&acc)[128], Cons& c) {
  const uint32_t p1 = wrap12(c.pos + 1), p2 = wrap12(c.pos + 2);
  const uint64_t da = mkdesc(c.sb + c.wg * 8192 + c.pos * SLOT, 16, 1024);
  const uint64_t b0 = mkdesc(c.sb + p1 * SLOT, 4096, 1024);
  const uint64_t b1 = mkdesc(c.sb + p2 * SLOT, 4096, 1024);
  c.wait_full(c.g);
  wg_fence();
  if (N == 256) {
    wgmma_ss_n256_tb(acc, da, b0, FIRST ? 0 : 1);
    wgmma_ss_n256_tb(acc, da + 2, b0 + 128, 1);
    wgmma_ss_n256_tb(acc, da + 4, b1, 1);
    wgmma_ss_n256_tb(acc, da + 6, b1 + 128, 1);
  } else {
    wgmma_ss_n192_tb(acc, da, b0, FIRST ? 0 : 1);
    wgmma_ss_n192_tb(acc, da + 2, b0 + 128, 1);
    wgmma_ss_n192_tb(acc, da + 4, b1, 1);
    wgmma_ss_n192_tb(acc, da + 6, b1 + 128, 1);
  }
  wg_commit();
  if (!FIRST) {
    wg_wait<1>();
    c.release(c.g - 1);
  }
  c.g++;
  c.pos = wrap12(p2 + 1);
}

template <int N>
__device__ __forceinline__ void gemm_loop(float (&acc)[128], Cons& c, int nk) {
  gemm_step<N, true>(acc, c);
#pragma unroll 1
  for (int k = 1; k < nk; k++) gemm_step<N, false>(acc, c);
  wg_wait<0>();
  c.release(c.g - 1);
  fence_regs(acc);
}
template <int N, int NB>
__device__ __forceinline__ void gemm_loop_flush(float (&acc)[128], Cons& c, const uint32_t (&pend)[NB * 16], bool flush) {
  gemm_step<N, true>(acc, c);
#pragma unroll 1
  for (int k = 1; k < 16; k++) {
    gemm_step<N, false>(acc, c);
    if (k == 3 && flush) {
      c.stg_acquire();
      stage_boxes<NB>(pend, 0, c);
    }
  }
  wg_wait<0>();
  c.release(c.g - 1);
  fence_regs(acc);
}
template <int NB>
__device__ __forceinline__ void h_epilogue(const float (&acc)[128], Cons& c, uint32_t (&pend)[NB * 16]) {
  uint32_t r[32];
#pragma unroll
  for (int i = 0; i < 32; i++) r[i] = pack_bf16_relu(acc[2 * i], acc[2 * i + 1]);
  c.stg_acquire();
  stage_boxes<2>(r, 0, c);
#pragma unroll
  for (int i = 0; i < NB * 16; i++) pend[i] = pack_bf16_relu(acc[64 + 2 * i], acc[65 + 2 * i]);
}

__device__ __forceinline__ uint32_t silu2(uint32_t f2) {
  const float a = bf_lo(f2), b = bf_hi(f2);
  return pack_bf16(a * rcp(1.0f + ex2(-1.4426950408889634f * a)), b * rcp(1.0f + ex2(-1.4426950408889634f * b)));
}

constexpr float SM_C = 0.08838834764831845f * 1.4426950408889634f;

__device__ __forceinline__ void row_max2(const float (&S)[64], float& n0, float& n1) {
  float x[4], y[4];
#pragma unroll
  for (int i = 0; i < 4; i++) { x[i] = fmaxf(S[4 * i], S[4 * i + 1]); y[i] = fmaxf(S[4 * i + 2], S[4 * i + 3]); }
#pragma unroll
  for (int i = 4; i < 16; i++) {
    x[i & 3] = fmaxf(x[i & 3], fmaxf(S[4 * i], S[4 * i + 1]));
    y[i & 3] = fmaxf(y[i & 3], fmaxf(S[4 * i + 2], S[4 * i + 3]));
  }
  n0 = fmaxf(fmaxf(x[0], x[1]), fmaxf(x[2], x[3]));
  n1 = fmaxf(fmaxf(y[0], y[1]), fmaxf(y[2], y[3]));
  n0 = fmaxf(n0, __shfl_xor_sync(~0u, n0, 1));
  n1 = fmaxf(n1, __shfl_xor_sync(~0u, n1, 1));
  n0 = fmaxf(n0, __shfl_xor_sync(~0u, n0, 2));
  n1 = fmaxf(n1, __shfl_xor_sync(~0u, n1, 2));
}
__device__ __forceinline__ void to_exponent(float (&S)[64], float cc0, float cc1) {
#pragma unroll
  for (int i = 0; i < 16; i++) {
    S[4 * i] = fmaf(S[4 * i], SM_C, cc0); S[4 * i + 1] = fmaf(S[4 * i + 1], SM_C, cc0);
    S[4 * i + 2] = fmaf(S[4 * i + 2], SM_C, cc1); S[4 * i + 3] = fmaf(S[4 * i + 3], SM_C, cc1);
  }
}
__device__ __forceinline__ void scale_o(float (&O)[64], float f0, float f1) {
#pragma unroll
  for (int i = 0; i < 16; i++) { O[4 * i] *= f0; O[4 * i + 1] *= f0; O[4 * i + 2] *= f1; O[4 * i + 3] *= f1; }
}
template <int G0>
__device__ __forceinline__ void exp_pack(const float (&S)[64], uint32_t (&p)[32], float (&a)[4]) {
#pragma unroll
  for (int i = G0; i < 16; i++) {
    const float e0 = ex2(S[4 * i]), e1 = ex2(S[4 * i + 1]), e2 = ex2(S[4 * i + 2]), e3 = ex2(S[4 * i + 3]);
    a[0] += e0; a[1] += e1; a[2] += e2; a[3] += e3;
    p[2 * i] = pack_bf16(e0, e1);
    p[2 * i + 1] = pack_bf16(e2, e3);
  }
}
#define EARLY 4
__device__ __forceinline__ void softmax_early(float (&S)[64], float cc0, float cc1, float (&a)[4], uint32_t (&pe)[2 * EARLY + 1], const Cons& c) {
  a[0] = a[1] = a[2] = a[3] = 0.f;
  ONCE(c) {
    to_exponent(S, cc0, cc1);
#pragma unroll
    for (int i = 0; i < EARLY; i++) {
      const float e0 = ex2(S[4 * i]), e1 = ex2(S[4 * i + 1]), e2 = ex2(S[4 * i + 2]), e3 = ex2(S[4 * i + 3]);
      a[0] += e0; a[1] += e1; a[2] += e2; a[3] += e3;
      pe[2 * i] = pack_bf16(e0, e1);
      pe[2 * i + 1] = pack_bf16(e2, e3);
    }
  }
}
__device__ __forceinline__ void softmax_late(float (&S)[64], uint32_t (&p)[32], float (&O)[64], float& cc0, float& cc1, float& l0, float& l1,
                                             float (&a)[4], const uint32_t (&pe)[2 * EARLY + 1], uint32_t zero) {
#pragma unroll
  for (int i = 0; i < 2 * EARLY; i++) p[i] = pe[i] ^ zero;
  exp_pack<EARLY>(S, p, a);
  if (__any_sync(~0u, !(fmaxf(a[0] + a[1], a[2] + a[3]) <= 65536.f))) {
    float d0, d1;
    row_max2(S, d0, d1);
    d0 = fmaxf(d0, 0.f); d1 = fmaxf(d1, 0.f);
#pragma unroll
    for (int i = 0; i < 16; i++) { S[4 * i] -= d0; S[4 * i + 1] -= d0; S[4 * i + 2] -= d1; S[4 * i + 3] -= d1; }
    cc0 -= d0; cc1 -= d1;
    const float f0 = ex2(-d0), f1 = ex2(-d1);
    scale_o(O, f0, f1);
    l0 *= f0; l1 *= f1;
    a[0] = a[1] = a[2] = a[3] = 0.f;
    exp_pack<0>(S, p, a);
  }
  l0 += a[0] + a[1];
  l1 += a[2] + a[3];
}

__device__ __forceinline__ void inv_rowsum(float l0, float l1, float& i0, float& i1) {
  l0 += __shfl_xor_sync(~0u, l0, 1); l1 += __shfl_xor_sync(~0u, l1, 1);
  l0 += __shfl_xor_sync(~0u, l0, 2); l1 += __shfl_xor_sync(~0u, l1, 2);
  i0 = rcp(l0); i1 = rcp(l1);
}
__device__ __forceinline__ void write_o(const float (&O)[64], const Cons& c) {
  uint32_t rowoff, xr;
  frag_addr(rowoff, xr);
  const uint32_t stg = c.sb + SM_STG + c.wg * 16384 + rowoff;
#pragma unroll
  for (int kb = 0; kb < 8; kb++)
    stsm4(stg + (kb >> 2) * 8192 + ((32 * (kb & 3)) ^ xr),
          pack_bf16(O[8 * kb], O[8 * kb + 1]), pack_bf16(O[8 * kb + 2], O[8 * kb + 3]),
          pack_bf16(O[8 * kb + 4], O[8 * kb + 5]), pack_bf16(O[8 * kb + 6], O[8 * kb + 7]));
  c.stg_publish();
}

__device__ __forceinline__ void issue_qk(float (&S)[64], const uint32_t (&q)[32], uint32_t s0, uint32_t s1, uint32_t zero) {
  const uint64_t d0 = mkdesc(s0, 16, 1024), d1 = mkdesc(s1, 16, 1024);
#pragma unroll
  for (int kk = 0; kk < 8; kk++)
    wgmma_rs_n128(S, q[4 * kk], q[4 * kk + 1], q[4 * kk + 2], q[4 * kk + 3], (kk < 4 ? d0 : d1) + (kk & 3) * 2, kk > 0 ? 1u : zero);
}
__device__ __forceinline__ void issue_pv(float (&O)[64], const uint32_t (&p)[32], uint32_t s0, uint32_t s1, uint32_t accum) {
  const uint64_t d0 = mkdesc(s0, 8192, 1024), d1 = mkdesc(s1, 8192, 1024);
#pragma unroll
  for (int kk = 0; kk < 8; kk++)
    wgmma_rs_n128_tb(O, p[4 * kk], p[4 * kk + 1], p[4 * kk + 2], p[4 * kk + 3], (kk < 4 ? d0 : d1) + (kk & 3) * 128, kk > 0 ? 1u : accum);
}

#define TURN_SYNC()   bar_sync(1 + c.wg, 256)
#define TURN_PASS()   bar_arrive(2 - c.wg, 256)

__device__ __forceinline__ void attn_tile(const float (&acc)[128], Cons& c, int t) {
  uint32_t q[32], p[32];
  float S[64], O[64];
  const uint32_t stash = c.sb + SM_STG + c.wg * 16384 + ((threadIdx.x >> 5) & 3) * 2048 + c.lane * 16;
#pragma unroll
  for (int i = 0; i < 32; i++) q[i] = pack_bf16(acc[2 * i], acc[2 * i + 1]);
  c.stg_acquire();
#pragma unroll
  for (int i = 0; i < 8; i++)
    sts128(stash + (i >> 2) * 8192 + (i & 3) * 512, pack_bf16(acc[64 + 8 * i], acc[65 + 8 * i]), pack_bf16(acc[66 + 8 * i], acc[67 + 8 * i]),
           pack_bf16(acc[68 + 8 * i], acc[69 + 8 * i]), pack_bf16(acc[70 + 8 * i], acc[71 + 8 * i]));
  fence_regs(q);
  TR(0, 0);
  TURN_SYNC();
  TR(0, 1);
  c.wait_full(c.g);
  wg_fence();
  issue_qk(O, q, c.sb + c.pos * SLOT, c.sb + wrap12(c.pos + 1) * SLOT, 0);
  wg_commit();
  c.wait_full(c.g + 1);
  wg_fence();
  issue_qk(S, q, c.sb + wrap12(c.pos + 2) * SLOT, c.sb + wrap12(c.pos + 3) * SLOT, 0);
  wg_commit();
  TURN_PASS();
  TR(0, 2);
  wg_wait<1>();
  TR(0, 3);
  fence_regs(O);
  c.release(c.g);
  float cc0, cc1, l0, l1, f0 = 0.f, f1 = 0.f;
  float a[4] = {0.f, 0.f, 0.f, 0.f};
  uint32_t pe[2 * EARLY + 1];
  row_max2(O, cc0, cc1);
  cc0 *= -SM_C; cc1 *= -SM_C;
  ONCE(c) { to_exponent(O, cc0, cc1); }
  wg_wait<0>();
  fence_regs(S);
  fence_regs(q);
  c.release(c.g + 1);
  exp_pack<0>(O, p, a);
  l0 = a[0] + a[1];
  l1 = a[2] + a[3];
  c.pos = wrap12(c.pos + 4);
  TR(1, 0);
  TURN_SYNC();
  TR(1, 1);
  c.wait_full(c.g + 2);
  wg_fence();
  issue_pv(O, p, c.sb + c.pos * SLOT, c.sb + wrap12(c.pos + 1) * SLOT, 0);
  wg_commit();
  TURN_PASS();
  TR(1, 2);
  softmax_early(S, cc0, cc1, a, pe, c);
  TR(1, 4);
  wg_wait<0>();
  TR(1, 5);
  fence_regs(O);
  fence_regs(p);
  c.release(c.g + 2);
  c.g += 3;
  c.pos = wrap12(c.pos + 2);
  softmax_late(S, p, O, cc0, cc1, l0, l1, a, pe, c.zero);
#pragma unroll 1
  for (int j = 1; j < 7 + (int)c.zero; j++) {
    const uint32_t k0 = c.pos, k1 = wrap12(k0 + 1), v0 = wrap12(k0 + 2), v1 = wrap12(k0 + 3);
    TR(j + 1, 0);
    TURN_SYNC();
    TR(j + 1, 1);
    c.wait_full(c.g);
    wg_fence();
    issue_qk(S, q, c.sb + k0 * SLOT, c.sb + k1 * SLOT, 0);
    wg_commit();
    if (j == 4) {
      scale_o(O, f0, f1);
      write_o(O, c);
    }
    c.wait_full(c.g + 1);
    wg_fence();
    issue_pv(O, p, c.sb + v0 * SLOT, c.sb + v1 * SLOT, j != 4);
    wg_commit();
    TURN_PASS();
    TR(j + 1, 2);
    wg_wait<1>();
    TR(j + 1, 3);
    fence_regs(S);
    fence_regs(q);
    c.release(c.g);
    if (j == 3) {
      row_max2(S, cc0, cc1);
      cc0 *= -SM_C; cc1 *= -SM_C;
      inv_rowsum(l0, l1, f0, f1);
      l0 = 0.f; l1 = 0.f;
    }
    softmax_early(S, cc0, cc1, a, pe, c);
    if (j == 2) {
#pragma unroll
      for (int i = 0; i < 8; i++) lds128(stash + (i >> 2) * 8192 + (i & 3) * 512, q[4 * i], q[4 * i + 1], q[4 * i + 2], q[4 * i + 3]);
      __syncwarp();
    }
    TR(j + 1, 4);
    wg_wait<0>();
    TR(j + 1, 5);
    fence_regs(O);
    fence_regs(p);
    c.release(c.g + 1);
    c.g += 2;
    c.pos = wrap12(v1 + 1);
    softmax_late(S, p, O, cc0, cc1, l0, l1, a, pe, c.zero);
  }
  TR(8, 0);
  TURN_SYNC();
  TR(8, 1);
  c.wait_full(c.g);
  wg_fence();
  issue_pv(O, p, c.sb + c.pos * SLOT, c.sb + wrap12(c.pos + 1) * SLOT, 1);
  wg_commit();
  TURN_PASS();
  TR(8, 2);
  c.stg_acquire();
  float a0, a1;
  inv_rowsum(l0, l1, a0, a1);
  wg_wait<0>();
  TR(8, 5);
  fence_regs(O);
  fence_regs(p);
  c.release(c.g);
  c.g++;
  c.pos = wrap12(c.pos + 2);
  scale_o(O, a0, a1);
  write_o(O, c);
  TR(9, 0);
}

struct Prod {
  uint32_t sb, g, pos, head, tail_g, tail_pos, hist;
  __device__ __forceinline__ uint32_t full() const { return sb + SM_BAR + B_FULL + (g & 7) * 8; }
  __device__ __forceinline__ uint32_t slot(uint32_t i) const { return sb + wrap12(pos + i) * SLOT; }
  __device__ __forceinline__ void acquire(uint32_t size) {
#pragma unroll 1
    while (head + size - tail_pos > NSLOT) {
      mbar_wait(sb + SM_BAR + B_EMPTY + (tail_g & 7) * 8, (tail_g >> 3) & 1);
      tail_pos += 2 + ((hist >> (tail_g & 31)) & 1);
      tail_g++;
    }
    hist = (hist & ~(1u << (g & 31))) | ((size - 2) << (g & 31));
  }
  __device__ __forceinline__ void advance(uint32_t size) { g++; head += size; pos = wrap12(pos + size); }
};

__device__ __forceinline__ void wait_flag(const unsigned* p, unsigned target) {
  while ((int)(ld_acquire(p) - target) < 0) {}
  fence_async_all();
}

__device__ __forceinline__ void init_barriers(uint32_t sb, int warp) {
  const uint32_t cnt = warp < 4 ? 1 : warp < 8 ? 16 : warp == 8 ? 4 : warp == 9 ? 1 : 11;
  if (warp < 11) mbar_init(sb + SM_BAR + warp * 16, cnt);
  if (warp < 10) mbar_init(sb + SM_BAR + warp * 16 + 8, cnt);
  asm volatile("fence.mbarrier_init.release.cluster;" ::: "memory");
}

#define TSP(i) do {} while (0)

__global__ void __cluster_dims__(2, 1, 1) __launch_bounds__(384, 1) fused_kernel(const __grid_constant__ Params P) {
  extern __shared__ uint8_t smem_raw[];
  const uint32_t sb = (smem_u32(smem_raw) + 1023u) & ~1023u;
  const int warp = __shfl_sync(~0u, (int)(threadIdx.x >> 5), 0);
  const int lane = threadIdx.x & 31;
  const int rank = blockIdx.x & 1;
  const int cl = blockIdx.x >> 1;
  const int j = cl >> 3;
  const int rb = (cl & 7) * 2 + rank;
  const bool is_s = j < 4, spare = j == 8;
  const int row0 = rb * 128;
  Flags* fl = P.flags;

  if (warp >= 8) {
    unsigned ep0 = 0;
    if (warp == 8) asm volatile("ld.volatile.global.u32 %0, [%1];" : "=r"(ep0) : "l"(&fl->epoch[blockIdx.x]));
    if (lane == 0) {
      if (warp == 8) prefetch_map(spare ? &P.w1b4 : &P.w1b3);
      if (warp == 9) prefetch_map(&P.act_ld);
      init_barriers(sb, warp);
    }
    __syncwarp();
    cluster_arrive();
    if (warp == 10 && lane == 0) {
      prefetch_map(&P.act_st); prefetch_map(&P.wq); prefetch_map(&P.k_ld); prefetch_map(&P.v_ld);
      prefetch_map(is_s ? &P.wo : &P.w2); prefetch_map(&P.x_ld); prefetch_map(&P.out_st);
    }
    __syncwarp();
    cluster_wait();
    asm volatile("setmaxnreg.dec.sync.aligned.u32 24;");
    if (warp == 8) {
      TSP(17);
#define ep1 (ep0 + 1)
      Prod p{sb, 0, 0, 0, 0, 0, 0};
#define LDA(dst, m, bar, c0, c1) tma_ld2(dst, m, bar, c0, c1)
#define LDW1(dst, m, bar, c0, c1, c2) tma_ld3_mc(dst, m, bar, c0, c1, c2)
#define LDW(dst, m, bar, c0, c1, c2) tma_ld3_mc(dst, m, bar, c0, c1, c2)
      {
        const CUtensorMap* mb = spare ? &P.w1b4 : &P.w1b3;
        const uint32_t bytes = spare ? 49152 : 40960;
        const int nt = spare ? 8 : 2;
#pragma unroll 1
        for (int t = 0; t < nt; t++) {
          const int r = spare ? ((cl & 1) * 4 + (t >> 1)) * 2 + rank : rb;
          const int nb0 = spare ? (H_SPARE0 >> 6) + (t & 1) * 4 : j * 6 + t * 3;
          int k = 0;
          if (t == 0) {
#pragma unroll 1
            for (; k < 4; k++) {
              p.acquire(3);
              if (lane == 0) { mbar_expect_tx(p.full(), bytes); LDW1(p.slot(1 + rank), mb, p.full(), 0, k * 64 + rank * 32, nb0); }
              p.advance(3);
            }
            TSP(14);
            asm volatile("" : "+r"(ep0));
            wait_flag(&fl->ln[r][0], ep1 * 64);
            TSP(15);
            if (lane == 0)
              for (int i = 0; i < 4; i++) tma_ld2(sb + i * 3 * SLOT, &P.act_ld, sb + SM_BAR + B_FULL + i * 8, C_XN + i * 64, r * 128);
          } else if (spare && !(t & 1)) {
            wait_flag(&fl->ln[r][0], ep1 * 64);
          }
#pragma unroll 1
          for (; k < 16; k++) {
            p.acquire(3);
            if (lane == 0) {
              mbar_expect_tx(p.full(), bytes);
              LDW1(p.slot(1 + rank), mb, p.full(), 0, k * 64 + rank * 32, nb0);
              tma_ld2(p.slot(0), &P.act_ld, p.full(), C_XN + k * 64, r * 128);
            }
            p.advance(3);
          }
        }
      }
      if (!spare) {
        const int kvrow = (j >> 1) * SK + KV0;
#pragma unroll 1
        for (int t = 0; t < 2; t++) {
          const int nb0 = (4 * j + 2 * t) * 2;
#pragma unroll 1
          for (int k = 0; k < 16; k++) {
            p.acquire(3);
            if (lane == 0) {
              mbar_expect_tx(p.full(), 49152);
              LDW1(p.slot(1 + rank), &P.wq, p.full(), 0, k * 64 + rank * 32, nb0);
              tma_ld2(p.slot(0), &P.act_ld, p.full(), C_XN + k * 64, row0);
            }
            p.advance(3);
          }
#pragma unroll 1
          for (int i = 0; i < 16; i++) {
            const bool is_k = i == 0 || (i < 15 && (i & 1));
            const int ch = (is_k ? ((i + 1) >> 1) : (i == 15 ? 7 : (i >> 1) - 1)) & 3;
            p.acquire(2);
            if (lane == 0) {
              mbar_expect_tx(p.full(), 32768);
              if (is_k) tma_ld2_mc(p.slot(rank), &P.k_ld, p.full(), rank * 64, kvrow + ch * 128);
              else      tma_ld3_mc(p.slot(rank), &P.v_ld, p.full(), 0, kvrow + ch * 128 + rank * 64, 0);
            }
            p.advance(2);
            if (t == 1 && i == 4 && !is_s) wait_flag(&fl->h[rb][0], ep1 * 64);
          }
        }
        const int jn = j & 3;
        if (is_s) {
          unsigned ready = 0;
#pragma unroll 1
          for (int i = 0; i < 64; i++) {
            const int hi = i >> 1;
            const int head = 4 * ((hi & 15) >> 1) + (hi & 1) + ((hi >> 4) << 1);
            const int kc = head * 128 + (i & 1) * 64;
            p.acquire(3);
            if (lane == 0) { mbar_expect_tx(p.full(), 49152); LDW(p.slot(1 + rank), &P.wo, p.full(), 0, kc + rank * 32, jn * 4); }
            if (!((ready >> head) & 1)) {
              do { ready = __ballot_sync(~0u, (int)(ld_acquire(&fl->o[rb][lane]) - ep1 * 2) >= 0); } while (!((ready >> head) & 1));
              __syncwarp();
              fence_async_all();
            }
            if (lane == 0) LDA(p.slot(0), &P.act_ld, p.full(), C_O + kc, row0);
            if (i == 52) {
              if (lane == 0) { prefetch_map(&P.x_ld); prefetch_map(&P.out_st); }
              if (lane < 4) tma_pf2(&P.x_ld, jn * 256 + lane * 64, row0);
            }
            p.advance(3);
          }
#pragma unroll 1
          for (int i = 0; i < 4; i++) {
            if (i == 2) { TSP(20); wait_flag(&fl->g[rb][jn], ep1 * 4); TSP(21); }
            p.acquire(2);
            if (lane == 0) {
              mbar_expect_tx(p.full(), 32768);
              const CUtensorMap* m = i < 2 ? &P.x_ld : &P.act_ld;
              const int c0 = (i < 2 ? 0 : C_G) + jn * 256 + (i & 1) * 128;
              tma_ld2(p.slot(0), m, p.full(), c0, row0);
              tma_ld2(p.slot(1), m, p.full(), c0 + 64, row0);
            }
            p.advance(2);
          }
        } else {
#pragma unroll 1
          for (int k = 0; k < 56; k++) {
            p.acquire(3);
            if (lane == 0) { mbar_expect_tx(p.full(), 49152); LDW(p.slot(1 + rank), &P.w2, p.full(), 0, k * 64 + rank * 32, jn * 4); }
            if (k == H_SPARE0 / 64) wait_flag(&fl->h[rb][16], ep1 * 8);
            if (lane == 0) LDA(p.slot(0), &P.act_ld, p.full(), C_H + k * 64, row0);
            p.advance(3);
          }
        }
      }
      if (lane == 0) { *(volatile unsigned*)&fl->epoch[blockIdx.x] = ep1; mbar_arrive(sb + SM_BAR + B_DONE); }
    } else if (warp < 11) {
      const int wg = warp - 9;
      if (lane == 0) {
        const uint32_t stg = sb + SM_STG + wg * 16384;
        const int nev = spare ? 16 : is_s ? 8 : 10;
#pragma unroll 1
        for (int n = 0; n < nev; n++) {
          int col, row = row0, nbox = 2;
          unsigned* flag;
          if (spare) {
            const int r = ((cl & 1) * 4 + (n >> 2)) * 2 + rank;
            row = r * 128;
            col = C_H + H_SPARE0 + (n & 3) * 128;
            flag = &fl->h[r][16];
          } else if (n < 4) {
            col = C_H + j * H_REG + (n >> 1) * 192 + (n & 1) * 128;
            nbox = 2 - (n & 1);
            flag = &fl->h[rb][0];
          } else if (n < 8) {
            col = C_O + (4 * j + n - 4) * 128;
            flag = &fl->o[rb][4 * j + n - 4];
          } else {
            col = C_G + (j & 3) * 256 + (n - 8) * 128;
            flag = &fl->g[rb][j & 3];
          }
          mbar_wait(sb + SM_BAR + B_SFULL + wg * 8, n & 1);
          if (n == 9 && wg == 0) TSP(20);
          tma_st2(&P.act_st, stg, col, row + wg * 64);
          if (nbox == 2) tma_st2(&P.act_st, stg + 8192, col + 64, row + wg * 64);
          bulk_commit();
          bulk_wait_read0();
          mbar_arrive(sb + SM_BAR + B_SEMPTY + wg * 8);
          if (n == 9 && wg == 0) TSP(21);
          bulk_wait0();
          if (n == 9 && wg == 0) TSP(22);
          red_release(flag, 1);
          if (n == 9 && wg == 0) TSP(23);
        }
        mbar_arrive(sb + SM_BAR + B_DONE);
      }
    } else {
      if (lane == 0) {
        const unsigned long long t0 = gtime();
        while (!mbar_try(sb + SM_BAR + B_DONE, 0)) {
          if (gtime() - t0 > 2000000000ull) __trap();
        }
      }
    }
    __syncwarp();
    cluster_arrive();
    cluster_wait();
  } else {
    const int wg = warp >> 2;
    TS(0);
    if (!spare) {
      const int r = row0 + j * 16 + warp * 2;
      uint32_t v[2][16];
#pragma unroll
      for (int a = 0; a < 2; a++)
#pragma unroll
        for (int i = 0; i < 4; i++)
          *(uint4*)&v[a][4 * i] = __ldg((const uint4*)(P.x + (size_t)(r + a) * DM + i * 256 + lane * 8));
      if (lane == 0) init_barriers(sb, warp);
      __syncwarp();
      cluster_arrive();
      float s[2], q[2];
#pragma unroll
      for (int a = 0; a < 2; a++) {
        float t0 = 0.f, t1 = 0.f;
#pragma unroll
        for (int i = 0; i < 16; i++) { t0 += bf_lo(v[a][i]); t1 += bf_hi(v[a][i]); }
        s[a] = t0 + t1;
      }
#pragma unroll
      for (int o = 16; o; o >>= 1) { s[0] += __shfl_xor_sync(~0u, s[0], o); s[1] += __shfl_xor_sync(~0u, s[1], o); }
#pragma unroll
      for (int a = 0; a < 2; a++) {
        s[a] *= 1.0f / DM;
        float t0 = 0.f, t1 = 0.f;
#pragma unroll
        for (int i = 0; i < 16; i++) {
          const float d0 = bf_lo(v[a][i]) - s[a], d1 = bf_hi(v[a][i]) - s[a];
          t0 = fmaf(d0, d0, t0); t1 = fmaf(d1, d1, t1);
        }
        q[a] = t0 + t1;
      }
#pragma unroll
      for (int o = 16; o; o >>= 1) { q[0] += __shfl_xor_sync(~0u, q[0], o); q[1] += __shfl_xor_sync(~0u, q[1], o); }
#pragma unroll
      for (int a = 0; a < 2; a++) {
        const uint32_t mb2 = pack_bf16(s[a], s[a]);
        const float inv = 1.0f / bf_round(sqrtf(bf_round(bf_round(q[a] * (1.0f / DM)) + 1e-5f)));
#pragma unroll
        for (int i = 0; i < 16; i++) {
          const __nv_bfloat162 d = __hsub2_rn(*(const __nv_bfloat162*)&v[a][i], *(const __nv_bfloat162*)&mb2);
          const uint32_t du = *(const uint32_t*)&d;
          v[a][i] = pack_bf16(bf_lo(du) * inv, bf_hi(du) * inv);
        }
#pragma unroll
        for (int i = 0; i < 4; i++)
          sts128(sb + SM_STG + warp * 4096 + a * 2048 + i * 512 + lane * 16, v[a][4 * i], v[a][4 * i + 1], v[a][4 * i + 2], v[a][4 * i + 3]);
      }
      TS(11);
      fence_async_smem();
      __syncwarp();
      if (lane == 0) {
#pragma unroll
        for (int a = 0; a < 2; a++)
          asm volatile("cp.async.bulk.global.shared::cta.bulk_group [%0], [%1], 2048;"
                       ::"l"(P.act + (size_t)(r + a) * ACT_W + C_XN), "r"(sb + SM_STG + warp * 4096 + a * 2048) : "memory");
        bulk_commit();
        bulk_wait0();
        TS(12);
        red_release(&fl->ln[rb][0], 1);
      }
      __syncwarp();
      TS(13);
    } else {
      if (lane == 0) init_barriers(sb, warp);
      __syncwarp();
      cluster_arrive();
    }
    cluster_wait();
    asm volatile("setmaxnreg.inc.sync.aligned.u32 240;");
    Cons c;
    c.zero = blockIdx.y; c.sb = sb; c.g = 0; c.pos = 0; c.nstg = 0; c.wg = wg; c.lane = lane;
    c.rel = mapa(sb + SM_BAR + B_EMPTY, lane & 1);
    float acc[128];
    TS(1);
    if (spare) {
      uint32_t pend[32];
#pragma unroll
      for (int i = 0; i < 32; i++) pend[i] = 0;
#pragma unroll 1
      for (int t = 0; t < 8; t++) {
        gemm_loop_flush<256, 2>(acc, c, pend, t > 0);
        h_epilogue<2>(acc, c, pend);
      }
      c.stg_acquire();
      stage_boxes<2>(pend, 0, c);
      TS(6);
    } else {
      if (wg == 1) bar_arrive(1, 256);
      {
        uint32_t pend[16];
#pragma unroll
        for (int i = 0; i < 16; i++) pend[i] = 0;
#pragma unroll 1
        for (int t = 0; t < 2; t++) {
          gemm_loop_flush<192, 1>(acc, c, pend, t > 0);
          h_epilogue<1>(acc, c, pend);
          TS(2 + t);
        }
        gemm_loop_flush<256, 1>(acc, c, pend, true);
      }
#pragma unroll 1
      for (int t = 0; t < 2; t++) {
        TS(8 + t);
        attn_tile(acc, c, t);
        TS(4 + t);
        gemm_loop<256>(acc, c, t == 0 ? 16 : is_s ? 64 : 56);
      }
      TS(6);
      uint32_t rowoff, xr;
      frag_addr(rowoff, xr);
      if (is_s) {
        const uint32_t x0 = c.pos;
#pragma unroll
        for (int b = 0; b < 4; b++) {
          if ((b & 1) == 0) { c.wait_full(c.g + (b >> 1)); c.wait_full(c.g + 2 + (b >> 1)); }
          if (b == 0) TS(22);
          if (b == 2) TS(23);
          const uint32_t xs = sb + wrap12(x0 + b) * SLOT + wg * 8192;
          const uint32_t sx = xs + rowoff, sg = sb + wrap12(wrap12(x0 + 4) + b) * SLOT + wg * 8192 + rowoff;
          uint32_t xv[16], gv[16];
#pragma unroll
          for (int kb = 0; kb < 4; kb++) {
            ldsm4(sx + ((32 * kb) ^ xr), xv[4 * kb], xv[4 * kb + 1], xv[4 * kb + 2], xv[4 * kb + 3]);
            ldsm4(sg + ((32 * kb) ^ xr), gv[4 * kb], gv[4 * kb + 1], gv[4 * kb + 2], gv[4 * kb + 3]);
          }
#pragma unroll
          for (int i = 0; i < 16; i++) {
            const uint32_t s2 = pack_bf16(acc[32 * b + 2 * i], acc[32 * b + 2 * i + 1]);
            const __nv_bfloat162 pr = __hmul2_rn(*(const __nv_bfloat162*)&s2, *(const __nv_bfloat162*)&gv[i]);
            const __nv_bfloat162 o = __hadd2_rn(*(const __nv_bfloat162*)&xv[i], pr);
            xv[i] = *(const uint32_t*)&o;
          }
#pragma unroll
          for (int kb = 0; kb < 4; kb++) stsm4(sx + ((32 * kb) ^ xr), xv[4 * kb], xv[4 * kb + 1], xv[4 * kb + 2], xv[4 * kb + 3]);
          fence_async_smem();
          __syncwarp();
          if (lane == 0) {
            tma_st2(&P.out_st, xs + (warp & 3) * 2048, (j & 3) * 256 + b * 64, row0 + warp * 16);
            bulk_commit();
          }
        }
        TS(24);
        if (lane == 0) bulk_wait_read0();
      } else {
        const uint32_t stg = sb + SM_STG + wg * 16384 + rowoff;
#pragma unroll
        for (int hh = 0; hh < 2; hh++) {
#pragma unroll
          for (int bx = 0; bx < 2; bx++) {
            uint32_t r[16];
            ONCE(c) {
#pragma unroll
              for (int i = 0; i < 16; i++) r[i] = silu2(pack_bf16(acc[64 * hh + 32 * bx + 2 * i], acc[64 * hh + 32 * bx + 2 * i + 1]) ^ once_);
            }
            if (bx == 0) c.stg_acquire();
#pragma unroll
            for (int kb = 0; kb < 4; kb++) stsm4(stg + bx * 8192 + ((32 * kb) ^ xr), r[4 * kb], r[4 * kb + 1], r[4 * kb + 2], r[4 * kb + 3]);
          }
          c.stg_publish();
          if (hh == 0) TS(22);
        }
      }
    }
    TS(7);
    __syncwarp();
    if (lane == 0) mbar_arrive(sb + SM_BAR + B_DONE);
    cluster_arrive();
    cluster_wait();
  }
}

typedef CUresult (*EncodeFn)(CUtensorMap*, CUtensorMapDataType, cuuint32_t, void*, const cuuint64_t*, const cuuint64_t*,
                             const cuuint32_t*, const cuuint32_t*, CUtensorMapInterleave, CUtensorMapSwizzle,
                             CUtensorMapL2promotion, CUtensorMapFloatOOBfill);

void map2d(EncodeFn enc, CUtensorMap* m, const void* base, uint64_t cols, uint64_t rows, uint32_t box_rows) {
  cuuint64_t dims[2] = {cols, rows};
  cuuint64_t strides[1] = {cols * 2};
  cuuint32_t box[2] = {64, box_rows};
  cuuint32_t es[2] = {1, 1};
  enc(m, CU_TENSOR_MAP_DATA_TYPE_BFLOAT16, 2, (void*)base, dims, strides, box, es, CU_TENSOR_MAP_INTERLEAVE_NONE,
      CU_TENSOR_MAP_SWIZZLE_128B, CU_TENSOR_MAP_L2_PROMOTION_L2_256B, CU_TENSOR_MAP_FLOAT_OOB_FILL_NONE);
}
void map3d(EncodeFn enc, CUtensorMap* m, const void* base, uint64_t cols, uint64_t rows, uint32_t box_rows, uint32_t box_blks) {
  cuuint64_t dims[3] = {64, rows, cols / 64};
  cuuint64_t strides[2] = {cols * 2, 128};
  cuuint32_t box[3] = {64, box_rows, box_blks};
  cuuint32_t es[3] = {1, 1, 1};
  enc(m, CU_TENSOR_MAP_DATA_TYPE_BFLOAT16, 3, (void*)base, dims, strides, box, es, CU_TENSOR_MAP_INTERLEAVE_NONE,
      CU_TENSOR_MAP_SWIZZLE_128B, CU_TENSOR_MAP_L2_PROMOTION_L2_256B, CU_TENSOR_MAP_FLOAT_OOB_FILL_NONE);
}

}

extern "C" void kernel_launch(void* const* d_in, const int* in_sizes, int n_in, void* d_out, int out_size) {
  (void)in_sizes; (void)n_in; (void)out_size;
  static EncodeFn enc = nullptr;
  static void* act = nullptr;
  static void* flags = nullptr;
  if (!enc) {
    void* fn = nullptr;
    cudaDriverEntryPointQueryResult qr;
    cudaGetDriverEntryPoint("cuTensorMapEncodeTiled", &fn, cudaEnableDefault, &qr);
    enc = (EncodeFn)fn;
    cudaGetSymbolAddress(&act, g_act);
    cudaGetSymbolAddress(&flags, g_flags);
    cudaFuncSetAttribute(fused_kernel, cudaFuncAttributeMaxDynamicSharedMemorySize, SMEM_BYTES);
  }
  Params P;
  map2d(enc, &P.act_ld, act, ACT_W, SEQ, 128);
  map2d(enc, &P.act_st, act, ACT_W, SEQ, 64);
  map2d(enc, &P.x_ld, d_in[0], DM, SEQ, 128);
  map2d(enc, &P.out_st, d_out, DM, SEQ, 16);
  map2d(enc, &P.k_ld, d_in[1], 128, 4 * SK, 128);
  map3d(enc, &P.v_ld, d_in[2], 128, 4 * SK, 64, 2);
  map3d(enc, &P.wq, d_in[3], NQ, DM, 32, 4);
  map3d(enc, &P.w1b4, d_in[6], DFF, DM, 32, 4);
  map3d(enc, &P.w1b3, d_in[6], DFF, DM, 32, 3);
  map3d(enc, &P.wo, d_in[4], DM, NQ, 32, 4);
  map3d(enc, &P.w2, d_in[7], DM, DFF, 32, 4);
  P.x = (const __nv_bfloat16*)d_in[0];
  P.act = (__nv_bfloat16*)act;
  P.flags = (Flags*)flags;
  fused_kernel<<<NCLUSTER * 2, 384, SMEM_BYTES>>>(P);
}
```

```cpp
#include <cuda_runtime.h>
#include <cuda_bf16.h>
#include <cuda.h>
#include <stdint.h>

namespace {

constexpr int SEQ    = 2048;
constexpr int DM     = 1024;
constexpr int NQ     = 4096;
constexpr int DFF    = 3584;
constexpr int SK     = 2048;
constexpr int WIN    = 512;
constexpr int KV0    = SK - WIN;
constexpr int C_XN = 0, C_O = 1024, C_H = 5120, C_G = 8704, ACT_W = 9728;

constexpr int H_REG = 384, H_SPARE0 = 8 * H_REG;
static_assert(H_SPARE0 + 512 == DFF, "H split");

constexpr int NSLOT = 12, SLOT = 16384, NBAR = 8;
constexpr int SM_STG = NSLOT * SLOT;
constexpr int SM_BAR = SM_STG + 2 * 16384;
constexpr int SMEM_BYTES = SM_BAR + 256 + 1024;
constexpr int B_FULL = 0, B_EMPTY = 64, B_SFULL = 128, B_SEMPTY = 144, B_DONE = 160;

constexpr int NCLUSTER = 66;

struct Flags {
  unsigned ln[16][32];
  unsigned h[16][32];
  unsigned o[16][32];
  unsigned g[16][32];
  unsigned epoch[160];
};
__device__ __nv_bfloat16 g_act[(size_t)SEQ * ACT_W];
__device__ Flags g_flags;

struct Params {
  CUtensorMap act_ld, act_st, x_ld, out_st, k_ld, v_ld, wq, w1b4, w1b3, wo, w2;
  const __nv_bfloat16* x;
  __nv_bfloat16* act;
  Flags* flags;
};

__device__ __forceinline__ uint32_t smem_u32(const void* p) { return (uint32_t)__cvta_generic_to_shared(p); }
__device__ __forceinline__ void mbar_init(uint32_t bar, uint32_t cnt) {
  asm volatile("mbarrier.init.shared::cta.b64 [%0], %1;" ::"r"(bar), "r"(cnt) : "memory");
}
__device__ __forceinline__ bool mbar_try(uint32_t bar, uint32_t parity) {
  uint32_t ok;
  asm volatile("{\n.reg .pred p;\nmbarrier.try_wait.parity.shared::cta.b64 p, [%1], %2;\nselp.u32 %0, 1, 0, p;\n}\n"
               : "=r"(ok) : "r"(bar), "r"(parity) : "memory");
  return ok;
}
__device__ __forceinline__ void mbar_wait(uint32_t bar, uint32_t parity) {
  asm volatile("{\n.reg .pred p;\nWAIT_%=:\nmbarrier.try_wait.parity.shared::cta.b64 p, [%0], %1;\n@p bra DONE_%=;\nbra WAIT_%=;\nDONE_%=:\n}\n"
               ::"r"(bar), "r"(parity) : "memory");
}
__device__ __forceinline__ void mbar_arrive(uint32_t bar) {
  asm volatile("mbarrier.arrive.shared::cta.b64 _, [%0];" ::"r"(bar) : "memory");
}
__device__ __forceinline__ void mbar_arrive_cluster(uint32_t cluster_addr) {
  asm volatile("mbarrier.arrive.shared::cluster.b64 _, [%0];" ::"r"(cluster_addr) : "memory");
}
__device__ __forceinline__ void mbar_expect_tx(uint32_t bar, uint32_t bytes) {
  asm volatile("mbarrier.arrive.expect_tx.shared::cta.b64 _, [%0], %1;" ::"r"(bar), "r"(bytes) : "memory");
}
__device__ __forceinline__ uint32_t mapa(uint32_t addr, uint32_t rank) {
  uint32_t r;
  asm("mapa.shared::cluster.u32 %0, %1, %2;" : "=r"(r) : "r"(addr), "r"(rank));
  return r;
}
__device__ __forceinline__ void cluster_arrive() { asm volatile("barrier.cluster.arrive.relaxed.aligned;" ::: "memory"); }
__device__ __forceinline__ void cluster_wait() { asm volatile("barrier.cluster.wait.acquire.aligned;" ::: "memory"); }
__device__ __forceinline__ void bar_sync(int id, int n) { asm volatile("bar.sync %0, %1;" ::"r"(id), "r"(n) : "memory"); }
__device__ __forceinline__ void bar_arrive(int id, int n) { asm volatile("bar.arrive %0, %1;" ::"r"(id), "r"(n) : "memory"); }
__device__ __forceinline__ void fence_async_smem() { asm volatile("fence.proxy.async.shared::cta;" ::: "memory"); }
__device__ __forceinline__ void fence_async_all() { asm volatile("fence.proxy.async.global;" ::: "memory"); }

__device__ __forceinline__ void tma_ld2(uint32_t dst, const CUtensorMap* m, uint32_t bar, int c0, int c1) {
  asm volatile("cp.async.bulk.tensor.2d.shared::cluster.global.mbarrier::complete_tx::bytes [%0], [%1, {%3, %4}], [%2];"
               ::"r"(dst), "l"(m), "r"(bar), "r"(c0), "r"(c1) : "memory");
}
__device__ __forceinline__ void tma_ld2_mc(uint32_t dst, const CUtensorMap* m, uint32_t bar, int c0, int c1) {
  asm volatile("cp.async.bulk.tensor.2d.shared::cluster.global.mbarrier::complete_tx::bytes.multicast::cluster [%0], [%1, {%3, %4}], [%2], %5;"
               ::"r"(dst), "l"(m), "r"(bar), "r"(c0), "r"(c1), "h"((uint16_t)3) : "memory");
}
__device__ __forceinline__ void tma_ld3_mc(uint32_t dst, const CUtensorMap* m, uint32_t bar, int c0, int c1, int c2) {
  asm volatile("cp.async.bulk.tensor.3d.shared::cluster.global.mbarrier::complete_tx::bytes.multicast::cluster [%0], [%1, {%3, %4, %5}], [%2], %6;"
               ::"r"(dst), "l"(m), "r"(bar), "r"(c0), "r"(c1), "r"(c2), "h"((uint16_t)3) : "memory");
}
__device__ __forceinline__ void tma_ld3_mc_hint(uint32_t dst, const CUtensorMap* m, uint32_t bar, int c0, int c1, int c2, uint64_t pol) {
  asm volatile("cp.async.bulk.tensor.3d.shared::cluster.global.mbarrier::complete_tx::bytes.multicast::cluster.L2::cache_hint [%0], [%1, {%3, %4, %5}], [%2], %6, %7;"
               ::"r"(dst), "l"(m), "r"(bar), "r"(c0), "r"(c1), "r"(c2), "h"((uint16_t)3), "l"(pol) : "memory");
}
__device__ __forceinline__ void tma_ld2_hint(uint32_t dst, const CUtensorMap* m, uint32_t bar, int c0, int c1, uint64_t pol) {
  asm volatile("cp.async.bulk.tensor.2d.shared::cluster.global.mbarrier::complete_tx::bytes.L2::cache_hint [%0], [%1, {%3, %4}], [%2], %5;"
               ::"r"(dst), "l"(m), "r"(bar), "r"(c0), "r"(c1), "l"(pol) : "memory");
}
__device__ __forceinline__ void tma_st2_hint(const CUtensorMap* m, uint32_t src, int c0, int c1, uint64_t pol) {
  asm volatile("cp.async.bulk.tensor.2d.global.shared::cta.bulk_group.L2::cache_hint [%0, {%2, %3}], [%1], %4;"
               ::"l"(m), "r"(src), "r"(c0), "r"(c1), "l"(pol) : "memory");
}
#define POL_FIRST 0x12F0000000000000ull
__device__ __forceinline__ uint64_t policy_evict_first() {
  uint64_t p;
  asm volatile("createpolicy.fractional.L2::evict_first.b64 %0, 1.0;" : "=l"(p));
  return p;
}
__device__ __forceinline__ void tma_st2(const CUtensorMap* m, uint32_t src, int c0, int c1) {
  asm volatile("cp.async.bulk.tensor.2d.global.shared::cta.bulk_group [%0, {%2, %3}], [%1];"
               ::"l"(m), "r"(src), "r"(c0), "r"(c1) : "memory");
}
__device__ __forceinline__ void tma_pf2(const CUtensorMap* m, int c0, int c1) {
  asm volatile("cp.async.bulk.prefetch.tensor.2d.L2.global [%0, {%1, %2}];" ::"l"(m), "r"(c0), "r"(c1) : "memory");
}
__device__ __forceinline__ void bulk_commit() { asm volatile("cp.async.bulk.commit_group;" ::: "memory"); }
__device__ __forceinline__ void bulk_wait_read0() { asm volatile("cp.async.bulk.wait_group.read 0;" ::: "memory"); }
__device__ __forceinline__ void bulk_wait0() { asm volatile("cp.async.bulk.wait_group 0;" ::: "memory"); }
__device__ __forceinline__ void prefetch_map(const CUtensorMap* m) {
  asm volatile("prefetch.tensormap [%0];" ::"l"(m) : "memory");
}
__device__ __forceinline__ unsigned ld_acquire(const unsigned* p) {
  unsigned v;
  asm volatile("ld.acquire.gpu.global.u32 %0, [%1];" : "=r"(v) : "l"(p) : "memory");
  return v;
}
__device__ __forceinline__ void red_release(unsigned* p, unsigned v) {
  asm volatile("red.release.gpu.global.add.u32 [%0], %1;" ::"l"(p), "r"(v) : "memory");
}
__device__ __forceinline__ void wg_fence() { asm volatile("wgmma.fence.sync.aligned;" ::: "memory"); }
__device__ __forceinline__ void wg_commit() { asm volatile("wgmma.commit_group.sync.aligned;" ::: "memory"); }
template <int N> __device__ __forceinline__ void wg_wait() { asm volatile("wgmma.wait_group.sync.aligned %0;" ::"n"(N) : "memory"); }
template <int N> __device__ __forceinline__ void fence_regs(float (&d)[N]) {
#pragma unroll
  for (int i = 0; i < N; i++) asm volatile("" : "+f"(d[i])::"memory");
}
template <int N> __device__ __forceinline__ void fence_regs(uint32_t (&d)[N]) {
#pragma unroll
  for (int i = 0; i < N; i++) asm volatile("" : "+r"(d[i])::"memory");
}
__device__ __forceinline__ uint64_t mkdesc(uint32_t addr, uint32_t lbo, uint32_t sbo) {
  return (uint64_t)((addr & 0x3FFFF) >> 4) | ((uint64_t)(lbo >> 4) << 16) | ((uint64_t)(sbo >> 4) << 32) | (1ull << 62);
}
__device__ __forceinline__ uint32_t pack_bf16(float lo, float hi) {
  uint32_t r;
  asm("cvt.rn.bf16x2.f32 %0, %1, %2;" : "=r"(r) : "f"(hi), "f"(lo));
  return r;
}
__device__ __forceinline__ uint32_t pack_bf16_relu(float lo, float hi) {
  uint32_t r;
  asm("cvt.rn.relu.bf16x2.f32 %0, %1, %2;" : "=r"(r) : "f"(hi), "f"(lo));
  return r;
}
__device__ __forceinline__ float bf_lo(uint32_t v) { return __uint_as_float(v << 16); }
__device__ __forceinline__ float bf_hi(uint32_t v) { return __uint_as_float(v & 0xFFFF0000u); }
__device__ __forceinline__ float bf_round(float v) { return bf_lo(pack_bf16(v, v)); }
__device__ __forceinline__ float ex2(float x) {
  float r;
  asm("ex2.approx.ftz.f32 %0, %1;" : "=f"(r) : "f"(x));
  return r;
}
__device__ __forceinline__ float rcp(float x) {
  float r;
  asm("rcp.approx.ftz.f32 %0, %1;" : "=f"(r) : "f"(x));
  return r;
}
__device__ __forceinline__ uint32_t tid_x() {
  uint32_t t;
  asm volatile("mov.u32 %0, %%tid.x;" : "=r"(t));
  return t;
}
__device__ __forceinline__ void stsm4(uint32_t addr, uint32_t r0, uint32_t r1, uint32_t r2, uint32_t r3) {
  asm volatile("stmatrix.sync.aligned.m8n8.x4.shared.b16 [%0], {%1, %2, %3, %4};" ::"r"(addr), "r"(r0), "r"(r1), "r"(r2), "r"(r3) : "memory");
}
__device__ __forceinline__ void ldsm4(uint32_t addr, uint32_t& r0, uint32_t& r1, uint32_t& r2, uint32_t& r3) {
  asm volatile("ldmatrix.sync.aligned.m8n8.x4.shared.b16 {%0, %1, %2, %3}, [%4];" : "=r"(r0), "=r"(r1), "=r"(r2), "=r"(r3) : "r"(addr) : "memory");
}
__device__ __forceinline__ void sts128(uint32_t addr, uint32_t r0, uint32_t r1, uint32_t r2, uint32_t r3) {
  asm volatile("st.shared.v4.b32 [%0], {%1, %2, %3, %4};" ::"r"(addr), "r"(r0), "r"(r1), "r"(r2), "r"(r3) : "memory");
}
__device__ __forceinline__ void lds128(uint32_t addr, uint32_t& r0, uint32_t& r1, uint32_t& r2, uint32_t& r3) {
  asm volatile("ld.shared.v4.b32 {%0, %1, %2, %3}, [%4];" : "=r"(r0), "=r"(r1), "=r"(r2), "=r"(r3) : "r"(addr) : "memory");
}
__device__ __forceinline__ unsigned long long gtime() {
  unsigned long long t;
  asm volatile("mov.u64 %0, %globaltimer;" : "=l"(t));
  return t;
}

__device__ __forceinline__ void wgmma_ss_n256_tb(float (&d)[128], uint64_t da, uint64_t db, uint32_t sc) {
  asm volatile("{\n.reg .pred p;\nsetp.ne.b32 p, %130, 0;\n"
    "wgmma.mma_async.sync.aligned.m64n256k16.f32.bf16.bf16 "
    "{%0, %1, %2, %3, %4, %5, %6, %7, %8, %9, %10, %11, %12, %13, %14, %15, %16, %17, %18, %19, %20, %21, %22, %23, %24, %25, %26, %27, %28, %29, %30, %31, %32, %33, %34, %35, %36, %37, %38, %39, %40, %41, %42, %43, %44, %45, %46, %47, %48, %49, %50, %51, %52, %53, %54, %55, %56, %57, %58, %59, %60, %61, %62, %63, %64, %65, %66, %67, %68, %69, %70, %71, %72, %73, %74, %75, %76, %77, %78, %79, %80, %81, %82, %83, %84, %85, %86, %87, %88, %89, %90, %91, %92, %93, %94, %95, %96, %97, %98, %99, %100, %101, %102, %103, %104, %105, %106, %107, %108, %109, %110, %111, %112, %113, %114, %115, %116, %117, %118, %119, %120, %121, %122, %123, %124, %125, %126, %127}, %128, %129, p, 1, 1, 0, 1;\n}\n"
    : "+f"(d[0]), "+f"(d[1]), "+f"(d[2]), "+f"(d[3]), "+f"(d[4]), "+f"(d[5]), "+f"(d[6]), "+f"(d[7]), "+f"(d[8]), "+f"(d[9]), "+f"(d[10]), "+f"(d[11]), "+f"(d[12]), "+f"(d[13]), "+f"(d[14]), "+f"(d[15]), "+f"(d[16]), "+f"(d[17]), "+f"(d[18]), "+f"(d[19]), "+f"(d[20]), "+f"(d[21]), "+f"(d[22]), "+f"(d[23]), "+f"(d[24]), "+f"(d[25]), "+f"(d[26]), "+f"(d[27]), "+f"(d[28]), "+f"(d[29]), "+f"(d[30]), "+f"(d[31]), "+f"(d[32]), "+f"(d[33]), "+f"(d[34]), "+f"(d[35]), "+f"(d[36]), "+f"(d[37]), "+f"(d[38]), "+f"(d[39]), "+f"(d[40]), "+f"(d[41]), "+f"(d[42]), "+f"(d[43]), "+f"(d[44]), "+f"(d[45]), "+f"(d[46]), "+f"(d[47]), "+f"(d[48]), "+f"(d[49]), "+f"(d[50]), "+f"(d[51]), "+f"(d[52]), "+f"(d[53]), "+f"(d[54]), "+f"(d[55]), "+f"(d[56]), "+f"(d[57]), "+f"(d[58]), "+f"(d[59]), "+f"(d[60]), "+f"(d[61]), "+f"(d[62]), "+f"(d[63]), "+f"(d[64]), "+f"(d[65]), "+f"(d[66]), "+f"(d[67]), "+f"(d[68]), "+f"(d[69]), "+f"(d[70]), "+f"(d[71]), "+f"(d[72]), "+f"(d[73]), "+f"(d[74]), "+f"(d[75]), "+f"(d[76]), "+f"(d[77]), "+f"(d[78]), "+f"(d[79]), "+f"(d[80]), "+f"(d[81]), "+f"(d[82]), "+f"(d[83]), "+f"(d[84]), "+f"(d[85]), "+f"(d[86]), "+f"(d[87]), "+f"(d[88]), "+f"(d[89]), "+f"(d[90]), "+f"(d[91]), "+f"(d[92]), "+f"(d[93]), "+f"(d[94]), "+f"(d[95]), "+f"(d[96]), "+f"(d[97]), "+f"(d[98]), "+f"(d[99]), "+f"(d[100]), "+f"(d[101]), "+f"(d[102]), "+f"(d[103]), "+f"(d[104]), "+f"(d[105]), "+f"(d[106]), "+f"(d[107]), "+f"(d[108]), "+f"(d[109]), "+f"(d[110]), "+f"(d[111]), "+f"(d[112]), "+f"(d[113]), "+f"(d[114]), "+f"(d[115]), "+f"(d[116]), "+f"(d[117]), "+f"(d[118]), "+f"(d[119]), "+f"(d[120]), "+f"(d[121]), "+f"(d[122]), "+f"(d[123]), "+f"(d[124]), "+f"(d[125]), "+f"(d[126]), "+f"(d[127])
    : "l"(da), "l"(db), "r"(sc));
}
__device__ __forceinline__ void wgmma_ss_n192_tb(float (&d)[128], uint64_t da, uint64_t db, uint32_t sc) {
  asm volatile("{\n.reg .pred p;\nsetp.ne.b32 p, %98, 0;\n"
    "wgmma.mma_async.sync.aligned.m64n192k16.f32.bf16.bf16 "
    "{%0, %1, %2, %3, %4, %5, %6, %7, %8, %9, %10, %11, %12, %13, %14, %15, %16, %17, %18, %19, %20, %21, %22, %23, %24, %25, %26, %27, %28, %29, %30, %31, %32, %33, %34, %35, %36, %37, %38, %39, %40, %41, %42, %43, %44, %45, %46, %47, %48, %49, %50, %51, %52, %53, %54, %55, %56, %57, %58, %59, %60, %61, %62, %63, %64, %65, %66, %67, %68, %69, %70, %71, %72, %73, %74, %75, %76, %77, %78, %79, %80, %81, %82, %83, %84, %85, %86, %87, %88, %89, %90, %91, %92, %93, %94, %95}, %96, %97, p, 1, 1, 0, 1;\n}\n"
    : "+f"(d[0]), "+f"(d[1]), "+f"(d[2]), "+f"(d[3]), "+f"(d[4]), "+f"(d[5]), "+f"(d[6]), "+f"(d[7]), "+f"(d[8]), "+f"(d[9]), "+f"(d[10]), "+f"(d[11]), "+f"(d[12]), "+f"(d[13]), "+f"(d[14]), "+f"(d[15]), "+f"(d[16]), "+f"(d[17]), "+f"(d[18]), "+f"(d[19]), "+f"(d[20]), "+f"(d[21]), "+f"(d[22]), "+f"(d[23]), "+f"(d[24]), "+f"(d[25]), "+f"(d[26]), "+f"(d[27]), "+f"(d[28]), "+f"(d[29]), "+f"(d[30]), "+f"(d[31]), "+f"(d[32]), "+f"(d[33]), "+f"(d[34]), "+f"(d[35]), "+f"(d[36]), "+f"(d[37]), "+f"(d[38]), "+f"(d[39]), "+f"(d[40]), "+f"(d[41]), "+f"(d[42]), "+f"(d[43]), "+f"(d[44]), "+f"(d[45]), "+f"(d[46]), "+f"(d[47]), "+f"(d[48]), "+f"(d[49]), "+f"(d[50]), "+f"(d[51]), "+f"(d[52]), "+f"(d[53]), "+f"(d[54]), "+f"(d[55]), "+f"(d[56]), "+f"(d[57]), "+f"(d[58]), "+f"(d[59]), "+f"(d[60]), "+f"(d[61]), "+f"(d[62]), "+f"(d[63]), "+f"(d[64]), "+f"(d[65]), "+f"(d[66]), "+f"(d[67]), "+f"(d[68]), "+f"(d[69]), "+f"(d[70]), "+f"(d[71]), "+f"(d[72]), "+f"(d[73]), "+f"(d[74]), "+f"(d[75]), "+f"(d[76]), "+f"(d[77]), "+f"(d[78]), "+f"(d[79]), "+f"(d[80]), "+f"(d[81]), "+f"(d[82]), "+f"(d[83]), "+f"(d[84]), "+f"(d[85]), "+f"(d[86]), "+f"(d[87]), "+f"(d[88]), "+f"(d[89]), "+f"(d[90]), "+f"(d[91]), "+f"(d[92]), "+f"(d[93]), "+f"(d[94]), "+f"(d[95])
    : "l"(da), "l"(db), "r"(sc));
}
__device__ __forceinline__ void wgmma_rs_n128(float (&d)[64], uint32_t a0, uint32_t a1, uint32_t a2, uint32_t a3, uint64_t db, uint32_t sc) {
  asm volatile("{\n.reg .pred p;\nsetp.ne.b32 p, %69, 0;\n"
    "wgmma.mma_async.sync.aligned.m64n128k16.f32.bf16.bf16 "
    "{%0, %1, %2, %3, %4, %5, %6, %7, %8, %9, %10, %11, %12, %13, %14, %15, %16, %17, %18, %19, %20, %21, %22, %23, %24, %25, %26, %27, %28, %29, %30, %31, %32, %33, %34, %35, %36, %37, %38, %39, %40, %41, %42, %43, %44, %45, %46, %47, %48, %49, %50, %51, %52, %53, %54, %55, %56, %57, %58, %59, %60, %61, %62, %63}, {%64, %65, %66, %67}, %68, p, 1, 1, 0;\n}\n"
    : "+f"(d[0]), "+f"(d[1]), "+f"(d[2]), "+f"(d[3]), "+f"(d[4]), "+f"(d[5]), "+f"(d[6]), "+f"(d[7]), "+f"(d[8]), "+f"(d[9]), "+f"(d[10]), "+f"(d[11]), "+f"(d[12]), "+f"(d[13]), "+f"(d[14]), "+f"(d[15]), "+f"(d[16]), "+f"(d[17]), "+f"(d[18]), "+f"(d[19]), "+f"(d[20]), "+f"(d[21]), "+f"(d[22]), "+f"(d[23]), "+f"(d[24]), "+f"(d[25]), "+f"(d[26]), "+f"(d[27]), "+f"(d[28]), "+f"(d[29]), "+f"(d[30]), "+f"(d[31]), "+f"(d[32]), "+f"(d[33]), "+f"(d[34]), "+f"(d[35]), "+f"(d[36]), "+f"(d[37]), "+f"(d[38]), "+f"(d[39]), "+f"(d[40]), "+f"(d[41]), "+f"(d[42]), "+f"(d[43]), "+f"(d[44]), "+f"(d[45]), "+f"(d[46]), "+f"(d[47]), "+f"(d[48]), "+f"(d[49]), "+f"(d[50]), "+f"(d[51]), "+f"(d[52]), "+f"(d[53]), "+f"(d[54]), "+f"(d[55]), "+f"(d[56]), "+f"(d[57]), "+f"(d[58]), "+f"(d[59]), "+f"(d[60]), "+f"(d[61]), "+f"(d[62]), "+f"(d[63])
    : "r"(a0), "r"(a1), "r"(a2), "r"(a3), "l"(db), "r"(sc));
}
__device__ __forceinline__ void wgmma_rs_n128_tb(float (&d)[64], uint32_t a0, uint32_t a1, uint32_t a2, uint32_t a3, uint64_t db, uint32_t sc) {
  asm volatile("{\n.reg .pred p;\nsetp.ne.b32 p, %69, 0;\n"
    "wgmma.mma_async.sync.aligned.m64n128k16.f32.bf16.bf16 "
    "{%0, %1, %2, %3, %4, %5, %6, %7, %8, %9, %10, %11, %12, %13, %14, %15, %16, %17, %18, %19, %20, %21, %22, %23, %24, %25, %26, %27, %28, %29, %30, %31, %32, %33, %34, %35, %36, %37, %38, %39, %40, %41, %42, %43, %44, %45, %46, %47, %48, %49, %50, %51, %52, %53, %54, %55, %56, %57, %58, %59, %60, %61, %62, %63}, {%64, %65, %66, %67}, %68, p, 1, 1, 1;\n}\n"
    : "+f"(d[0]), "+f"(d[1]), "+f"(d[2]), "+f"(d[3]), "+f"(d[4]), "+f"(d[5]), "+f"(d[6]), "+f"(d[7]), "+f"(d[8]), "+f"(d[9]), "+f"(d[10]), "+f"(d[11]), "+f"(d[12]), "+f"(d[13]), "+f"(d[14]), "+f"(d[15]), "+f"(d[16]), "+f"(d[17]), "+f"(d[18]), "+f"(d[19]), "+f"(d[20]), "+f"(d[21]), "+f"(d[22]), "+f"(d[23]), "+f"(d[24]), "+f"(d[25]), "+f"(d[26]), "+f"(d[27]), "+f"(d[28]), "+f"(d[29]), "+f"(d[30]), "+f"(d[31]), "+f"(d[32]), "+f"(d[33]), "+f"(d[34]), "+f"(d[35]), "+f"(d[36]), "+f"(d[37]), "+f"(d[38]), "+f"(d[39]), "+f"(d[40]), "+f"(d[41]), "+f"(d[42]), "+f"(d[43]), "+f"(d[44]), "+f"(d[45]), "+f"(d[46]), "+f"(d[47]), "+f"(d[48]), "+f"(d[49]), "+f"(d[50]), "+f"(d[51]), "+f"(d[52]), "+f"(d[53]), "+f"(d[54]), "+f"(d[55]), "+f"(d[56]), "+f"(d[57]), "+f"(d[58]), "+f"(d[59]), "+f"(d[60]), "+f"(d[61]), "+f"(d[62]), "+f"(d[63])
    : "r"(a0), "r"(a1), "r"(a2), "r"(a3), "l"(db), "r"(sc));
}

#define TS(i) do {} while (0)
#define TR(j, i) do {} while (0)
#define TSS(i, c) do {} while (0)

__device__ __forceinline__ uint32_t wrap12(uint32_t p) { return p >= NSLOT ? p - NSLOT : p; }

#define ONCE(c) _Pragma("unroll 1") for (uint32_t once_ = 0; once_ <= (c).zero; once_++)
struct Cons {
  uint32_t sb;
  uint32_t g, pos;
  uint32_t rel;
  uint32_t nstg;
  uint32_t zero;
  int wg, lane;
  __device__ __forceinline__ void wait_full(uint32_t gg) const { mbar_wait(sb + SM_BAR + B_FULL + (gg & 7) * 8, (gg >> 3) & 1); }
  __device__ __forceinline__ void release(uint32_t gg) const { if (lane < 2) mbar_arrive_cluster(rel + (gg & 7) * 8); }
  __device__ __forceinline__ void stg_acquire() { mbar_wait(sb + SM_BAR + B_SEMPTY + wg * 8, (nstg & 1) ^ 1); nstg++; }
  __device__ __forceinline__ void stg_publish() const {
    fence_async_smem();
    __syncwarp();
    if (lane == 0) mbar_arrive(sb + SM_BAR + B_SFULL + wg * 8);
  }
};

__device__ __forceinline__ void frag_addr(uint32_t& rowoff, uint32_t& xr) {
  const uint32_t t = tid_x();
  rowoff = ((t >> 5) & 3) * 2048 + (t & 15) * 128;
  xr = (((t >> 4) & 1) ^ (t & 7)) << 4;
}
template <int NB, int NR>
__device__ __forceinline__ void stage_boxes(const uint32_t (&r)[NR], int r0, const Cons& c) {
  uint32_t rowoff, xr;
  frag_addr(rowoff, xr);
  const uint32_t stg = c.sb + SM_STG + c.wg * 16384 + rowoff;
#pragma unroll
  for (int b = 0; b < NB; b++)
#pragma unroll
    for (int kb = 0; kb < 4; kb++)
      stsm4(stg + b * 8192 + ((32 * kb) ^ xr), r[r0 + b * 16 + kb * 4], r[r0 + b * 16 + kb * 4 + 1], r[r0 + b * 16 + kb * 4 + 2], r[r0 + b * 16 + kb * 4 + 3]);
  c.stg_publish();
}

template <int N, bool FIRST>
__device__ __forceinline__ void gemm_step(float (&acc)[128], Cons& c) {
  const uint32_t p1 = wrap12(c.pos + 1), p2 = wrap12(c.pos + 2);
  const uint64_t da = mkdesc(c.sb + c.wg * 8192 + c.pos * SLOT, 16, 1024);
  const uint64_t b0 = mkdesc(c.sb + p1 * SLOT, 4096, 1024);
  const uint64_t b1 = mkdesc(c.sb + p2 * SLOT, 4096, 1024);
  c.wait_full(c.g);
  wg_fence();
  if (N == 256) {
    wgmma_ss_n256_tb(acc, da, b0, FIRST ? 0 : 1);
    wgmma_ss_n256_tb(acc, da + 2, b0 + 128, 1);
    wgmma_ss_n256_tb(acc, da + 4, b1, 1);
    wgmma_ss_n256_tb(acc, da + 6, b1 + 128, 1);
  } else {
    wgmma_ss_n192_tb(acc, da, b0, FIRST ? 0 : 1);
    wgmma_ss_n192_tb(acc, da + 2, b0 + 128, 1);
    wgmma_ss_n192_tb(acc, da + 4, b1, 1);
    wgmma_ss_n192_tb(acc, da + 6, b1 + 128, 1);
  }
  wg_commit();
  if (!FIRST) {
    wg_wait<1>();
    c.release(c.g - 1);
  }
  c.g++;
  c.pos = wrap12(p2 + 1);
}

template <int N>
__device__ __forceinline__ void gemm_loop(float (&acc)[128], Cons& c, int nk) {
  gemm_step<N, true>(acc, c);
#pragma unroll 1
  for (int k = 1; k < nk; k++) gemm_step<N, false>(acc, c);
  wg_wait<0>();
  c.release(c.g - 1);
  fence_regs(acc);
}
template <int N, int NB>
__device__ __forceinline__ void gemm_loop_flush(float (&acc)[128], Cons& c, const uint32_t (&pend)[NB * 16], bool flush) {
  gemm_step<N, true>(acc, c);
#pragma unroll 1
  for (int k = 1; k < 16; k++) {
    gemm_step<N, false>(acc, c);
    if (k == 3 && flush) {
      c.stg_acquire();
      stage_boxes<NB>(pend, 0, c);
    }
  }
  wg_wait<0>();
  c.release(c.g - 1);
  fence_regs(acc);
}
template <int NB>
__device__ __forceinline__ void h_epilogue(const float (&acc)[128], Cons& c, uint32_t (&pend)[NB * 16]) {
  uint32_t r[32];
#pragma unroll
  for (int i = 0; i < 32; i++) r[i] = pack_bf16_relu(acc[2 * i], acc[2 * i + 1]);
  c.stg_acquire();
  stage_boxes<2>(r, 0, c);
#pragma unroll
  for (int i = 0; i < NB * 16; i++) pend[i] = pack_bf16_relu(acc[64 + 2 * i], acc[65 + 2 * i]);
}

__device__ __forceinline__ uint32_t silu2(uint32_t f2) {
  const float a = bf_lo(f2), b = bf_hi(f2);
  return pack_bf16(a * rcp(1.0f + ex2(-1.4426950408889634f * a)), b * rcp(1.0f + ex2(-1.4426950408889634f * b)));
}

constexpr float SM_C = 0.08838834764831845f * 1.4426950408889634f;

__device__ __forceinline__ void row_max2(const float (&S)[64], float& n0, float& n1) {
  float x[4], y[4];
#pragma unroll
  for (int i = 0; i < 4; i++) { x[i] = fmaxf(S[4 * i], S[4 * i + 1]); y[i] = fmaxf(S[4 * i + 2], S[4 * i + 3]); }
#pragma unroll
  for (int i = 4; i < 16; i++) {
    x[i & 3] = fmaxf(x[i & 3], fmaxf(S[4 * i], S[4 * i + 1]));
    y[i & 3] = fmaxf(y[i & 3], fmaxf(S[4 * i + 2], S[4 * i + 3]));
  }
  n0 = fmaxf(fmaxf(x[0], x[1]), fmaxf(x[2], x[3]));
  n1 = fmaxf(fmaxf(y[0], y[1]), fmaxf(y[2], y[3]));
  n0 = fmaxf(n0, __shfl_xor_sync(~0u, n0, 1));
  n1 = fmaxf(n1, __shfl_xor_sync(~0u, n1, 1));
  n0 = fmaxf(n0, __shfl_xor_sync(~0u, n0, 2));
  n1 = fmaxf(n1, __shfl_xor_sync(~0u, n1, 2));
}
__device__ __forceinline__ void to_exponent(float (&S)[64], float cc0, float cc1) {
#pragma unroll
  for (int i = 0; i < 16; i++) {
    S[4 * i] = fmaf(S[4 * i], SM_C, cc0); S[4 * i + 1] = fmaf(S[4 * i + 1], SM_C, cc0);
    S[4 * i + 2] = fmaf(S[4 * i + 2], SM_C, cc1); S[4 * i + 3] = fmaf(S[4 * i + 3], SM_C, cc1);
  }
}
__device__ __forceinline__ void scale_o(float (&O)[64], float f0, float f1) {
#pragma unroll
  for (int i = 0; i < 16; i++) { O[4 * i] *= f0; O[4 * i + 1] *= f0; O[4 * i + 2] *= f1; O[4 * i + 3] *= f1; }
}
template <int G0>
__device__ __forceinline__ void exp_pack(const float (&S)[64], uint32_t (&p)[32], float (&a)[4]) {
#pragma unroll
  for (int i = G0; i < 16; i++) {
    const float e0 = ex2(S[4 * i]), e1 = ex2(S[4 * i + 1]), e2 = ex2(S[4 * i + 2]), e3 = ex2(S[4 * i + 3]);
    a[0] += e0; a[1] += e1; a[2] += e2; a[3] += e3;
    p[2 * i] = pack_bf16(e0, e1);
    p[2 * i + 1] = pack_bf16(e2, e3);
  }
}
#define EARLY 4
__device__ __forceinline__ void softmax_early(float (&S)[64], float cc0, float cc1, float (&a)[4], uint32_t (&pe)[2 * EARLY + 1], const Cons& c) {
  a[0] = a[1] = a[2] = a[3] = 0.f;
  ONCE(c) {
    to_exponent(S, cc0, cc1);
#pragma unroll
    for (int i = 0; i < EARLY; i++) {
      const float e0 = ex2(S[4 * i]), e1 = ex2(S[4 * i + 1]), e2 = ex2(S[4 * i + 2]), e3 = ex2(S[4 * i + 3]);
      a[0] += e0; a[1] += e1; a[2] += e2; a[3] += e3;
      pe[2 * i] = pack_bf16(e0, e1);
      pe[2 * i + 1] = pack_bf16(e2, e3);
    }
  }
}
__device__ __forceinline__ void softmax_late(float (&S)[64], uint32_t (&p)[32], float (&O)[64], float& cc0, float& cc1, float& l0, float& l1,
                                             float (&a)[4], const uint32_t (&pe)[2 * EARLY + 1], uint32_t zero) {
#pragma unroll
  for (int i = 0; i < 2 * EARLY; i++) p[i] = pe[i] ^ zero;
  exp_pack<EARLY>(S, p, a);
  if (__any_sync(~0u, !(fmaxf(a[0] + a[1], a[2] + a[3]) <= 65536.f))) {
    float d0, d1;
    row_max2(S, d0, d1);
    d0 = fmaxf(d0, 0.f); d1 = fmaxf(d1, 0.f);
#pragma unroll
    for (int i = 0; i < 16; i++) { S[4 * i] -= d0; S[4 * i + 1] -= d0; S[4 * i + 2] -= d1; S[4 * i + 3] -= d1; }
    cc0 -= d0; cc1 -= d1;
    const float f0 = ex2(-d0), f1 = ex2(-d1);
    scale_o(O, f0, f1);
    l0 *= f0; l1 *= f1;
    a[0] = a[1] = a[2] = a[3] = 0.f;
    exp_pack<0>(S, p, a);
  }
  l0 += a[0] + a[1];
  l1 += a[2] + a[3];
}

__device__ __forceinline__ void inv_rowsum(float l0, float l1, float& i0, float& i1) {
  l0 += __shfl_xor_sync(~0u, l0, 1); l1 += __shfl_xor_sync(~0u, l1, 1);
  l0 += __shfl_xor_sync(~0u, l0, 2); l1 += __shfl_xor_sync(~0u, l1, 2);
  i0 = rcp(l0); i1 = rcp(l1);
}
__device__ __forceinline__ void write_o(const float (&O)[64], const Cons& c) {
  uint32_t rowoff, xr;
  frag_addr(rowoff, xr);
  const uint32_t stg = c.sb + SM_STG + c.wg * 16384 + rowoff;
#pragma unroll
  for (int kb = 0; kb < 8; kb++)
    stsm4(stg + (kb >> 2) * 8192 + ((32 * (kb & 3)) ^ xr),
          pack_bf16(O[8 * kb], O[8 * kb + 1]), pack_bf16(O[8 * kb + 2], O[8 * kb + 3]),
          pack_bf16(O[8 * kb + 4], O[8 * kb + 5]), pack_bf16(O[8 * kb + 6], O[8 * kb + 7]));
  c.stg_publish();
}

__device__ __forceinline__ void issue_qk(float (&S)[64], const uint32_t (&q)[32], uint32_t s0, uint32_t s1, uint32_t zero) {
  const uint64_t d0 = mkdesc(s0, 16, 1024), d1 = mkdesc(s1, 16, 1024);
#pragma unroll
  for (int kk = 0; kk < 8; kk++)
    wgmma_rs_n128(S, q[4 * kk], q[4 * kk + 1], q[4 * kk + 2], q[4 * kk + 3], (kk < 4 ? d0 : d1) + (kk & 3) * 2, kk > 0 ? 1u : zero);
}
__device__ __forceinline__ void issue_pv(float (&O)[64], const uint32_t (&p)[32], uint32_t s0, uint32_t s1, uint32_t accum) {
  const uint64_t d0 = mkdesc(s0, 8192, 1024), d1 = mkdesc(s1, 8192, 1024);
#pragma unroll
  for (int kk = 0; kk < 8; kk++)
    wgmma_rs_n128_tb(O, p[4 * kk], p[4 * kk + 1], p[4 * kk + 2], p[4 * kk + 3], (kk < 4 ? d0 : d1) + (kk & 3) * 128, kk > 0 ? 1u : accum);
}

#define TURN_SYNC()   bar_sync(1 + c.wg, 256)
#define TURN_PASS()   bar_arrive(2 - c.wg, 256)

__device__ __forceinline__ void attn_tile(const float (&acc)[128], Cons& c, int t) {
  uint32_t q[32], p[32];
  float S[64], O[64];
  const uint32_t stash = c.sb + SM_STG + c.wg * 16384 + ((threadIdx.x >> 5) & 3) * 2048 + c.lane * 16;
#pragma unroll
  for (int i = 0; i < 32; i++) q[i] = pack_bf16(acc[2 * i], acc[2 * i + 1]);
  c.stg_acquire();
#pragma unroll
  for (int i = 0; i < 8; i++)
    sts128(stash + (i >> 2) * 8192 + (i & 3) * 512, pack_bf16(acc[64 + 8 * i], acc[65 + 8 * i]), pack_bf16(acc[66 + 8 * i], acc[67 + 8 * i]),
           pack_bf16(acc[68 + 8 * i], acc[69 + 8 * i]), pack_bf16(acc[70 + 8 * i], acc[71 + 8 * i]));
  fence_regs(q);
  TR(0, 0);
  TURN_SYNC();
  TR(0, 1);
  c.wait_full(c.g);
  wg_fence();
  issue_qk(O, q, c.sb + c.pos * SLOT, c.sb + wrap12(c.pos + 1) * SLOT, 0);
  wg_commit();
  c.wait_full(c.g + 1);
  wg_fence();
  issue_qk(S, q, c.sb + wrap12(c.pos + 2) * SLOT, c.sb + wrap12(c.pos + 3) * SLOT, 0);
  wg_commit();
  TURN_PASS();
  TR(0, 2);
  wg_wait<1>();
  TR(0, 3);
  fence_regs(O);
  c.release(c.g);
  float cc0, cc1, l0, l1, f0 = 0.f, f1 = 0.f;
  float a[4] = {0.f, 0.f, 0.f, 0.f};
  uint32_t pe[2 * EARLY + 1];
  row_max2(O, cc0, cc1);
  cc0 *= -SM_C; cc1 *= -SM_C;
  ONCE(c) { to_exponent(O, cc0, cc1); }
  wg_wait<0>();
  fence_regs(S);
  fence_regs(q);
  c.release(c.g + 1);
  exp_pack<0>(O, p, a);
  l0 = a[0] + a[1];
  l1 = a[2] + a[3];
  c.pos = wrap12(c.pos + 4);
  TR(1, 0);
  TURN_SYNC();
  TR(1, 1);
  c.wait_full(c.g + 2);
  wg_fence();
  issue_pv(O, p, c.sb + c.pos * SLOT, c.sb + wrap12(c.pos + 1) * SLOT, 0);
  wg_commit();
  TURN_PASS();
  TR(1, 2);
  softmax_early(S, cc0, cc1, a, pe, c);
  TR(1, 4);
  wg_wait<0>();
  TR(1, 5);
  fence_regs(O);
  fence_regs(p);
  c.release(c.g + 2);
  c.g += 3;
  c.pos = wrap12(c.pos + 2);
  softmax_late(S, p, O, cc0, cc1, l0, l1, a, pe, c.zero);
#pragma unroll 1
  for (int j = 1; j < 7 + (int)c.zero; j++) {
    const uint32_t k0 = c.pos, k1 = wrap12(k0 + 1), v0 = wrap12(k0 + 2), v1 = wrap12(k0 + 3);
    TR(j + 1, 0);
    TURN_SYNC();
    TR(j + 1, 1);
    c.wait_full(c.g);
    wg_fence();
    issue_qk(S, q, c.sb + k0 * SLOT, c.sb + k1 * SLOT, 0);
    wg_commit();
    if (j == 4) {
      scale_o(O, f0, f1);
      write_o(O, c);
    }
    c.wait_full(c.g + 1);
    wg_fence();
    issue_pv(O, p, c.sb + v0 * SLOT, c.sb + v1 * SLOT, j != 4);
    wg_commit();
    TURN_PASS();
    TR(j + 1, 2);
    wg_wait<1>();
    TR(j + 1, 3);
    fence_regs(S);
    fence_regs(q);
    c.release(c.g);
    if (j == 3) {
      row_max2(S, cc0, cc1);
      cc0 *= -SM_C; cc1 *= -SM_C;
      inv_rowsum(l0, l1, f0, f1);
      l0 = 0.f; l1 = 0.f;
    }
    softmax_early(S, cc0, cc1, a, pe, c);
    if (j == 2) {
#pragma unroll
      for (int i = 0; i < 8; i++) lds128(stash + (i >> 2) * 8192 + (i & 3) * 512, q[4 * i], q[4 * i + 1], q[4 * i + 2], q[4 * i + 3]);
      __syncwarp();
    }
    TR(j + 1, 4);
    wg_wait<0>();
    TR(j + 1, 5);
    fence_regs(O);
    fence_regs(p);
    c.release(c.g + 1);
    c.g += 2;
    c.pos = wrap12(v1 + 1);
    softmax_late(S, p, O, cc0, cc1, l0, l1, a, pe, c.zero);
  }
  TR(8, 0);
  TURN_SYNC();
  TR(8, 1);
  c.wait_full(c.g);
  wg_fence();
  issue_pv(O, p, c.sb + c.pos * SLOT, c.sb + wrap12(c.pos + 1) * SLOT, 1);
  wg_commit();
  TURN_PASS();
  TR(8, 2);
  c.stg_acquire();
  float a0, a1;
  inv_rowsum(l0, l1, a0, a1);
  wg_wait<0>();
  TR(8, 5);
  fence_regs(O);
  fence_regs(p);
  c.release(c.g);
  c.g++;
  c.pos = wrap12(c.pos + 2);
  scale_o(O, a0, a1);
  write_o(O, c);
  TR(9, 0);
}

struct Prod {
  uint32_t sb, g, pos, head, tail_g, tail_pos, hist;
  __device__ __forceinline__ uint32_t full() const { return sb + SM_BAR + B_FULL + (g & 7) * 8; }
  __device__ __forceinline__ uint32_t slot(uint32_t i) const { return sb + wrap12(pos + i) * SLOT; }
  __device__ __forceinline__ void acquire(uint32_t size) {
#pragma unroll 1
    while (head + size - tail_pos > NSLOT) {
      mbar_wait(sb + SM_BAR + B_EMPTY + (tail_g & 7) * 8, (tail_g >> 3) & 1);
      tail_pos += 2 + ((hist >> (tail_g & 31)) & 1);
      tail_g++;
    }
    hist = (hist & ~(1u << (g & 31))) | ((size - 2) << (g & 31));
  }
  __device__ __forceinline__ void advance(uint32_t size) { g++; head += size; pos = wrap12(pos + size); }
};

__device__ __forceinline__ void wait_flag(const unsigned* p, unsigned target) {
  while ((int)(ld_acquire(p) - target) < 0) {}
  fence_async_all();
}

__device__ __forceinline__ void init_barriers(uint32_t sb, int warp) {
  const uint32_t cnt = warp < 4 ? 1 : warp < 8 ? 16 : warp == 8 ? 4 : warp == 9 ? 1 : 11;
  if (warp < 11) mbar_init(sb + SM_BAR + warp * 16, cnt);
  if (warp < 10) mbar_init(sb + SM_BAR + warp * 16 + 8, cnt);
  asm volatile("fence.mbarrier_init.release.cluster;" ::: "memory");
}

#define TSP(i) do {} while (0)

__global__ void __cluster_dims__(2, 1, 1) __launch_bounds__(384, 1) fused_kernel(const __grid_constant__ Params P) {
  extern __shared__ uint8_t smem_raw[];
  const uint32_t sb = (smem_u32(smem_raw) + 1023u) & ~1023u;
  const int warp = __shfl_sync(~0u, (int)(threadIdx.x >> 5), 0);
  const int lane = threadIdx.x & 31;
  const int rank = blockIdx.x & 1;
  const int cl = blockIdx.x >> 1;
  const int j = cl >> 3;
  const int rb = (cl & 7) * 2 + rank;
  const bool is_s = j < 4, spare = j == 8;
  const int row0 = rb * 128;
  Flags* fl = P.flags;

  if (warp >= 8) {
    unsigned ep0 = 0;
    if (warp == 8) asm volatile("ld.volatile.global.u32 %0, [%1];" : "=r"(ep0) : "l"(&fl->epoch[blockIdx.x]));
    if (lane == 0) {
      if (warp == 8) prefetch_map(spare ? &P.w1b4 : &P.w1b3);
      if (warp == 9) prefetch_map(&P.act_ld);
      init_barriers(sb, warp);
    }
    __syncwarp();
    cluster_arrive();
    if (warp == 10 && lane == 0) {
      prefetch_map(&P.act_st); prefetch_map(&P.wq); prefetch_map(&P.k_ld); prefetch_map(&P.v_ld);
      prefetch_map(is_s ? &P.wo : &P.w2); prefetch_map(&P.x_ld); prefetch_map(&P.out_st);
    }
    __syncwarp();
    cluster_wait();
    asm volatile("setmaxnreg.dec.sync.aligned.u32 24;");
    if (warp == 8) {
      TSP(17);
#define ep1 (ep0 + 1)
      Prod p{sb, 0, 0, 0, 0, 0, 0};
#define LDA(dst, m, bar, c0, c1) tma_ld2(dst, m, bar, c0, c1)
#define LDW1(dst, m, bar, c0, c1, c2) tma_ld3_mc(dst, m, bar, c0, c1, c2)
#define LDW(dst, m, bar, c0, c1, c2) tma_ld3_mc(dst, m, bar, c0, c1, c2)
      {
        const CUtensorMap* mb = spare ? &P.w1b4 : &P.w1b3;
        const uint32_t bytes = spare ? 49152 : 40960;
        const int nt = spare ? 8 : 2;
#pragma unroll 1
        for (int t = 0; t < nt; t++) {
          const int r = spare ? ((cl & 1) * 4 + (t >> 1)) * 2 + rank : rb;
          const int nb0 = spare ? (H_SPARE0 >> 6) + (t & 1) * 4 : j * 6 + t * 3;
          int k = 0;
          if (t == 0) {
#pragma unroll 1
            for (; k < 4; k++) {
              p.acquire(3);
              if (lane == 0) { mbar_expect_tx(p.full(), bytes); LDW1(p.slot(1 + rank), mb, p.full(), 0, k * 64 + rank * 32, nb0); }
              p.advance(3);
            }
            TSP(14);
            asm volatile("" : "+r"(ep0));
            wait_flag(&fl->ln[r][0], ep1 * 64);
            TSP(15);
            if (lane == 0)
              for (int i = 0; i < 4; i++) tma_ld2(sb + i * 3 * SLOT, &P.act_ld, sb + SM_BAR + B_FULL + i * 8, C_XN + i * 64, r * 128);
          } else if (spare && !(t & 1)) {
            wait_flag(&fl->ln[r][0], ep1 * 64);
          }
#pragma unroll 1
          for (; k < 16; k++) {
            p.acquire(3);
            if (lane == 0) {
              mbar_expect_tx(p.full(), bytes);
              LDW1(p.slot(1 + rank), mb, p.full(), 0, k * 64 + rank * 32, nb0);
              tma_ld2(p.slot(0), &P.act_ld, p.full(), C_XN + k * 64, r * 128);
            }
            p.advance(3);
          }
        }
      }
      if (!spare) {
        const int kvrow = (j >> 1) * SK + KV0;
#pragma unroll 1
        for (int t = 0; t < 2; t++) {
          const int nb0 = (4 * j + 2 * t) * 2;
#pragma unroll 1
          for (int k = 0; k < 16; k++) {
            p.acquire(3);
            if (lane == 0) {
              mbar_expect_tx(p.full(), 49152);
              LDW1(p.slot(1 + rank), &P.wq, p.full(), 0, k * 64 + rank * 32, nb0);
              tma_ld2(p.slot(0), &P.act_ld, p.full(), C_XN + k * 64, row0);
            }
            p.advance(3);
          }
#pragma unroll 1
          for (int i = 0; i < 16; i++) {
            const bool is_k = i == 0 || (i < 15 && (i & 1));
            const int ch = (is_k ? ((i + 1) >> 1) : (i == 15 ? 7 : (i >> 1) - 1)) & 3;
            p.acquire(2);
            if (lane == 0) {
              mbar_expect_tx(p.full(), 32768);
              if (is_k) tma_ld2_mc(p.slot(rank), &P.k_ld, p.full(), rank * 64, kvrow + ch * 128);
              else      tma_ld3_mc(p.slot(rank), &P.v_ld, p.full(), 0, kvrow + ch * 128 + rank * 64, 0);
            }
            p.advance(2);
            if (t == 1 && i == 4 && !is_s) wait_flag(&fl->h[rb][0], ep1 * 64);
          }
        }
        const int jn = j & 3;
        if (is_s) {
          unsigned ready = 0;
#pragma unroll 1
          for (int i = 0; i < 64; i++) {
            const int hi = i >> 1;
            const int head = 4 * ((hi & 15) >> 1) + (hi & 1) + ((hi >> 4) << 1);
            const int kc = head * 128 + (i & 1) * 64;
            p.acquire(3);
            if (lane == 0) { mbar_expect_tx(p.full(), 49152); LDW(p.slot(1 + rank), &P.wo, p.full(), 0, kc + rank * 32, jn * 4); }
            if (!((ready >> head) & 1)) {
              do { ready = __ballot_sync(~0u, (int)(ld_acquire(&fl->o[rb][lane]) - ep1 * 2) >= 0); } while (!((ready >> head) & 1));
              __syncwarp();
              fence_async_all();
            }
            if (lane == 0) LDA(p.slot(0), &P.act_ld, p.full(), C_O + kc, row0);
            if (i == 52) {
              if (lane == 0) { prefetch_map(&P.x_ld); prefetch_map(&P.out_st); }
              if (lane < 4) tma_pf2(&P.x_ld, jn * 256 + lane * 64, row0);
            }
            p.advance(3);
          }
#pragma unroll 1
          for (int i = 0; i < 4; i++) {
            if (i == 2) { TSP(20); wait_flag(&fl->g[rb][jn], ep1 * 4); TSP(21); }
            p.acquire(2);
            if (lane == 0) {
              mbar_expect_tx(p.full(), 32768);
              const CUtensorMap* m = i < 2 ? &P.x_ld : &P.act_ld;
              const int c0 = (i < 2 ? 0 : C_G) + jn * 256 + (i & 1) * 128;
              tma_ld2(p.slot(0), m, p.full(), c0, row0);
              tma_ld2(p.slot(1), m, p.full(), c0 + 64, row0);
            }
            p.advance(2);
          }
        } else {
#pragma unroll 1
          for (int k = 0; k < 56; k++) {
            p.acquire(3);
            if (lane == 0) { mbar_expect_tx(p.full(), 49152); LDW(p.slot(1 + rank), &P.w2, p.full(), 0, k * 64 + rank * 32, jn * 4); }
            if (k == H_SPARE0 / 64) wait_flag(&fl->h[rb][16], ep1 * 8);
            if (lane == 0) LDA(p.slot(0), &P.act_ld, p.full(), C_H + k * 64, row0);
            p.advance(3);
          }
        }
      }
      if (lane == 0) { *(volatile unsigned*)&fl->epoch[blockIdx.x] = ep1; mbar_arrive(sb + SM_BAR + B_DONE); }
    } else if (warp < 11) {
      const int wg = warp - 9;
      if (lane == 0) {
        const uint32_t stg = sb + SM_STG + wg * 16384;
        const int nev = spare ? 16 : is_s ? 8 : 10;
#pragma unroll 1
        for (int n = 0; n < nev; n++) {
          int col, row = row0, nbox = 2;
          unsigned* flag;
          if (spare) {
            const int r = ((cl & 1) * 4 + (n >> 2)) * 2 + rank;
            row = r * 128;
            col = C_H + H_SPARE0 + (n & 3) * 128;
            flag = &fl->h[r][16];
          } else if (n < 4) {
            col = C_H + j * H_REG + (n >> 1) * 192 + (n & 1) * 128;
            nbox = 2 - (n & 1);
            flag = &fl->h[rb][0];
          } else if (n < 8) {
            col = C_O + (4 * j + n - 4) * 128;
            flag = &fl->o[rb][4 * j + n - 4];
          } else {
            col = C_G + (j & 3) * 256 + (n - 8) * 128;
            flag = &fl->g[rb][j & 3];
          }
          mbar_wait(sb + SM_BAR + B_SFULL + wg * 8, n & 1);
          if (n == 9 && wg == 0) TSP(20);
          tma_st2(&P.act_st, stg, col, row + wg * 64);
          if (nbox == 2) tma_st2(&P.act_st, stg + 8192, col + 64, row + wg * 64);
          bulk_commit();
          bulk_wait_read0();
          mbar_arrive(sb + SM_BAR + B_SEMPTY + wg * 8);
          if (n == 9 && wg == 0) TSP(21);
          bulk_wait0();
          if (n == 9 && wg == 0) TSP(22);
          red_release(flag, 1);
          if (n == 9 && wg == 0) TSP(23);
        }
        mbar_arrive(sb + SM_BAR + B_DONE);
      }
    } else {
      if (lane == 0) {
        const unsigned long long t0 = gtime();
        while (!mbar_try(sb + SM_BAR + B_DONE, 0)) {
          if (gtime() - t0 > 2000000000ull) __trap();
        }
      }
    }
    __syncwarp();
    cluster_arrive();
    cluster_wait();
  } else {
    const int wg = warp >> 2;
    TS(0);
    if (!spare) {
      const int r = row0 + j * 16 + warp * 2;
      uint32_t v[2][16];
#pragma unroll
      for (int a = 0; a < 2; a++)
#pragma unroll
        for (int i = 0; i < 4; i++)
          *(uint4*)&v[a][4 * i] = __ldg((const uint4*)(P.x + (size_t)(r + a) * DM + i * 256 + lane * 8));
      if (lane == 0) init_barriers(sb, warp);
      __syncwarp();
      cluster_arrive();
      float s[2], q[2];
#pragma unroll
      for (int a = 0; a < 2; a++) {
        float t0 = 0.f, t1 = 0.f;
#pragma unroll
        for (int i = 0; i < 16; i++) { t0 += bf_lo(v[a][i]); t1 += bf_hi(v[a][i]); }
        s[a] = t0 + t1;
      }
#pragma unroll
      for (int o = 16; o; o >>= 1) { s[0] += __shfl_xor_sync(~0u, s[0], o); s[1] += __shfl_xor_sync(~0u, s[1], o); }
#pragma unroll
      for (int a = 0; a < 2; a++) {
        s[a] *= 1.0f / DM;
        float t0 = 0.f, t1 = 0.f;
#pragma unroll
        for (int i = 0; i < 16; i++) {
          const float d0 = bf_lo(v[a][i]) - s[a], d1 = bf_hi(v[a][i]) - s[a];
          t0 = fmaf(d0, d0, t0); t1 = fmaf(d1, d1, t1);
        }
        q[a] = t0 + t1;
      }
#pragma unroll
      for (int o = 16; o; o >>= 1) { q[0] += __shfl_xor_sync(~0u, q[0], o); q[1] += __shfl_xor_sync(~0u, q[1], o); }
#pragma unroll
      for (int a = 0; a < 2; a++) {
        const uint32_t mb2 = pack_bf16(s[a], s[a]);
        float sd;
        asm("sqrt.approx.ftz.f32 %0, %1;" : "=f"(sd) : "f"(bf_round(bf_round(q[a] * (1.0f / DM)) + 1e-5f)));
        const float inv = rcp(bf_round(sd));
#pragma unroll
        for (int i = 0; i < 16; i++) {
          const __nv_bfloat162 d = __hsub2_rn(*(const __nv_bfloat162*)&v[a][i], *(const __nv_bfloat162*)&mb2);
          const uint32_t du = *(const uint32_t*)&d;
          v[a][i] = pack_bf16(bf_lo(du) * inv, bf_hi(du) * inv);
        }
#pragma unroll
        for (int i = 0; i < 4; i++)
          sts128(sb + SM_STG + warp * 4096 + a * 2048 + i * 512 + lane * 16, v[a][4 * i], v[a][4 * i + 1], v[a][4 * i + 2], v[a][4 * i + 3]);
      }
      TS(11);
      fence_async_smem();
      __syncwarp();
      if (lane == 0) {
#pragma unroll
        for (int a = 0; a < 2; a++)
          asm volatile("cp.async.bulk.global.shared::cta.bulk_group [%0], [%1], 2048;"
                       ::"l"(P.act + (size_t)(r + a) * ACT_W + C_XN), "r"(sb + SM_STG + warp * 4096 + a * 2048) : "memory");
        bulk_commit();
        bulk_wait0();
        TS(12);
        red_release(&fl->ln[rb][0], 1);
      }
      __syncwarp();
      TS(13);
    } else {
      if (lane == 0) init_barriers(sb, warp);
      __syncwarp();
      cluster_arrive();
    }
    cluster_wait();
    asm volatile("setmaxnreg.inc.sync.aligned.u32 240;");
    Cons c;
    c.zero = blockIdx.y; c.sb = sb; c.g = 0; c.pos = 0; c.nstg = 0; c.wg = wg; c.lane = lane;
    c.rel = mapa(sb + SM_BAR + B_EMPTY, lane & 1);
    float acc[128];
    TS(1);
    if (spare) {
      uint32_t pend[32];
#pragma unroll
      for (int i = 0; i < 32; i++) pend[i] = 0;
#pragma unroll 1
      for (int t = 0; t < 8; t++) {
        gemm_loop_flush<256, 2>(acc, c, pend, t > 0);
        h_epilogue<2>(acc, c, pend);
      }
      c.stg_acquire();
      stage_boxes<2>(pend, 0, c);
      TS(6);
    } else {
      if (wg == 1) bar_arrive(1, 256);
      {
        uint32_t pend[16];
#pragma unroll
        for (int i = 0; i < 16; i++) pend[i] = 0;
#pragma unroll 1
        for (int t = 0; t < 2; t++) {
          gemm_loop_flush<192, 1>(acc, c, pend, t > 0);
          h_epilogue<1>(acc, c, pend);
          TS(2 + t);
        }
        gemm_loop_flush<256, 1>(acc, c, pend, true);
      }
#pragma unroll 1
      for (int t = 0; t < 2; t++) {
        TS(8 + t);
        attn_tile(acc, c, t);
        TS(4 + t);
        gemm_loop<256>(acc, c, t == 0 ? 16 : is_s ? 64 : 56);
      }
      TS(6);
      uint32_t rowoff, xr;
      frag_addr(rowoff, xr);
      if (is_s) {
        const uint32_t x0 = c.pos;
#pragma unroll
        for (int b = 0; b < 4; b++) {
          if ((b & 1) == 0) { c.wait_full(c.g + (b >> 1)); c.wait_full(c.g + 2 + (b >> 1)); }
          if (b == 0) TS(22);
          if (b == 2) TS(23);
          const uint32_t xs = sb + wrap12(x0 + b) * SLOT + wg * 8192;
          const uint32_t sx = xs + rowoff, sg = sb + wrap12(wrap12(x0 + 4) + b) * SLOT + wg * 8192 + rowoff;
          uint32_t xv[16], gv[16];
#pragma unroll
          for (int kb = 0; kb < 4; kb++) {
            ldsm4(sx + ((32 * kb) ^ xr), xv[4 * kb], xv[4 * kb + 1], xv[4 * kb + 2], xv[4 * kb + 3]);
            ldsm4(sg + ((32 * kb) ^ xr), gv[4 * kb], gv[4 * kb + 1], gv[4 * kb + 2], gv[4 * kb + 3]);
          }
#pragma unroll
          for (int i = 0; i < 16; i++) {
            const uint32_t s2 = pack_bf16(acc[32 * b + 2 * i], acc[32 * b + 2 * i + 1]);
            const __nv_bfloat162 pr = __hmul2_rn(*(const __nv_bfloat162*)&s2, *(const __nv_bfloat162*)&gv[i]);
            const __nv_bfloat162 o = __hadd2_rn(*(const __nv_bfloat162*)&xv[i], pr);
            xv[i] = *(const uint32_t*)&o;
          }
#pragma unroll
          for (int kb = 0; kb < 4; kb++) stsm4(sx + ((32 * kb) ^ xr), xv[4 * kb], xv[4 * kb + 1], xv[4 * kb + 2], xv[4 * kb + 3]);
          fence_async_smem();
          __syncwarp();
          if (lane == 0) {
            tma_st2(&P.out_st, xs + (warp & 3) * 2048, (j & 3) * 256 + b * 64, row0 + warp * 16);
            bulk_commit();
          }
        }
        TS(24);
        if (lane == 0) bulk_wait_read0();
      } else {
        const uint32_t stg = sb + SM_STG + wg * 16384 + rowoff;
#pragma unroll
        for (int hh = 0; hh < 2; hh++) {
#pragma unroll
          for (int bx = 0; bx < 2; bx++) {
            uint32_t r[16];
            ONCE(c) {
#pragma unroll
              for (int i = 0; i < 16; i++) r[i] = silu2(pack_bf16(acc[64 * hh + 32 * bx + 2 * i], acc[64 * hh + 32 * bx + 2 * i + 1]) ^ once_);
            }
            if (bx == 0) c.stg_acquire();
#pragma unroll
            for (int kb = 0; kb < 4; kb++) stsm4(stg + bx * 8192 + ((32 * kb) ^ xr), r[4 * kb], r[4 * kb + 1], r[4 * kb + 2], r[4 * kb + 3]);
          }
          c.stg_publish();
          if (hh == 0) TS(22);
        }
      }
    }
    TS(7);
    __syncwarp();
    if (lane == 0) mbar_arrive(sb + SM_BAR + B_DONE);
    cluster_arrive();
    cluster_wait();
  }
}

typedef CUresult (*EncodeFn)(CUtensorMap*, CUtensorMapDataType, cuuint32_t, void*, const cuuint64_t*, const cuuint64_t*,
                             const cuuint32_t*, const cuuint32_t*, CUtensorMapInterleave, CUtensorMapSwizzle,
                             CUtensorMapL2promotion, CUtensorMapFloatOOBfill);

void map2d(EncodeFn enc, CUtensorMap* m, const void* base, uint64_t cols, uint64_t rows, uint32_t box_rows) {
  cuuint64_t dims[2] = {cols, rows};
  cuuint64_t strides[1] = {cols * 2};
  cuuint32_t box[2] = {64, box_rows};
  cuuint32_t es[2] = {1, 1};
  enc(m, CU_TENSOR_MAP_DATA_TYPE_BFLOAT16, 2, (void*)base, dims, strides, box, es, CU_TENSOR_MAP_INTERLEAVE_NONE,
      CU_TENSOR_MAP_SWIZZLE_128B, CU_TENSOR_MAP_L2_PROMOTION_L2_256B, CU_TENSOR_MAP_FLOAT_OOB_FILL_NONE);
}
void map3d(EncodeFn enc, CUtensorMap* m, const void* base, uint64_t cols, uint64_t rows, uint32_t box_rows, uint32_t box_blks) {
  cuuint64_t dims[3] = {64, rows, cols / 64};
  cuuint64_t strides[2] = {cols * 2, 128};
  cuuint32_t box[3] = {64, box_rows, box_blks};
  cuuint32_t es[3] = {1, 1, 1};
  enc(m, CU_TENSOR_MAP_DATA_TYPE_BFLOAT16, 3, (void*)base, dims, strides, box, es, CU_TENSOR_MAP_INTERLEAVE_NONE,
      CU_TENSOR_MAP_SWIZZLE_128B, CU_TENSOR_MAP_L2_PROMOTION_L2_256B, CU_TENSOR_MAP_FLOAT_OOB_FILL_NONE);
}

}

extern "C" void kernel_launch(void* const* d_in, const int* in_sizes, int n_in, void* d_out, int out_size) {
  (void)in_sizes; (void)n_in; (void)out_size;
  static EncodeFn enc = nullptr;
  static void* act = nullptr;
  static void* flags = nullptr;
  if (!enc) {
    void* fn = nullptr;
    cudaDriverEntryPointQueryResult qr;
    cudaGetDriverEntryPoint("cuTensorMapEncodeTiled", &fn, cudaEnableDefault, &qr);
    enc = (EncodeFn)fn;
    cudaGetSymbolAddress(&act, g_act);
    cudaGetSymbolAddress(&flags, g_flags);
    cudaFuncSetAttribute(fused_kernel, cudaFuncAttributeMaxDynamicSharedMemorySize, SMEM_BYTES);
  }
  Params P;
  map2d(enc, &P.act_ld, act, ACT_W, SEQ, 128);
  map2d(enc, &P.act_st, act, ACT_W, SEQ, 64);
  map2d(enc, &P.x_ld, d_in[0], DM, SEQ, 128);
  map2d(enc, &P.out_st, d_out, DM, SEQ, 16);
  map2d(enc, &P.k_ld, d_in[1], 128, 4 * SK, 128);
  map3d(enc, &P.v_ld, d_in[2], 128, 4 * SK, 64, 2);
  map3d(enc, &P.wq, d_in[3], NQ, DM, 32, 4);
  map3d(enc, &P.w1b4, d_in[6], DFF, DM, 32, 4);
  map3d(enc, &P.w1b3, d_in[6], DFF, DM, 32, 3);
  map3d(enc, &P.wo, d_in[4], DM, NQ, 32, 4);
  map3d(enc, &P.w2, d_in[7], DM, DFF, 32, 4);
  P.x = (const __nv_bfloat16*)d_in[0];
  P.act = (__nv_bfloat16*)act;
  P.flags = (Flags*)flags;
  fused_kernel<<<NCLUSTER * 2, 384, SMEM_BYTES>>>(P);
}
```

```cpp
#include <cuda_runtime.h>
#include <cuda_bf16.h>
#include <cuda.h>
#include <stdint.h>

namespace {

constexpr int SEQ    = 2048;
constexpr int DM     = 1024;
constexpr int NQ     = 4096;
constexpr int DFF    = 3584;
constexpr int SK     = 2048;
constexpr int WIN    = 512;
constexpr int KV0    = SK - WIN;
constexpr int C_XN = 0, C_O = 1024, C_H = 5120, ACT_W = 8704;

constexpr int H_REG = 384, H_SPARE0 = 8 * H_REG;
static_assert(H_SPARE0 + 512 == DFF, "H split");

constexpr int NSLOT = 12, SLOT = 16384, NBAR = 8;
constexpr int SM_STG = NSLOT * SLOT;
constexpr int SM_BAR = SM_STG + 2 * 16384;
constexpr int SMEM_BYTES = SM_BAR + 256 + 1024;
constexpr int B_FULL = 0, B_EMPTY = 64, B_SFULL = 128, B_SEMPTY = 144, B_DONE = 160, B_GRDY = 168;

constexpr int NCLUSTER = 66;

struct Flags {
  unsigned ln[16][32];
  unsigned h[16][32];
  unsigned o[16][32];
  unsigned g[16][32];
  unsigned epoch[160];
};
__device__ __nv_bfloat16 g_act[(size_t)SEQ * ACT_W];
__device__ uint4 g_gate[16 * 4 * 16 * 256];
__device__ Flags g_flags;

struct Params {
  CUtensorMap act_ld, act_st, x_ld, out_st, k_ld, v_ld, wq, w1b4, w1b3, wo, w2;
  const __nv_bfloat16* x;
  __nv_bfloat16* act;
  uint4* gate;
  Flags* flags;
};

__device__ __forceinline__ uint32_t smem_u32(const void* p) { return (uint32_t)__cvta_generic_to_shared(p); }
__device__ __forceinline__ void mbar_init(uint32_t bar, uint32_t cnt) {
  asm volatile("mbarrier.init.shared::cta.b64 [%0], %1;" ::"r"(bar), "r"(cnt) : "memory");
}
__device__ __forceinline__ bool mbar_try(uint32_t bar, uint32_t parity) {
  uint32_t ok;
  asm volatile("{\n.reg .pred p;\nmbarrier.try_wait.parity.shared::cta.b64 p, [%1], %2;\nselp.u32 %0, 1, 0, p;\n}\n"
               : "=r"(ok) : "r"(bar), "r"(parity) : "memory");
  return ok;
}
__device__ __forceinline__ void mbar_wait(uint32_t bar, uint32_t parity) {
  asm volatile("{\n.reg .pred p;\nWAIT_%=:\nmbarrier.try_wait.parity.shared::cta.b64 p, [%0], %1;\n@p bra DONE_%=;\nbra WAIT_%=;\nDONE_%=:\n}\n"
               ::"r"(bar), "r"(parity) : "memory");
}
__device__ __forceinline__ void mbar_arrive(uint32_t bar) {
  asm volatile("mbarrier.arrive.shared::cta.b64 _, [%0];" ::"r"(bar) : "memory");
}
__device__ __forceinline__ void mbar_arrive_cluster(uint32_t cluster_addr) {
  asm volatile("mbarrier.arrive.shared::cluster.b64 _, [%0];" ::"r"(cluster_addr) : "memory");
}
__device__ __forceinline__ void mbar_expect_tx(uint32_t bar, uint32_t bytes) {
  asm volatile("mbarrier.arrive.expect_tx.shared::cta.b64 _, [%0], %1;" ::"r"(bar), "r"(bytes) : "memory");
}
__device__ __forceinline__ uint32_t mapa(uint32_t addr, uint32_t rank) {
  uint32_t r;
  asm("mapa.shared::cluster.u32 %0, %1, %2;" : "=r"(r) : "r"(addr), "r"(rank));
  return r;
}
__device__ __forceinline__ void cluster_arrive() { asm volatile("barrier.cluster.arrive.relaxed.aligned;" ::: "memory"); }
__device__ __forceinline__ void cluster_wait() { asm volatile("barrier.cluster.wait.acquire.aligned;" ::: "memory"); }
__device__ __forceinline__ void bar_sync(int id, int n) { asm volatile("bar.sync %0, %1;" ::"r"(id), "r"(n) : "memory"); }
__device__ __forceinline__ void bar_arrive(int id, int n) { asm volatile("bar.arrive %0, %1;" ::"r"(id), "r"(n) : "memory"); }
__device__ __forceinline__ void fence_async_smem() { asm volatile("fence.proxy.async.shared::cta;" ::: "memory"); }
__device__ __forceinline__ void fence_async_all() { asm volatile("fence.proxy.async.global;" ::: "memory"); }

__device__ __forceinline__ void tma_ld2(uint32_t dst, const CUtensorMap* m, uint32_t bar, int c0, int c1) {
  asm volatile("cp.async.bulk.tensor.2d.shared::cluster.global.mbarrier::complete_tx::bytes [%0], [%1, {%3, %4}], [%2];"
               ::"r"(dst), "l"(m), "r"(bar), "r"(c0), "r"(c1) : "memory");
}
__device__ __forceinline__ void tma_ld2_mc(uint32_t dst, const CUtensorMap* m, uint32_t bar, int c0, int c1) {
  asm volatile("cp.async.bulk.tensor.2d.shared::cluster.global.mbarrier::complete_tx::bytes.multicast::cluster [%0], [%1, {%3, %4}], [%2], %5;"
               ::"r"(dst), "l"(m), "r"(bar), "r"(c0), "r"(c1), "h"((uint16_t)3) : "memory");
}
__device__ __forceinline__ void tma_ld3_mc(uint32_t dst, const CUtensorMap* m, uint32_t bar, int c0, int c1, int c2) {
  asm volatile("cp.async.bulk.tensor.3d.shared::cluster.global.mbarrier::complete_tx::bytes.multicast::cluster [%0], [%1, {%3, %4, %5}], [%2], %6;"
               ::"r"(dst), "l"(m), "r"(bar), "r"(c0), "r"(c1), "r"(c2), "h"((uint16_t)3) : "memory");
}
__device__ __forceinline__ void tma_ld3_mc_hint(uint32_t dst, const CUtensorMap* m, uint32_t bar, int c0, int c1, int c2, uint64_t pol) {
  asm volatile("cp.async.bulk.tensor.3d.shared::cluster.global.mbarrier::complete_tx::bytes.multicast::cluster.L2::cache_hint [%0], [%1, {%3, %4, %5}], [%2], %6, %7;"
               ::"r"(dst), "l"(m), "r"(bar), "r"(c0), "r"(c1), "r"(c2), "h"((uint16_t)3), "l"(pol) : "memory");
}
__device__ __forceinline__ void tma_ld2_hint(uint32_t dst, const CUtensorMap* m, uint32_t bar, int c0, int c1, uint64_t pol) {
  asm volatile("cp.async.bulk.tensor.2d.shared::cluster.global.mbarrier::complete_tx::bytes.L2::cache_hint [%0], [%1, {%3, %4}], [%2], %5;"
               ::"r"(dst), "l"(m), "r"(bar), "r"(c0), "r"(c1), "l"(pol) : "memory");
}
__device__ __forceinline__ void tma_st2_hint(const CUtensorMap* m, uint32_t src, int c0, int c1, uint64_t pol) {
  asm volatile("cp.async.bulk.tensor.2d.global.shared::cta.bulk_group.L2::cache_hint [%0, {%2, %3}], [%1], %4;"
               ::"l"(m), "r"(src), "r"(c0), "r"(c1), "l"(pol) : "memory");
}
#define POL_FIRST 0x12F0000000000000ull
__device__ __forceinline__ uint64_t policy_evict_first() {
  uint64_t p;
  asm volatile("createpolicy.fractional.L2::evict_first.b64 %0, 1.0;" : "=l"(p));
  return p;
}
__device__ __forceinline__ void tma_st2(const CUtensorMap* m, uint32_t src, int c0, int c1) {
  asm volatile("cp.async.bulk.tensor.2d.global.shared::cta.bulk_group [%0, {%2, %3}], [%1];"
               ::"l"(m), "r"(src), "r"(c0), "r"(c1) : "memory");
}
__device__ __forceinline__ void tma_pf2(const CUtensorMap* m, int c0, int c1) {
  asm volatile("cp.async.bulk.prefetch.tensor.2d.L2.global [%0, {%1, %2}];" ::"l"(m), "r"(c0), "r"(c1) : "memory");
}
__device__ __forceinline__ void bulk_commit() { asm volatile("cp.async.bulk.commit_group;" ::: "memory"); }
__device__ __forceinline__ void bulk_wait_read0() { asm volatile("cp.async.bulk.wait_group.read 0;" ::: "memory"); }
__device__ __forceinline__ void bulk_wait0() { asm volatile("cp.async.bulk.wait_group 0;" ::: "memory"); }
__device__ __forceinline__ void prefetch_map(const CUtensorMap* m) {
  asm volatile("prefetch.tensormap [%0];" ::"l"(m) : "memory");
}
__device__ __forceinline__ unsigned ld_acquire(const unsigned* p) {
  unsigned v;
  asm volatile("ld.acquire.gpu.global.u32 %0, [%1];" : "=r"(v) : "l"(p) : "memory");
  return v;
}
__device__ __forceinline__ void red_release(unsigned* p, unsigned v) {
  asm volatile("red.release.gpu.global.add.u32 [%0], %1;" ::"l"(p), "r"(v) : "memory");
}
__device__ __forceinline__ void wg_fence() { asm volatile("wgmma.fence.sync.aligned;" ::: "memory"); }
__device__ __forceinline__ void wg_commit() { asm volatile("wgmma.commit_group.sync.aligned;" ::: "memory"); }
template <int N> __device__ __forceinline__ void wg_wait() { asm volatile("wgmma.wait_group.sync.aligned %0;" ::"n"(N) : "memory"); }
template <int N> __device__ __forceinline__ void fence_regs(float (&d)[N]) {
#pragma unroll
  for (int i = 0; i < N; i++) asm volatile("" : "+f"(d[i])::"memory");
}
template <int N> __device__ __forceinline__ void fence_regs(uint32_t (&d)[N]) {
#pragma unroll
  for (int i = 0; i < N; i++) asm volatile("" : "+r"(d[i])::"memory");
}
__device__ __forceinline__ uint64_t mkdesc(uint32_t addr, uint32_t lbo, uint32_t sbo) {
  return (uint64_t)((addr & 0x3FFFF) >> 4) | ((uint64_t)(lbo >> 4) << 16) | ((uint64_t)(sbo >> 4) << 32) | (1ull << 62);
}
__device__ __forceinline__ uint32_t pack_bf16(float lo, float hi) {
  uint32_t r;
  asm("cvt.rn.bf16x2.f32 %0, %1, %2;" : "=r"(r) : "f"(hi), "f"(lo));
  return r;
}
__device__ __forceinline__ uint32_t pack_bf16_relu(float lo, float hi) {
  uint32_t r;
  asm("cvt.rn.relu.bf16x2.f32 %0, %1, %2;" : "=r"(r) : "f"(hi), "f"(lo));
  return r;
}
__device__ __forceinline__ float bf_lo(uint32_t v) { return __uint_as_float(v << 16); }
__device__ __forceinline__ float bf_hi(uint32_t v) { return __uint_as_float(v & 0xFFFF0000u); }
__device__ __forceinline__ float bf_round(float v) { return bf_lo(pack_bf16(v, v)); }
__device__ __forceinline__ float ex2(float x) {
  float r;
  asm("ex2.approx.ftz.f32 %0, %1;" : "=f"(r) : "f"(x));
  return r;
}
__device__ __forceinline__ float rcp(float x) {
  float r;
  asm("rcp.approx.ftz.f32 %0, %1;" : "=f"(r) : "f"(x));
  return r;
}
__device__ __forceinline__ uint32_t tid_x() {
  uint32_t t;
  asm volatile("mov.u32 %0, %%tid.x;" : "=r"(t));
  return t;
}
__device__ __forceinline__ void stsm4(uint32_t addr, uint32_t r0, uint32_t r1, uint32_t r2, uint32_t r3) {
  asm volatile("stmatrix.sync.aligned.m8n8.x4.shared.b16 [%0], {%1, %2, %3, %4};" ::"r"(addr), "r"(r0), "r"(r1), "r"(r2), "r"(r3) : "memory");
}
__device__ __forceinline__ void ldsm4(uint32_t addr, uint32_t& r0, uint32_t& r1, uint32_t& r2, uint32_t& r3) {
  asm volatile("ldmatrix.sync.aligned.m8n8.x4.shared.b16 {%0, %1, %2, %3}, [%4];" : "=r"(r0), "=r"(r1), "=r"(r2), "=r"(r3) : "r"(addr) : "memory");
}
__device__ __forceinline__ void sts128(uint32_t addr, uint32_t r0, uint32_t r1, uint32_t r2, uint32_t r3) {
  asm volatile("st.shared.v4.b32 [%0], {%1, %2, %3, %4};" ::"r"(addr), "r"(r0), "r"(r1), "r"(r2), "r"(r3) : "memory");
}
__device__ __forceinline__ void lds128(uint32_t addr, uint32_t& r0, uint32_t& r1, uint32_t& r2, uint32_t& r3) {
  asm volatile("ld.shared.v4.b32 {%0, %1, %2, %3}, [%4];" : "=r"(r0), "=r"(r1), "=r"(r2), "=r"(r3) : "r"(addr) : "memory");
}
__device__ __forceinline__ unsigned long long gtime() {
  unsigned long long t;
  asm volatile("mov.u64 %0, %globaltimer;" : "=l"(t));
  return t;
}

__device__ __forceinline__ void wgmma_ss_n256_tb(float (&d)[128], uint64_t da, uint64_t db, uint32_t sc) {
  asm volatile("{\n.reg .pred p;\nsetp.ne.b32 p, %130, 0;\n"
    "wgmma.mma_async.sync.aligned.m64n256k16.f32.bf16.bf16 "
    "{%0, %1, %2, %3, %4, %5, %6, %7, %8, %9, %10, %11, %12, %13, %14, %15, %16, %17, %18, %19, %20, %21, %22, %23, %24, %25, %26, %27, %28, %29, %30, %31, %32, %33, %34, %35, %36, %37, %38, %39, %40, %41, %42, %43, %44, %45, %46, %47, %48, %49, %50, %51, %52, %53, %54, %55, %56, %57, %58, %59, %60, %61, %62, %63, %64, %65, %66, %67, %68, %69, %70, %71, %72, %73, %74, %75, %76, %77, %78, %79, %80, %81, %82, %83, %84, %85, %86, %87, %88, %89, %90, %91, %92, %93, %94, %95, %96, %97, %98, %99, %100, %101, %102, %103, %104, %105, %106, %107, %108, %109, %110, %111, %112, %113, %114, %115, %116, %117, %118, %119, %120, %121, %122, %123, %124, %125, %126, %127}, %128, %129, p, 1, 1, 0, 1;\n}\n"
    : "+f"(d[0]), "+f"(d[1]), "+f"(d[2]), "+f"(d[3]), "+f"(d[4]), "+f"(d[5]), "+f"(d[6]), "+f"(d[7]), "+f"(d[8]), "+f"(d[9]), "+f"(d[10]), "+f"(d[11]), "+f"(d[12]), "+f"(d[13]), "+f"(d[14]), "+f"(d[15]), "+f"(d[16]), "+f"(d[17]), "+f"(d[18]), "+f"(d[19]), "+f"(d[20]), "+f"(d[21]), "+f"(d[22]), "+f"(d[23]), "+f"(d[24]), "+f"(d[25]), "+f"(d[26]), "+f"(d[27]), "+f"(d[28]), "+f"(d[29]), "+f"(d[30]), "+f"(d[31]), "+f"(d[32]), "+f"(d[33]), "+f"(d[34]), "+f"(d[35]), "+f"(d[36]), "+f"(d[37]), "+f"(d[38]), "+f"(d[39]), "+f"(d[40]), "+f"(d[41]), "+f"(d[42]), "+f"(d[43]), "+f"(d[44]), "+f"(d[45]), "+f"(d[46]), "+f"(d[47]), "+f"(d[48]), "+f"(d[49]), "+f"(d[50]), "+f"(d[51]), "+f"(d[52]), "+f"(d[53]), "+f"(d[54]), "+f"(d[55]), "+f"(d[56]), "+f"(d[57]), "+f"(d[58]), "+f"(d[59]), "+f"(d[60]), "+f"(d[61]), "+f"(d[62]), "+f"(d[63]), "+f"(d[64]), "+f"(d[65]), "+f"(d[66]), "+f"(d[67]), "+f"(d[68]), "+f"(d[69]), "+f"(d[70]), "+f"(d[71]), "+f"(d[72]), "+f"(d[73]), "+f"(d[74]), "+f"(d[75]), "+f"(d[76]), "+f"(d[77]), "+f"(d[78]), "+f"(d[79]), "+f"(d[80]), "+f"(d[81]), "+f"(d[82]), "+f"(d[83]), "+f"(d[84]), "+f"(d[85]), "+f"(d[86]), "+f"(d[87]), "+f"(d[88]), "+f"(d[89]), "+f"(d[90]), "+f"(d[91]), "+f"(d[92]), "+f"(d[93]), "+f"(d[94]), "+f"(d[95]), "+f"(d[96]), "+f"(d[97]), "+f"(d[98]), "+f"(d[99]), "+f"(d[100]), "+f"(d[101]), "+f"(d[102]), "+f"(d[103]), "+f"(d[104]), "+f"(d[105]), "+f"(d[106]), "+f"(d[107]), "+f"(d[108]), "+f"(d[109]), "+f"(d[110]), "+f"(d[111]), "+f"(d[112]), "+f"(d[113]), "+f"(d[114]), "+f"(d[115]), "+f"(d[116]), "+f"(d[117]), "+f"(d[118]), "+f"(d[119]), "+f"(d[120]), "+f"(d[121]), "+f"(d[122]), "+f"(d[123]), "+f"(d[124]), "+f"(d[125]), "+f"(d[126]), "+f"(d[127])
    : "l"(da), "l"(db), "r"(sc));
}
__device__ __forceinline__ void wgmma_ss_n192_tb(float (&d)[96], uint64_t da, uint64_t db, uint32_t sc) {
  asm volatile("{\n.reg .pred p;\nsetp.ne.b32 p, %98, 0;\n"
    "wgmma.mma_async.sync.aligned.m64n192k16.f32.bf16.bf16 "
    "{%0, %1, %2, %3, %4, %5, %6, %7, %8, %9, %10, %11, %12, %13, %14, %15, %16, %17, %18, %19, %20, %21, %22, %23, %24, %25, %26, %27, %28, %29, %30, %31, %32, %33, %34, %35, %36, %37, %38, %39, %40, %41, %42, %43, %44, %45, %46, %47, %48, %49, %50, %51, %52, %53, %54, %55, %56, %57, %58, %59, %60, %61, %62, %63, %64, %65, %66, %67, %68, %69, %70, %71, %72, %73, %74, %75, %76, %77, %78, %79, %80, %81, %82, %83, %84, %85, %86, %87, %88, %89, %90, %91, %92, %93, %94, %95}, %96, %97, p, 1, 1, 0, 1;\n}\n"
    : "+f"(d[0]), "+f"(d[1]), "+f"(d[2]), "+f"(d[3]), "+f"(d[4]), "+f"(d[5]), "+f"(d[6]), "+f"(d[7]), "+f"(d[8]), "+f"(d[9]), "+f"(d[10]), "+f"(d[11]), "+f"(d[12]), "+f"(d[13]), "+f"(d[14]), "+f"(d[15]), "+f"(d[16]), "+f"(d[17]), "+f"(d[18]), "+f"(d[19]), "+f"(d[20]), "+f"(d[21]), "+f"(d[22]), "+f"(d[23]), "+f"(d[24]), "+f"(d[25]), "+f"(d[26]), "+f"(d[27]), "+f"(d[28]), "+f"(d[29]), "+f"(d[30]), "+f"(d[31]), "+f"(d[32]), "+f"(d[33]), "+f"(d[34]), "+f"(d[35]), "+f"(d[36]), "+f"(d[37]), "+f"(d[38]), "+f"(d[39]), "+f"(d[40]), "+f"(d[41]), "+f"(d[42]), "+f"(d[43]), "+f"(d[44]), "+f"(d[45]), "+f"(d[46]), "+f"(d[47]), "+f"(d[48]), "+f"(d[49]), "+f"(d[50]), "+f"(d[51]), "+f"(d[52]), "+f"(d[53]), "+f"(d[54]), "+f"(d[55]), "+f"(d[56]), "+f"(d[57]), "+f"(d[58]), "+f"(d[59]), "+f"(d[60]), "+f"(d[61]), "+f"(d[62]), "+f"(d[63]), "+f"(d[64]), "+f"(d[65]), "+f"(d[66]), "+f"(d[67]), "+f"(d[68]), "+f"(d[69]), "+f"(d[70]), "+f"(d[71]), "+f"(d[72]), "+f"(d[73]), "+f"(d[74]), "+f"(d[75]), "+f"(d[76]), "+f"(d[77]), "+f"(d[78]), "+f"(d[79]), "+f"(d[80]), "+f"(d[81]), "+f"(d[82]), "+f"(d[83]), "+f"(d[84]), "+f"(d[85]), "+f"(d[86]), "+f"(d[87]), "+f"(d[88]), "+f"(d[89]), "+f"(d[90]), "+f"(d[91]), "+f"(d[92]), "+f"(d[93]), "+f"(d[94]), "+f"(d[95])
    : "l"(da), "l"(db), "r"(sc));
}
__device__ __forceinline__ void wgmma_rs_n128(float (&d)[64], uint32_t a0, uint32_t a1, uint32_t a2, uint32_t a3, uint64_t db, uint32_t sc) {
  asm volatile("{\n.reg .pred p;\nsetp.ne.b32 p, %69, 0;\n"
    "wgmma.mma_async.sync.aligned.m64n128k16.f32.bf16.bf16 "
    "{%0, %1, %2, %3, %4, %5, %6, %7, %8, %9, %10, %11, %12, %13, %14, %15, %16, %17, %18, %19, %20, %21, %22, %23, %24, %25, %26, %27, %28, %29, %30, %31, %32, %33, %34, %35, %36, %37, %38, %39, %40, %41, %42, %43, %44, %45, %46, %47, %48, %49, %50, %51, %52, %53, %54, %55, %56, %57, %58, %59, %60, %61, %62, %63}, {%64, %65, %66, %67}, %68, p, 1, 1, 0;\n}\n"
    : "+f"(d[0]), "+f"(d[1]), "+f"(d[2]), "+f"(d[3]), "+f"(d[4]), "+f"(d[5]), "+f"(d[6]), "+f"(d[7]), "+f"(d[8]), "+f"(d[9]), "+f"(d[10]), "+f"(d[11]), "+f"(d[12]), "+f"(d[13]), "+f"(d[14]), "+f"(d[15]), "+f"(d[16]), "+f"(d[17]), "+f"(d[18]), "+f"(d[19]), "+f"(d[20]), "+f"(d[21]), "+f"(d[22]), "+f"(d[23]), "+f"(d[24]), "+f"(d[25]), "+f"(d[26]), "+f"(d[27]), "+f"(d[28]), "+f"(d[29]), "+f"(d[30]), "+f"(d[31]), "+f"(d[32]), "+f"(d[33]), "+f"(d[34]), "+f"(d[35]), "+f"(d[36]), "+f"(d[37]), "+f"(d[38]), "+f"(d[39]), "+f"(d[40]), "+f"(d[41]), "+f"(d[42]), "+f"(d[43]), "+f"(d[44]), "+f"(d[45]), "+f"(d[46]), "+f"(d[47]), "+f"(d[48]), "+f"(d[49]), "+f"(d[50]), "+f"(d[51]), "+f"(d[52]), "+f"(d[53]), "+f"(d[54]), "+f"(d[55]), "+f"(d[56]), "+f"(d[57]), "+f"(d[58]), "+f"(d[59]), "+f"(d[60]), "+f"(d[61]), "+f"(d[62]), "+f"(d[63])
    : "r"(a0), "r"(a1), "r"(a2), "r"(a3), "l"(db), "r"(sc));
}
__device__ __forceinline__ void wgmma_rs_n128_tb(float (&d)[64], uint32_t a0, uint32_t a1, uint32_t a2, uint32_t a3, uint64_t db, uint32_t sc) {
  asm volatile("{\n.reg .pred p;\nsetp.ne.b32 p, %69, 0;\n"
    "wgmma.mma_async.sync.aligned.m64n128k16.f32.bf16.bf16 "
    "{%0, %1, %2, %3, %4, %5, %6, %7, %8, %9, %10, %11, %12, %13, %14, %15, %16, %17, %18, %19, %20, %21, %22, %23, %24, %25, %26, %27, %28, %29, %30, %31, %32, %33, %34, %35, %36, %37, %38, %39, %40, %41, %42, %43, %44, %45, %46, %47, %48, %49, %50, %51, %52, %53, %54, %55, %56, %57, %58, %59, %60, %61, %62, %63}, {%64, %65, %66, %67}, %68, p, 1, 1, 1;\n}\n"
    : "+f"(d[0]), "+f"(d[1]), "+f"(d[2]), "+f"(d[3]), "+f"(d[4]), "+f"(d[5]), "+f"(d[6]), "+f"(d[7]), "+f"(d[8]), "+f"(d[9]), "+f"(d[10]), "+f"(d[11]), "+f"(d[12]), "+f"(d[13]), "+f"(d[14]), "+f"(d[15]), "+f"(d[16]), "+f"(d[17]), "+f"(d[18]), "+f"(d[19]), "+f"(d[20]), "+f"(d[21]), "+f"(d[22]), "+f"(d[23]), "+f"(d[24]), "+f"(d[25]), "+f"(d[26]), "+f"(d[27]), "+f"(d[28]), "+f"(d[29]), "+f"(d[30]), "+f"(d[31]), "+f"(d[32]), "+f"(d[33]), "+f"(d[34]), "+f"(d[35]), "+f"(d[36]), "+f"(d[37]), "+f"(d[38]), "+f"(d[39]), "+f"(d[40]), "+f"(d[41]), "+f"(d[42]), "+f"(d[43]), "+f"(d[44]), "+f"(d[45]), "+f"(d[46]), "+f"(d[47]), "+f"(d[48]), "+f"(d[49]), "+f"(d[50]), "+f"(d[51]), "+f"(d[52]), "+f"(d[53]), "+f"(d[54]), "+f"(d[55]), "+f"(d[56]), "+f"(d[57]), "+f"(d[58]), "+f"(d[59]), "+f"(d[60]), "+f"(d[61]), "+f"(d[62]), "+f"(d[63])
    : "r"(a0), "r"(a1), "r"(a2), "r"(a3), "l"(db), "r"(sc));
}

#define TS(i) do {} while (0)
#define TR(j, i) do {} while (0)
#define TSS(i, c) do {} while (0)

__device__ __forceinline__ uint32_t wrap12(uint32_t p) { return p >= NSLOT ? p - NSLOT : p; }

#define ONCE(c) _Pragma("unroll 1") for (uint32_t once_ = 0; once_ <= (c).zero; once_++)
struct Cons {
  uint32_t sb;
  uint32_t g, pos;
  uint32_t rel;
  uint32_t nstg;
  uint32_t zero;
  int wg, lane;
  __device__ __forceinline__ void wait_full(uint32_t gg) const { mbar_wait(sb + SM_BAR + B_FULL + (gg & 7) * 8, (gg >> 3) & 1); }
  __device__ __forceinline__ void release(uint32_t gg) const { if (lane < 2) mbar_arrive_cluster(rel + (gg & 7) * 8); }
  __device__ __forceinline__ void stg_acquire() { mbar_wait(sb + SM_BAR + B_SEMPTY + wg * 8, (nstg & 1) ^ 1); nstg++; }
  __device__ __forceinline__ void stg_publish() const {
    fence_async_smem();
    __syncwarp();
    if (lane == 0) mbar_arrive(sb + SM_BAR + B_SFULL + wg * 8);
  }
};

__device__ __forceinline__ void frag_addr(uint32_t& rowoff, uint32_t& xr) {
  const uint32_t t = tid_x();
  rowoff = ((t >> 5) & 3) * 2048 + (t & 15) * 128;
  xr = (((t >> 4) & 1) ^ (t & 7)) << 4;
}
template <int NB, int NR>
__device__ __forceinline__ void stage_boxes(const uint32_t (&r)[NR], int r0, const Cons& c) {
  uint32_t rowoff, xr;
  frag_addr(rowoff, xr);
  const uint32_t stg = c.sb + SM_STG + c.wg * 16384 + rowoff;
#pragma unroll
  for (int b = 0; b < NB; b++)
#pragma unroll
    for (int kb = 0; kb < 4; kb++)
      stsm4(stg + b * 8192 + ((32 * kb) ^ xr), r[r0 + b * 16 + kb * 4], r[r0 + b * 16 + kb * 4 + 1], r[r0 + b * 16 + kb * 4 + 2], r[r0 + b * 16 + kb * 4 + 3]);
  c.stg_publish();
}

template <bool FIRST>
__device__ __forceinline__ void gemm_step(float (&acc)[128], Cons& c) {
  const uint32_t p1 = wrap12(c.pos + 1), p2 = wrap12(c.pos + 2);
  const uint64_t da = mkdesc(c.sb + c.wg * 8192 + c.pos * SLOT, 16, 1024);
  const uint64_t b0 = mkdesc(c.sb + p1 * SLOT, 4096, 1024);
  const uint64_t b1 = mkdesc(c.sb + p2 * SLOT, 4096, 1024);
  c.wait_full(c.g);
  wg_fence();
  wgmma_ss_n256_tb(acc, da, b0, FIRST ? 0 : 1);
  wgmma_ss_n256_tb(acc, da + 2, b0 + 128, 1);
  wgmma_ss_n256_tb(acc, da + 4, b1, 1);
  wgmma_ss_n256_tb(acc, da + 6, b1 + 128, 1);
  wg_commit();
  if (!FIRST) {
    wg_wait<1>();
    c.release(c.g - 1);
  }
  c.g++;
  c.pos = wrap12(p2 + 1);
}

__device__ __forceinline__ void gemm_body(float (&acc)[128], Cons& c, int nk) {
  gemm_step<true>(acc, c);
#pragma unroll 1
  for (int k = 1; k < nk; k++) gemm_step<false>(acc, c);
}
__device__ __forceinline__ void gemm_drain(float (&acc)[128], Cons& c) {
  wg_wait<0>();
  c.release(c.g - 1);
  fence_regs(acc);
}
template <int NE>
__device__ __forceinline__ void gemm_loop_flush(float (&acc)[128], Cons& c, const uint32_t (&pend)[NE * 32], bool flush) {
  gemm_step<true>(acc, c);
#pragma unroll 1
  for (int k = 1; k < 16; k++) {
    gemm_step<false>(acc, c);
    if (k == 3 && flush) {
      c.stg_acquire();
      stage_boxes<2>(pend, 0, c);
    }
    if (NE == 2 && k == 7) {
      c.stg_acquire();
      stage_boxes<2>(pend, 32 * (NE - 1), c);
    }
  }
  wg_wait<0>();
  c.release(c.g - 1);
  fence_regs(acc);
}
template <bool FIRST>
__device__ __forceinline__ void h_step(float (&h0)[96], float (&h1)[96], Cons& c) {
  const uint64_t da = mkdesc(c.sb + c.wg * 8192 + c.pos * SLOT, 16, 1024);
  const uint64_t db = mkdesc(c.sb + (c.pos + 1) * SLOT, 8192, 1024);
  c.wait_full(c.g);
  wg_fence();
#pragma unroll
  for (int kk = 0; kk < 4; kk++) {
    wgmma_ss_n192_tb(h0, da + 2 * kk, db + 128 * kk, (FIRST && kk == 0) ? 0 : 1);
    wgmma_ss_n192_tb(h1, da + 2 * kk, db + 128 * kk + 1536, (FIRST && kk == 0) ? 0 : 1);
  }
  wg_commit();
  if (!FIRST) {
    wg_wait<1>();
    c.release(c.g - 1);
  }
  c.g++;
  c.pos = wrap12(c.pos + 4);
}

__device__ __forceinline__ uint32_t silu2(uint32_t f2) {
  const float a = bf_lo(f2), b = bf_hi(f2);
  return pack_bf16(a * rcp(1.0f + ex2(-1.4426950408889634f * a)), b * rcp(1.0f + ex2(-1.4426950408889634f * b)));
}

constexpr float SM_C = 0.08838834764831845f * 1.4426950408889634f;

__device__ __forceinline__ void row_max2(const float (&S)[64], float& n0, float& n1) {
  float x[4], y[4];
#pragma unroll
  for (int i = 0; i < 4; i++) { x[i] = fmaxf(S[4 * i], S[4 * i + 1]); y[i] = fmaxf(S[4 * i + 2], S[4 * i + 3]); }
#pragma unroll
  for (int i = 4; i < 16; i++) {
    x[i & 3] = fmaxf(x[i & 3], fmaxf(S[4 * i], S[4 * i + 1]));
    y[i & 3] = fmaxf(y[i & 3], fmaxf(S[4 * i + 2], S[4 * i + 3]));
  }
  n0 = fmaxf(fmaxf(x[0], x[1]), fmaxf(x[2], x[3]));
  n1 = fmaxf(fmaxf(y[0], y[1]), fmaxf(y[2], y[3]));
  n0 = fmaxf(n0, __shfl_xor_sync(~0u, n0, 1));
  n1 = fmaxf(n1, __shfl_xor_sync(~0u, n1, 1));
  n0 = fmaxf(n0, __shfl_xor_sync(~0u, n0, 2));
  n1 = fmaxf(n1, __shfl_xor_sync(~0u, n1, 2));
}
__device__ __forceinline__ void scale_o(float (&O)[64], float f0, float f1) {
#pragma unroll
  for (int i = 0; i < 16; i++) { O[4 * i] *= f0; O[4 * i + 1] *= f0; O[4 * i + 2] *= f1; O[4 * i + 3] *= f1; }
}
template <int R>
__device__ __forceinline__ void row_ex2(float (&S)[64]) {
#pragma unroll
  for (int i = 0; i < 16; i++) { S[4 * i + 2 * R] = ex2(S[4 * i + 2 * R]); S[4 * i + 2 * R + 1] = ex2(S[4 * i + 2 * R + 1]); }
}
template <int R>
__device__ __forceinline__ void row_pack(const float (&S)[64], uint32_t (&p)[32]) {
#pragma unroll
  for (int i = 0; i < 16; i++) p[2 * i + R] = pack_bf16(S[4 * i + 2 * R], S[4 * i + 2 * R + 1]);
}
__device__ __forceinline__ void add_offset(float (&S)[64], float cc0, float cc1) {
#pragma unroll
  for (int i = 0; i < 16; i++) { S[4 * i] += cc0; S[4 * i + 1] += cc0; S[4 * i + 2] += cc1; S[4 * i + 3] += cc1; }
}
__device__ __forceinline__ void exp_begin(float (&S)[64], float cc0, float cc1, bool off, const Cons& c) {
  if (__builtin_expect(off, 0)) add_offset(S, cc0, cc1);
  ONCE(c) { row_ex2<0>(S); }
}
__device__ __forceinline__ void exp_end(float (&S)[64], uint32_t (&p)[32], float& s0, float& s1, const Cons& c) {
  s0 = 0.f;
  ONCE(c) {
    row_ex2<1>(S);
#pragma unroll
    for (int i = 0; i < 16; i++) { s0 += S[4 * i]; s0 += S[4 * i + 1]; }
    row_pack<0>(S, p);
  }
  float a[4] = {S[2], S[3], S[6], S[7]};
#pragma unroll
  for (int i = 2; i < 16; i++) { a[2 * (i & 1)] += S[4 * i + 2]; a[2 * (i & 1) + 1] += S[4 * i + 3]; }
  row_pack<1>(S, p);
  s1 = (a[0] + a[1]) + (a[2] + a[3]);
}
__device__ __forceinline__ void recompute_scores(float (&S)[64], const uint32_t (&q)[32], uint32_t k0, uint32_t k1) {
  const uint32_t l = tid_x() & 31;
  float4 t[16];
#pragma unroll 1
  for (int i = 0; i < 16; i++) {
    float d0 = 0.f, d1 = 0.f, d2 = 0.f, d3 = 0.f;
#pragma unroll
    for (int h = 0; h < 4; h++) {
      uint32_t b0, b1, b2, b3;
      ldsm4((h < 2 ? k0 : k1) + (8 * i + (l & 7)) * 128 + (((4 * (h & 1) + (l >> 3)) ^ (l & 7)) << 4), b0, b1, b2, b3);
      asm volatile("mma.sync.aligned.m16n8k16.row.col.f32.bf16.bf16.f32 {%0, %1, %2, %3}, {%4, %5, %6, %7}, {%8, %9}, {%0, %1, %2, %3};"
                   : "+f"(d0), "+f"(d1), "+f"(d2), "+f"(d3) : "r"(q[8 * h]), "r"(q[8 * h + 1]), "r"(q[8 * h + 2]), "r"(q[8 * h + 3]), "r"(b0), "r"(b1));
      asm volatile("mma.sync.aligned.m16n8k16.row.col.f32.bf16.bf16.f32 {%0, %1, %2, %3}, {%4, %5, %6, %7}, {%8, %9}, {%0, %1, %2, %3};"
                   : "+f"(d0), "+f"(d1), "+f"(d2), "+f"(d3) : "r"(q[8 * h + 4]), "r"(q[8 * h + 5]), "r"(q[8 * h + 6]), "r"(q[8 * h + 7]), "r"(b2), "r"(b3));
    }
    t[i] = make_float4(d0, d1, d2, d3);
  }
#pragma unroll
  for (int i = 0; i < 16; i++) { S[4 * i] = t[i].x; S[4 * i + 1] = t[i].y; S[4 * i + 2] = t[i].z; S[4 * i + 3] = t[i].w; }
}
template <bool HAS_O, bool REL_V>
__device__ __forceinline__ void softmax_chunk(float (&S)[64], uint32_t (&p)[32], float (&O)[64], uint32_t (&q)[32], float& cc0, float& cc1,
                                              bool& off, float& l0, float& l1, bool first, uint32_t k0, uint32_t k1, uint32_t vg, const Cons& c) {
  float s0, s1;
  exp_begin(S, cc0, cc1, off, c);
  wg_wait<0>();
  fence_regs(O);
  fence_regs(p);
  fence_regs(q);
  if (REL_V) c.release(vg);
#pragma unroll 1
  for (uint32_t pass = c.zero;; pass++) {
    exp_end(S, p, s0, s1, c);
    const float lo = first ? 8.67361738e-19f : 0.f;
    if (__builtin_expect(pass != 0 || !__any_sync(~0u, !(fmaxf(s0, s1) <= 65536.f && fminf(s0, s1) >= lo)), 1)) break;
    recompute_scores(S, q, k0, k1);
    float n0, n1;
    row_max2(S, n0, n1);
    n0 = first ? -n0 : fminf(cc0, -n0);
    n1 = first ? -n1 : fminf(cc1, -n1);
    if (HAS_O && !first) {
      const float f0 = ex2(n0 - cc0), f1 = ex2(n1 - cc1);
      scale_o(O, f0, f1);
      l0 *= f0; l1 *= f1;
    }
    cc0 = n0; cc1 = n1;
    off = true;
    add_offset(S, cc0, cc1);
    row_ex2<0>(S);
  }
  l0 += s0;
  l1 += s1;
}

__device__ __forceinline__ void inv_rowsum(float l0, float l1, float& i0, float& i1) {
  l0 += __shfl_xor_sync(~0u, l0, 1); l1 += __shfl_xor_sync(~0u, l1, 1);
  l0 += __shfl_xor_sync(~0u, l0, 2); l1 += __shfl_xor_sync(~0u, l1, 2);
  i0 = rcp(l0); i1 = rcp(l1);
}
__device__ __forceinline__ void write_o(const float (&O)[64], const Cons& c) {
  uint32_t rowoff, xr;
  frag_addr(rowoff, xr);
  const uint32_t stg = c.sb + SM_STG + c.wg * 16384 + rowoff;
#pragma unroll
  for (int kb = 0; kb < 8; kb++)
    stsm4(stg + (kb >> 2) * 8192 + ((32 * (kb & 3)) ^ xr),
          pack_bf16(O[8 * kb], O[8 * kb + 1]), pack_bf16(O[8 * kb + 2], O[8 * kb + 3]),
          pack_bf16(O[8 * kb + 4], O[8 * kb + 5]), pack_bf16(O[8 * kb + 6], O[8 * kb + 7]));
  c.stg_publish();
}

__device__ __forceinline__ void issue_qk(float (&S)[64], const uint32_t (&q)[32], uint32_t s0, uint32_t s1, uint32_t zero) {
  const uint64_t d0 = mkdesc(s0, 16, 1024), d1 = mkdesc(s1, 16, 1024);
#pragma unroll
  for (int kk = 0; kk < 8; kk++)
    wgmma_rs_n128(S, q[4 * kk], q[4 * kk + 1], q[4 * kk + 2], q[4 * kk + 3], (kk < 4 ? d0 : d1) + (kk & 3) * 2, kk > 0 ? 1u : zero);
}
__device__ __forceinline__ void issue_pv(float (&O)[64], const uint32_t (&p)[32], uint32_t s0, uint32_t s1, uint32_t accum) {
  const uint64_t d0 = mkdesc(s0, 8192, 1024), d1 = mkdesc(s1, 8192, 1024);
#pragma unroll
  for (int kk = 0; kk < 8; kk++)
    wgmma_rs_n128_tb(O, p[4 * kk], p[4 * kk + 1], p[4 * kk + 2], p[4 * kk + 3], (kk < 4 ? d0 : d1) + (kk & 3) * 128, kk > 0 ? 1u : accum);
}

#define TURN_SYNC()   bar_sync(1 + c.wg, 256)
#define TURN_PASS()   bar_arrive(2 - c.wg, 256)

__device__ __forceinline__ void attn_tile(const float (&acc)[128], Cons& c, int t) {
  uint32_t q[32], p[32];
  float S[64], O[64];
  auto stash_addr = [&]() { const uint32_t t_ = tid_x(); return c.sb + SM_STG + c.wg * 16384 + ((t_ >> 5) & 3) * 2048 + (t_ & 31) * 16; };
  uint32_t stash = stash_addr();
#pragma unroll
  for (int i = 0; i < 32; i++) q[i] = pack_bf16(acc[2 * i] * SM_C, acc[2 * i + 1] * SM_C);
  c.stg_acquire();
#pragma unroll
  for (int i = 0; i < 8; i++)
    sts128(stash + (i >> 2) * 8192 + (i & 3) * 512, pack_bf16(acc[64 + 8 * i] * SM_C, acc[65 + 8 * i] * SM_C), pack_bf16(acc[66 + 8 * i] * SM_C, acc[67 + 8 * i] * SM_C),
           pack_bf16(acc[68 + 8 * i] * SM_C, acc[69 + 8 * i] * SM_C), pack_bf16(acc[70 + 8 * i] * SM_C, acc[71 + 8 * i] * SM_C));
  fence_regs(q);
  TR(0, 0);
  TURN_SYNC();
  TR(0, 1);
  c.wait_full(c.g);
  wg_fence();
  issue_qk(O, q, c.sb + c.pos * SLOT, c.sb + wrap12(c.pos + 1) * SLOT, 0);
  wg_commit();
  c.wait_full(c.g + 1);
  wg_fence();
  issue_qk(S, q, c.sb + wrap12(c.pos + 2) * SLOT, c.sb + wrap12(c.pos + 3) * SLOT, 0);
  wg_commit();
  TURN_PASS();
  TR(0, 2);
  wg_wait<1>();
  TR(0, 3);
  fence_regs(O);
  float cc0 = 0.f, cc1 = 0.f, l0 = 0.f, l1 = 0.f, f0 = 0.f, f1 = 0.f;
  bool off = false;
#pragma unroll
  for (int i = 0; i < 32; i++) p[i] = 0;
  softmax_chunk<false, false>(O, p, S, q, cc0, cc1, off, l0, l1, true, c.sb + c.pos * SLOT, c.sb + wrap12(c.pos + 1) * SLOT, 0, c);
  c.release(c.g);
  TR(1, 0);
  TURN_SYNC();
  TR(1, 1);
  c.wait_full(c.g + 2);
  wg_fence();
  issue_pv(O, p, c.sb + wrap12(c.pos + 4) * SLOT, c.sb + wrap12(c.pos + 5) * SLOT, 0);
  wg_commit();
  TURN_PASS();
  TR(1, 2);
  softmax_chunk<true, true>(S, p, O, q, cc0, cc1, off, l0, l1, false, c.sb + wrap12(c.pos + 2) * SLOT, c.sb + wrap12(c.pos + 3) * SLOT, c.g + 2, c);
  c.release(c.g + 1);
  c.g += 3;
  c.pos = wrap12(c.pos + 6);
#pragma unroll 1
  for (int n = 2; n < 8 + (int)c.zero; n++) {
    const uint32_t k0 = c.pos, k1 = wrap12(k0 + 1), v0 = wrap12(k0 + 2), v1 = wrap12(k0 + 3);
    TR(n, 0);
    TURN_SYNC();
    TR(n, 1);
    c.wait_full(c.g);
    wg_fence();
    issue_qk(S, q, c.sb + k0 * SLOT, c.sb + k1 * SLOT, 0);
    wg_commit();
    if (n == 5) {
      scale_o(O, f0, f1);
      write_o(O, c);
    }
    c.wait_full(c.g + 1);
    wg_fence();
    issue_pv(O, p, c.sb + v0 * SLOT, c.sb + v1 * SLOT, n != 5);
    wg_commit();
    TURN_PASS();
    TR(n, 2);
    wg_wait<1>();
    TR(n, 3);
    fence_regs(S);
    if (n == 4) {
      inv_rowsum(l0, l1, f0, f1);
      l0 = 0.f; l1 = 0.f; cc0 = 0.f; cc1 = 0.f;
      off = false;
    }
    softmax_chunk<true, true>(S, p, O, q, cc0, cc1, off, l0, l1, n == 4, c.sb + k0 * SLOT, c.sb + k1 * SLOT, c.g + 1, c);
    c.release(c.g);
    c.g += 2;
    c.pos = wrap12(v1 + 1);
    if (n == 3) {
      const uint32_t stash = stash_addr();
#pragma unroll
      for (int i = 0; i < 8; i++) lds128(stash + (i >> 2) * 8192 + (i & 3) * 512, q[4 * i], q[4 * i + 1], q[4 * i + 2], q[4 * i + 3]);
      __syncwarp();
    }
  }
  TR(8, 0);
  TURN_SYNC();
  TR(8, 1);
  c.wait_full(c.g);
  wg_fence();
  issue_pv(O, p, c.sb + c.pos * SLOT, c.sb + wrap12(c.pos + 1) * SLOT, 1);
  wg_commit();
  TURN_PASS();
  TR(8, 2);
  c.stg_acquire();
  float a0, a1;
  inv_rowsum(l0, l1, a0, a1);
  wg_wait<0>();
  TR(8, 5);
  fence_regs(O);
  fence_regs(p);
  c.release(c.g);
  c.g++;
  c.pos = wrap12(c.pos + 2);
  scale_o(O, a0, a1);
  write_o(O, c);
  TR(9, 0);
}

struct Prod {
  uint32_t sb, g, pos, head, tail_g, tail_pos, hist;
  __device__ __forceinline__ uint32_t full() const { return sb + SM_BAR + B_FULL + (g & 7) * 8; }
  __device__ __forceinline__ uint32_t slot(uint32_t i) const { return sb + wrap12(pos + i) * SLOT; }
  __device__ __forceinline__ void acquire(uint32_t size) {
#pragma unroll 1
    while (head + size - tail_pos > NSLOT) {
      mbar_wait(sb + SM_BAR + B_EMPTY + (tail_g & 7) * 8, (tail_g >> 3) & 1);
      tail_pos += 2 + ((hist >> (2 * (tail_g & 15))) & 3);
      tail_g++;
    }
    hist = (hist & ~(3u << (2 * (g & 15)))) | ((size - 2) << (2 * (g & 15)));
  }
  __device__ __forceinline__ void advance(uint32_t size) { g++; head += size; pos = wrap12(pos + size); }
};

__device__ __forceinline__ void wait_flag(const unsigned* p, unsigned target) {
  while ((int)(ld_acquire(p) - target) < 0) {}
  fence_async_all();
}

__device__ __forceinline__ void init_barriers(uint32_t sb, int warp) {
  constexpr uint32_t NREL = 16;
  const uint32_t cnt = warp < 4 ? 1 : warp < 8 ? NREL : warp == 8 ? 4 : warp == 9 ? 1 : 11;
  if (warp < 11) {
    mbar_init(sb + SM_BAR + warp * 16, cnt);
    mbar_init(sb + SM_BAR + warp * 16 + 8, warp == 10 ? 1 : cnt);
  }
  asm volatile("fence.mbarrier_init.release.cluster;" ::: "memory");
}

#define TSP(i) do {} while (0)

__global__ void __cluster_dims__(2, 1, 1) __launch_bounds__(384, 1) fused_kernel(const __grid_constant__ Params P) {
  extern __shared__ uint8_t smem_raw[];
  const uint32_t sb = (smem_u32(smem_raw) + 1023u) & ~1023u;
  const int warp = __shfl_sync(~0u, (int)(threadIdx.x >> 5), 0);
  const int lane = threadIdx.x & 31;
  const int rank = blockIdx.x & 1;
  const int cl = blockIdx.x >> 1;
  const int j = cl >> 3;
  const int rb = (cl & 7) * 2 + rank;
  const bool is_s = j < 4, spare = j == 8;
  const int row0 = rb * 128;
  Flags* fl = P.flags;

  if (warp >= 8) {
    unsigned ep0 = 0;
    if (warp == 8 || warp == 11) asm volatile("ld.volatile.global.u32 %0, [%1];" : "=r"(ep0) : "l"(&fl->epoch[blockIdx.x]));
    if (lane == 0) {
      if (warp == 8) prefetch_map(spare ? &P.w1b4 : &P.w1b3);
      if (warp == 9) prefetch_map(&P.act_ld);
      init_barriers(sb, warp);
    }
    __syncwarp();
    cluster_arrive();
    if (warp == 10 && lane == 0) {
      prefetch_map(&P.act_st); prefetch_map(&P.wq); prefetch_map(&P.k_ld); prefetch_map(&P.v_ld);
      prefetch_map(is_s ? &P.wo : &P.w2); prefetch_map(&P.x_ld); prefetch_map(&P.out_st);
    }
    __syncwarp();
    cluster_wait();
    asm volatile("setmaxnreg.dec.sync.aligned.u32 24;");
    if (warp == 8) {
      TSP(17);
#define ep1 (ep0 + 1)
      Prod p{sb, 0, 0, 0, 0, 0, 0};
#define LDA(dst, m, bar, c0, c1) tma_ld2(dst, m, bar, c0, c1)
#define LDW1(dst, m, bar, c0, c1, c2) tma_ld3_mc(dst, m, bar, c0, c1, c2)
#define LDW(dst, m, bar, c0, c1, c2) tma_ld3_mc(dst, m, bar, c0, c1, c2)
      if (spare) {
#pragma unroll 1
        for (int t = 0; t < 8; t++) {
          const int r = ((cl & 1) * 4 + (t >> 1)) * 2 + rank;
          if (!(t & 1)) wait_flag(&fl->ln[r][0], ep1 * 64);
#pragma unroll 1
          for (int k = 0; k < 16; k++) {
            p.acquire(3);
            if (lane == 0) {
              mbar_expect_tx(p.full(), 49152);
              LDW1(p.slot(1 + rank), &P.w1b4, p.full(), 0, k * 64 + rank * 32, (H_SPARE0 >> 6) + (t & 1) * 4);
              tma_ld2(p.slot(0), &P.act_ld, p.full(), C_XN + k * 64, r * 128);
            }
            p.advance(3);
          }
        }
      } else {
#pragma unroll 1
        for (int k = 0; k < 16; k++) {
          p.acquire(4);
          if (lane == 0) {
            mbar_expect_tx(p.full(), 65536);
            LDW1(p.slot(1) + rank * 24576, &P.w1b3, p.full(), 0, k * 64, j * 6 + rank * 3);
            if (k >= 3) tma_ld2(p.slot(0), &P.act_ld, p.full(), C_XN + k * 64, row0);
          }
          p.advance(4);
          if (k == 2) {
            TSP(14);
            asm volatile("" : "+r"(ep0));
            wait_flag(&fl->ln[rb][0], ep1 * 64);
            TSP(15);
            if (lane == 0)
              for (int i = 0; i < 3; i++) tma_ld2(sb + i * 4 * SLOT, &P.act_ld, sb + SM_BAR + B_FULL + i * 8, C_XN + i * 64, row0);
          }
        }
      }
      if (!spare) {
        const int kvrow = (j >> 1) * SK + KV0;
#pragma unroll 1
        for (int t = 0; t < 2; t++) {
          const int nb0 = (4 * j + 2 * t) * 2;
#pragma unroll 1
          for (int k = 0; k < 16; k++) {
            p.acquire(3);
            if (lane == 0) {
              mbar_expect_tx(p.full(), 49152);
              LDW1(p.slot(1 + rank), &P.wq, p.full(), 0, k * 64 + rank * 32, nb0);
              tma_ld2(p.slot(0), &P.act_ld, p.full(), C_XN + k * 64, row0);
            }
            p.advance(3);
          }
#pragma unroll 1
          for (int i = 0; i < 16; i++) {
            const bool is_k = i == 0 || (i < 15 && (i & 1));
            const int ch = (is_k ? ((i + 1) >> 1) : (i == 15 ? 7 : (i >> 1) - 1)) & 3;
            p.acquire(2);
            if (lane == 0) {
              mbar_expect_tx(p.full(), 32768);
              if (is_k) tma_ld2_mc(p.slot(rank), &P.k_ld, p.full(), rank * 64, kvrow + ch * 128);
              else      tma_ld3_mc(p.slot(rank), &P.v_ld, p.full(), 0, kvrow + ch * 128 + rank * 64, 0);
            }
            p.advance(2);
            if (t == 1 && i == 4 && !is_s) wait_flag(&fl->h[rb][0], ep1 * 48);
          }
        }
        const int jn = j & 3;
        if (is_s) {
          unsigned ready = 0;
#pragma unroll 1
          for (int i = 0; i < 64; i++) {
            const int hi = i >> 1;
            const int head = 4 * ((hi & 15) >> 1) + (hi & 1) + ((hi >> 4) << 1);
            const int kc = head * 128 + (i & 1) * 64;
            p.acquire(3);
            if (lane == 0) { mbar_expect_tx(p.full(), 49152); LDW(p.slot(1 + rank), &P.wo, p.full(), 0, kc + rank * 32, jn * 4); }
            if (!((ready >> head) & 1)) {
              do { ready = __ballot_sync(~0u, (int)(ld_acquire(&fl->o[rb][lane]) - ep1 * 2) >= 0); } while (!((ready >> head) & 1));
              __syncwarp();
              fence_async_all();
            }
            if (lane == 0) LDA(p.slot(0), &P.act_ld, p.full(), C_O + kc, row0);
            if (i == 52) {
              if (lane == 0) { prefetch_map(&P.x_ld); prefetch_map(&P.out_st); }
              if (lane < 4) tma_pf2(&P.x_ld, jn * 256 + lane * 64, row0);
            }
            p.advance(3);
          }
#pragma unroll 1
          for (int i = 0; i < 2; i++) {
            p.acquire(2);
            if (lane == 0) {
              mbar_expect_tx(p.full(), 32768);
              tma_ld2(p.slot(0), &P.x_ld, p.full(), jn * 256 + i * 128, row0);
              tma_ld2(p.slot(1), &P.x_ld, p.full(), jn * 256 + i * 128 + 64, row0);
            }
            p.advance(2);
          }
        } else {
#pragma unroll 1
          for (int k = 0; k < 56; k++) {
            p.acquire(3);
            if (lane == 0) { mbar_expect_tx(p.full(), 49152); LDW(p.slot(1 + rank), &P.w2, p.full(), 0, k * 64 + rank * 32, jn * 4); }
            if (k == H_SPARE0 / 64) wait_flag(&fl->h[rb][16], ep1 * 8);
            if (lane == 0) LDA(p.slot(0), &P.act_ld, p.full(), C_H + k * 64, row0);
            p.advance(3);
          }
        }
      }
      if (lane == 0) { *(volatile unsigned*)&fl->epoch[blockIdx.x] = ep1; mbar_arrive(sb + SM_BAR + B_DONE); }
    } else if (warp < 11) {
      const int wg = warp - 9;
      if (lane == 0) {
        const uint32_t stg = sb + SM_STG + wg * 16384;
        const int nev = spare ? 16 : 7;
#pragma unroll 1
        for (int n = 0; n < nev; n++) {
          int col, row = row0;
          unsigned* flag;
          if (spare) {
            const int r = ((cl & 1) * 4 + (n >> 2)) * 2 + rank;
            row = r * 128;
            col = C_H + H_SPARE0 + (n & 3) * 128;
            flag = &fl->h[r][16];
          } else if (n < 3) {
            col = C_H + j * H_REG + n * 128;
            flag = &fl->h[rb][0];
          } else {
            col = C_O + (4 * j + n - 3) * 128;
            flag = &fl->o[rb][4 * j + n - 3];
          }
          mbar_wait(sb + SM_BAR + B_SFULL + wg * 8, n & 1);
          tma_st2(&P.act_st, stg, col, row + wg * 64);
          tma_st2(&P.act_st, stg + 8192, col + 64, row + wg * 64);
          bulk_commit();
          bulk_wait_read0();
          mbar_arrive(sb + SM_BAR + B_SEMPTY + wg * 8);
          bulk_wait0();
          red_release(flag, 1);
        }
        mbar_arrive(sb + SM_BAR + B_DONE);
      }
    } else {
      if (lane == 0) {
        const unsigned long long t0 = gtime();
        bool poll = is_s;
        while (!mbar_try(sb + SM_BAR + B_DONE, 0)) {
          if (poll && (int)(ld_acquire(&fl->g[rb][j & 3]) - (ep0 + 1) * 8) >= 0) {
            TSP(21);
            mbar_arrive(sb + SM_BAR + B_GRDY);
            poll = false;
          }
          if (gtime() - t0 > 2000000000ull) __trap();
        }
      }
    }
    __syncwarp();
    cluster_arrive();
    cluster_wait();
  } else {
    const int wg = warp >> 2;
    TS(0);
    if (!spare) {
      const int r = row0 + j * 16 + warp * 2;
      uint32_t v[2][16];
#pragma unroll
      for (int a = 0; a < 2; a++)
#pragma unroll
        for (int i = 0; i < 4; i++)
          *(uint4*)&v[a][4 * i] = __ldg((const uint4*)(P.x + (size_t)(r + a) * DM + i * 256 + lane * 8));
      if (lane == 0) init_barriers(sb, warp);
      __syncwarp();
      cluster_arrive();
      float s[2], q[2];
#pragma unroll
      for (int a = 0; a < 2; a++) {
        float t0 = 0.f, t1 = 0.f;
#pragma unroll
        for (int i = 0; i < 16; i++) { t0 += bf_lo(v[a][i]); t1 += bf_hi(v[a][i]); }
        s[a] = t0 + t1;
      }
#pragma unroll
      for (int o = 16; o; o >>= 1) { s[0] += __shfl_xor_sync(~0u, s[0], o); s[1] += __shfl_xor_sync(~0u, s[1], o); }
#pragma unroll
      for (int a = 0; a < 2; a++) {
        s[a] *= 1.0f / DM;
        float t0 = 0.f, t1 = 0.f;
#pragma unroll
        for (int i = 0; i < 16; i++) {
          const float d0 = bf_lo(v[a][i]) - s[a], d1 = bf_hi(v[a][i]) - s[a];
          t0 = fmaf(d0, d0, t0); t1 = fmaf(d1, d1, t1);
        }
        q[a] = t0 + t1;
      }
#pragma unroll
      for (int o = 16; o; o >>= 1) { q[0] += __shfl_xor_sync(~0u, q[0], o); q[1] += __shfl_xor_sync(~0u, q[1], o); }
#pragma unroll
      for (int a = 0; a < 2; a++) {
        const uint32_t mb2 = pack_bf16(s[a], s[a]);
        float sd;
        asm("sqrt.approx.ftz.f32 %0, %1;" : "=f"(sd) : "f"(bf_round(bf_round(q[a] * (1.0f / DM)) + 1e-5f)));
        const float inv = rcp(bf_round(sd));
        const float ih = bf_round(inv);
        const uint32_t ih2 = pack_bf16(ih, ih), il2 = pack_bf16(inv - ih, inv - ih);
#pragma unroll
        for (int i = 0; i < 16; i++) {
          const __nv_bfloat162 d = __hsub2_rn(*(const __nv_bfloat162*)&v[a][i], *(const __nv_bfloat162*)&mb2);
          const __nv_bfloat162 o = __hfma2(d, *(const __nv_bfloat162*)&ih2, __hmul2_rn(d, *(const __nv_bfloat162*)&il2));
          v[a][i] = *(const uint32_t*)&o;
        }
#pragma unroll
        for (int i = 0; i < 4; i++)
          sts128(sb + SM_STG + warp * 4096 + a * 2048 + i * 512 + lane * 16, v[a][4 * i], v[a][4 * i + 1], v[a][4 * i + 2], v[a][4 * i + 3]);
      }
      TS(11);
      fence_async_smem();
      __syncwarp();
      if (lane == 0) {
#pragma unroll
        for (int a = 0; a < 2; a++)
          asm volatile("cp.async.bulk.global.shared::cta.bulk_group [%0], [%1], 2048;"
                       ::"l"(P.act + (size_t)(r + a) * ACT_W + C_XN), "r"(sb + SM_STG + warp * 4096 + a * 2048) : "memory");
        bulk_commit();
        bulk_wait0();
        TS(12);
        red_release(&fl->ln[rb][0], 1);
      }
      __syncwarp();
      TS(13);
    } else {
      if (lane == 0) init_barriers(sb, warp);
      __syncwarp();
      cluster_arrive();
    }
    cluster_wait();
    asm volatile("setmaxnreg.inc.sync.aligned.u32 240;");
    Cons c;
    c.zero = blockIdx.y; c.sb = sb; c.g = 0; c.pos = 0; c.nstg = 0; c.wg = wg; c.lane = lane;
    c.rel = mapa(sb + SM_BAR + B_EMPTY, lane & 1);
    float acc[128];
    TS(1);
    if (spare) {
      uint32_t pend[32];
#pragma unroll
      for (int i = 0; i < 32; i++) pend[i] = 0;
#pragma unroll 1
      for (int t = 0; t < 8; t++) {
        gemm_loop_flush<1>(acc, c, pend, t > 0);
        uint32_t r[32];
#pragma unroll
        for (int i = 0; i < 32; i++) r[i] = pack_bf16_relu(acc[2 * i], acc[2 * i + 1]);
        c.stg_acquire();
        stage_boxes<2>(r, 0, c);
#pragma unroll
        for (int i = 0; i < 32; i++) pend[i] = pack_bf16_relu(acc[64 + 2 * i], acc[65 + 2 * i]);
      }
      c.stg_acquire();
      stage_boxes<2>(pend, 0, c);
      TS(6);
    } else {
      if (wg == 1) bar_arrive(1, 256);
      {
        float h0[96], h1[96];
        h_step<true>(h0, h1, c);
#pragma unroll 1
        for (int k = 1; k < 16; k++) h_step<false>(h0, h1, c);
        wg_wait<0>();
        c.release(c.g - 1);
        fence_regs(h0);
        fence_regs(h1);
        TS(2);
        uint32_t r[32], pend[64];
#pragma unroll
        for (int i = 0; i < 32; i++) r[i] = pack_bf16_relu(h0[2 * i], h0[2 * i + 1]);
        c.stg_acquire();
        stage_boxes<2>(r, 0, c);
#pragma unroll
        for (int i = 0; i < 16; i++) pend[i] = pack_bf16_relu(h0[64 + 2 * i], h0[65 + 2 * i]);
#pragma unroll
        for (int i = 0; i < 48; i++) pend[16 + i] = pack_bf16_relu(h1[2 * i], h1[2 * i + 1]);
        fence_regs(pend);
        TS(3);
        gemm_loop_flush<2>(acc, c, pend, true);
      }
#pragma unroll 1
      for (int t = 0;; t++) {
        TS(8 + t);
        attn_tile(acc, c, t);
        TS(4 + t);
        if (t == 1) break;
        gemm_body(acc, c, 16);
        gemm_drain(acc, c);
      }
      uint4* gate = P.gate + (rb * 4 + (j & 3)) * 4096 + threadIdx.x;
      if (is_s) {
        gemm_body(acc, c, 63);
        mbar_wait(sb + SM_BAR + B_GRDY, 0);
        uint32_t gv[64];
#pragma unroll
        for (int i = 0; i < 16; i++) *(uint4*)&gv[4 * i] = __ldcg(gate + i * 256);
        gemm_step<false>(acc, c);
        gemm_drain(acc, c);
        TS(6);
        uint32_t rowoff, xr;
        frag_addr(rowoff, xr);
#pragma unroll
        for (int b = 0; b < 4; b++) {
          if ((b & 1) == 0) c.wait_full(c.g + (b >> 1));
          if (b == 0) TS(22);
          if (b == 2) TS(23);
          const uint32_t xs = sb + wrap12(c.pos + b) * SLOT + wg * 8192;
          uint32_t xv[16];
#pragma unroll
          for (int kb = 0; kb < 4; kb++) ldsm4(xs + rowoff + ((32 * kb) ^ xr), xv[4 * kb], xv[4 * kb + 1], xv[4 * kb + 2], xv[4 * kb + 3]);
#pragma unroll
          for (int i = 0; i < 16; i++) {
            const uint32_t s2 = pack_bf16(acc[32 * b + 2 * i], acc[32 * b + 2 * i + 1]);
            const __nv_bfloat162 pr = __hmul2_rn(*(const __nv_bfloat162*)&s2, *(const __nv_bfloat162*)&gv[16 * b + i]);
            const __nv_bfloat162 o = __hadd2_rn(*(const __nv_bfloat162*)&xv[i], pr);
            xv[i] = *(const uint32_t*)&o;
          }
#pragma unroll
          for (int kb = 0; kb < 4; kb++) stsm4(xs + rowoff + ((32 * kb) ^ xr), xv[4 * kb], xv[4 * kb + 1], xv[4 * kb + 2], xv[4 * kb + 3]);
          fence_async_smem();
          __syncwarp();
          if (lane == 0) {
            tma_st2(&P.out_st, xs + (warp & 3) * 2048, (j & 3) * 256 + b * 64, row0 + warp * 16);
            bulk_commit();
          }
        }
        TS(24);
        if (lane == 0) bulk_wait_read0();
      } else {
        gemm_body(acc, c, 56);
        gemm_drain(acc, c);
        TS(6);
#pragma unroll
        for (int bx = 0; bx < 4; bx++) {
          uint32_t r[16];
          ONCE(c) {
#pragma unroll
            for (int i = 0; i < 16; i++) r[i] = silu2(pack_bf16(acc[32 * bx + 2 * i], acc[32 * bx + 2 * i + 1]) ^ once_);
          }
#pragma unroll
          for (int i = 0; i < 4; i++) __stcg(gate + (4 * bx + i) * 256, *(const uint4*)&r[4 * i]);
          if (bx == 1) TS(22);
        }
        TS(23);
        __syncwarp();
        if (lane == 0) red_release(&fl->g[rb][j & 3], 1);
      }
    }
    TS(7);
    __syncwarp();
    if (lane == 0) mbar_arrive(sb + SM_BAR + B_DONE);
    cluster_arrive();
    cluster_wait();
  }
}

typedef CUresult (*EncodeFn)(CUtensorMap*, CUtensorMapDataType, cuuint32_t, void*, const cuuint64_t*, const cuuint64_t*,
                             const cuuint32_t*, const cuuint32_t*, CUtensorMapInterleave, CUtensorMapSwizzle,
                             CUtensorMapL2promotion, CUtensorMapFloatOOBfill);

void map2d(EncodeFn enc, CUtensorMap* m, const void* base, uint64_t cols, uint64_t rows, uint32_t box_rows) {
  cuuint64_t dims[2] = {cols, rows};
  cuuint64_t strides[1] = {cols * 2};
  cuuint32_t box[2] = {64, box_rows};
  cuuint32_t es[2] = {1, 1};
  enc(m, CU_TENSOR_MAP_DATA_TYPE_BFLOAT16, 2, (void*)base, dims, strides, box, es, CU_TENSOR_MAP_INTERLEAVE_NONE,
      CU_TENSOR_MAP_SWIZZLE_128B, CU_TENSOR_MAP_L2_PROMOTION_L2_256B, CU_TENSOR_MAP_FLOAT_OOB_FILL_NONE);
}
void map3d(EncodeFn enc, CUtensorMap* m, const void* base, uint64_t cols, uint64_t rows, uint32_t box_rows, uint32_t box_blks) {
  cuuint64_t dims[3] = {64, rows, cols / 64};
  cuuint64_t strides[2] = {cols * 2, 128};
  cuuint32_t box[3] = {64, box_rows, box_blks};
  cuuint32_t es[3] = {1, 1, 1};
  enc(m, CU_TENSOR_MAP_DATA_TYPE_BFLOAT16, 3, (void*)base, dims, strides, box, es, CU_TENSOR_MAP_INTERLEAVE_NONE,
      CU_TENSOR_MAP_SWIZZLE_128B, CU_TENSOR_MAP_L2_PROMOTION_L2_256B, CU_TENSOR_MAP_FLOAT_OOB_FILL_NONE);
}

}

extern "C" void kernel_launch(void* const* d_in, const int* in_sizes, int n_in, void* d_out, int out_size) {
  (void)in_sizes; (void)n_in; (void)out_size;
  static EncodeFn enc = nullptr;
  static void* act = nullptr;
  static void* flags = nullptr;
  static void* gate = nullptr;
  if (!enc) {
    void* fn = nullptr;
    cudaDriverEntryPointQueryResult qr;
    cudaGetDriverEntryPoint("cuTensorMapEncodeTiled", &fn, cudaEnableDefault, &qr);
    enc = (EncodeFn)fn;
    cudaGetSymbolAddress(&act, g_act);
    cudaGetSymbolAddress(&flags, g_flags);
    cudaGetSymbolAddress(&gate, g_gate);
    cudaFuncSetAttribute(fused_kernel, cudaFuncAttributeMaxDynamicSharedMemorySize, SMEM_BYTES);
  }
  Params P;
  map2d(enc, &P.act_ld, act, ACT_W, SEQ, 128);
  map2d(enc, &P.act_st, act, ACT_W, SEQ, 64);
  map2d(enc, &P.x_ld, d_in[0], DM, SEQ, 128);
  map2d(enc, &P.out_st, d_out, DM, SEQ, 16);
  map2d(enc, &P.k_ld, d_in[1], 128, 4 * SK, 128);
  map3d(enc, &P.v_ld, d_in[2], 128, 4 * SK, 64, 2);
  map3d(enc, &P.wq, d_in[3], NQ, DM, 32, 4);
  map3d(enc, &P.w1b4, d_in[6], DFF, DM, 32, 4);
  map3d(enc, &P.w1b3, d_in[6], DFF, DM, 64, 3);
  map3d(enc, &P.wo, d_in[4], DM, NQ, 32, 4);
  map3d(enc, &P.w2, d_in[7], DM, DFF, 32, 4);
  P.x = (const __nv_bfloat16*)d_in[0];
  P.act = (__nv_bfloat16*)act;
  P.gate = (uint4*)gate;
  P.flags = (Flags*)flags;
  fused_kernel<<<NCLUSTER * 2, 384, SMEM_BYTES>>>(P);
}
```
